```python
import torch

def _softmax(x, axis=-1):
    return torch.softmax(x, dim=axis)
def _gelu(x):
    return torch.nn.functional.gelu(x, approximate="tanh")
def _silu(x):
    return torch.nn.functional.silu(x)
def _sigmoid(x):
    return torch.sigmoid(x)
def _layernorm(x, axis=-1, eps=1e-5):
    m = x.mean(dim=axis, keepdim=True)
    v = x.var(dim=axis, keepdim=True, unbiased=False)
    return (x - m) / torch.sqrt(v + eps)
def _scatter_add(tgt, idx, src, axis=0):
    return tgt.clone().index_add_(axis, idx, src)
def _segment_sum(src, seg, n):
    out = torch.zeros((n,) + src.shape[1:], dtype=src.dtype)
    return out.index_add_(0, seg, src)
def _pad(x, pw):
    flat = tuple(v for pair in reversed(pw) for v in pair)
    return torch.nn.functional.pad(x, flat)

kernel_name = 'recurrent_scan__ssm_conv_h3__dense_activation_gelu__prompt'

def setup_inputs():

    _w = (lambda a: (lambda t: t.to(torch.bfloat16) if t.is_floating_point() else t)(torch.as_tensor(a)))
    def _A_setup():
        B, S, D = 1, 2048, 640
        ks = 4
        return {
            "q": _w((lambda *s: torch.randn(*s, dtype=torch.bfloat16) * 0.05)(B, S, D)),
            "k": _w((lambda *s: torch.randn(*s, dtype=torch.bfloat16) * 0.8)(B, S, D)),
            "v": _w((lambda *s: torch.randn(*s, dtype=torch.bfloat16) * 0.8)(B, S, D)),
            "shift_k": _w((lambda *s: torch.randn(*s, dtype=torch.bfloat16) * 0.8)(D, ks) * 0.5),
            "ssm_k": _w((lambda *s: torch.randn(*s, dtype=torch.bfloat16) * 0.8)(D, S) * (1.0 / S ** 0.5)),
            "ssm_D": _w((lambda *s: torch.randn(*s, dtype=torch.bfloat16) * 0.8)(D)),
        }
    _A_in = _A_setup()

    def _B_setup():
        B, S, D, F = 1, 2048, 640, 1728
        return {
            "x": _w((lambda *s: torch.randn(*s, dtype=torch.bfloat16) * 0.05)(B, S, D)),
            "w1": _w((lambda *s: torch.randn(*s, dtype=torch.bfloat16) * 0.2)(D, F) * (D ** -0.5)),
            "b1": _w((lambda *s: torch.randn(*s, dtype=torch.bfloat16) * 0.2)(F) * 0.01),
            "w2": _w((lambda *s: torch.randn(*s, dtype=torch.bfloat16) * 0.2)(F, D) * (F ** -0.5)),
            "b2": _w((lambda *s: torch.randn(*s, dtype=torch.bfloat16) * 0.2)(D) * 0.01),
        }
    _B_in = _B_setup()

    return {
        "A_q": _A_in["q"],
        "A_k": _A_in["k"],
        "A_v": _A_in["v"],
        "A_shift_k": _A_in["shift_k"],
        "A_ssm_k": _A_in["ssm_k"],
        "A_ssm_D": _A_in["ssm_D"],
        "B_x": _B_in["x"],
        "B_w1": _B_in["w1"],
        "B_b1": _B_in["b1"],
        "B_w2": _B_in["w2"],
        "B_b2": _B_in["b2"],
    }

def reference(A_q, A_k, A_v, A_shift_k, A_ssm_k, A_ssm_D, B_x, B_w1, B_b1, B_w2, B_b2):
    def _A_ref(q, k, v, shift_k, ssm_k, ssm_D):
        B, S, D = q.shape
        ks = shift_k.shape[-1]
        k_pad = _pad(k, ((0, 0), (ks - 1, 0), (0, 0)))
        k_shift = torch.zeros_like(k)
        for t in range(ks):
            k_shift = k_shift + k_pad[:, t:t + S, :] * shift_k[:, ks - 1 - t][None, None, :]
        kv = k_shift * v
        L = 2 * S
        kv_pad = _pad(kv, ((0, 0), (0, S), (0, 0)))
        kf_pad = _pad(ssm_k, ((0, 0), (0, S)))
        kv_f = (lambda x, axes=(-2,-1): torch.fft.rfft2(x.float(), dim=axes))(kv_pad[:, None, :, :], axes=(1, 2))
        kf_f = (lambda x, axes=(-2,-1): torch.fft.rfft2(x.float(), dim=axes))(kf_pad[:, None, :], axes=(1, 2))
        kf_f = (lambda x, *d: x.permute(*d))(kf_f, 1, 2, 0)
        y_f = kv_f * kf_f[None, :, :, :]
        y = (lambda x, s, axes=(-2,-1): torch.fft.irfft2(x, s=s, dim=axes).to(torch.bfloat16))(y_f, (1, L), axes=(1, 2))[:, 0, :S, :]
        y = y + kv * ssm_D[None, None, :]
        return q * y

    def _B_ref(x, w1, b1, w2, b2):
        h = torch.einsum("bsd,df->bsf", x, w1) + b1
        h = _gelu(h)
        return torch.einsum("bsf,fd->bsd", h, w2) + b2

    x = A_q
    xn = _layernorm(x, axis=-1)
    s = _A_ref(xn, A_k, A_v, A_shift_k, A_ssm_k, A_ssm_D)
    g = _silu(_B_ref(xn, B_w1, B_b1, B_w2, B_b2))
    return x + s * g
```

```cpp
#include <cuda_runtime.h>
#include <cuda_bf16.h>
#include <cuda.h>
#include <stdint.h>

#define INIT_SEQ S(1) S(2) S(3) K(0) K(1) T
#define AUX_PRE
#define AUX_SEQ AUX_PRE W(B_KVS) PUBA W(B_STATFREE) KC F(0) PF(1) G(0) X(0) PF(2) PF(3) PUBB F(1) X(1) FLB PF(4) PW PUBC F(2) FLC W(B_G1FREE) F(3) G(1) X(3) X(2) G(2) Y(0) R X(4) F(4) Y(1) Y(2) Y(3) R XE Y(4)
#define CH_W0 0xf2
#define CH_W1 0xf3
#define CH_W2 0xf410
#define CS_KB 5
#define CHK 3
#define SK2 2
#define YK 26
#define DFT_AT 16
#define USE_GO 1
#define GO_AT 2
#define HS_LAG 0
#define LOOKAHEAD 2
#define SPLIT9 0
#define GELU_BF16 4
#define R_G 160
#define R_P 32
#define DBG_TIME 0

namespace {

constexpr int S_ = 2048, D_ = 640, F_ = 1728;
constexpr int NCTA = 132;
typedef __nv_bfloat16 bf16;

__device__ __align__(1024) bf16 g_h[S_ * F_];
__device__ __align__(1024) bf16 g_kvZ[D_ * S_];
__device__ __align__(1024) bf16 g_yT[D_ * S_];
__device__ __align__(128) uint2 g_stats[S_];
constexpr int CSP = F_ / 2 + 32;
__device__ __align__(128) uint2 g_cs[2 * CSP];
constexpr int FL_EPOCH = 0, FL_START = 32, FL_KV = 64  , FL_Y = FL_KV + 3 * 32, FL_H = FL_Y + 32  , FL_G2 = FL_H + 96 * 32  , FL_COUNT = FL_G2 + 9 * 32;
__device__ __align__(128) unsigned g_flags[FL_COUNT];
__device__ __align__(128) const uint32_t g_tab[6144] = {
0x3f803f80,0x3f803f80,0x3f803f80,0x3f803f80,0x3f803f80,0x3f803f80,0x3f803f80,0x3f803f80,0x3f803f80,0x3f803f80,0x3f803f80,0x3f803f80,0x3f803f80,0x3f803f80,0x3f803f80,0x3f803f80,
0x0,0x0,0x0,0x0,0x0,0x0,0x0,0x0,0x0,0x0,0x0,0x0,0x0,0x0,0x0,0x0,
0x3f183f2c,0x3edb3f04,0x3e793eac,0x3d493e16,0x3f7d3f80,0x3f713f78,0x3f5c3f67,0x3f3e3f4e,0xbf4ebf3e,0xbf67bf5c,0xbf78bf71,0xbf80bf7d,0xbe16bd49,0xbeacbe79,0xbf04bedb,0xbf2cbf18,
0x3f4e3f3e,0x3f673f5c,0x3f783f71,0x3f803f7d,0x3e163d49,0x3eac3e79,0x3f043edb,0x3f2c3f18,0x3f183f2c,0x3edb3f04,0x3e793eac,0x3d493e16,0x3f7d3f80,0x3f713f78,0x3f5c3f67,0x3f3e3f4e,
0xbf75bf7f,0xbf46bf62,0xbef1bf22,0xbdc9be95,0x3e953dc9,0x3f223ef1,0x3f623f46,0x3f7f3f75,0x3f753f7f,0x3f463f62,0x3ef13f22,0x3dc93e95,0xbe95bdc9,0xbf22bef1,0xbf62bf46,0xbf7fbf75,
0xbe95bdc9,0xbf22bef1,0xbf62bf46,0xbf7fbf75,0xbf75bf7f,0xbf46bf62,0xbef1bf22,0xbdc9be95,0x3e953dc9,0x3f223ef1,0x3f623f46,0x3f7f3f75,0x3f753f7f,0x3f463f62,0x3ef13f22,0x3dc93e95,
0x3eac3f18,0xbe793d49,0xbf3ebf04,0xbf7dbf67,0x3edb3e16,0x3f5c3f2c,0x3f803f78,0x3f4e3f71,0xbf71bf4e,0xbf78bf80,0xbf2cbf5c,0xbe16bedb,0x3f673f7d,0x3f043f3e,0xbd493e79,0xbf18beac,
0x3f713f4e,0x3f783f80,0x3f2c3f5c,0x3e163edb,0xbf67bf7d,0xbf04bf3e,0x3d49be79,0x3f183eac,0x3eac3f18,0xbe793d49,0xbf3ebf04,0xbf7dbf67,0x3edb3e16,0x3f5c3f2c,0x3f803f78,0x3f4e3f71,
0x3f0e3e48,0x3f7b3f55,0x3f553f7b,0x3e483f0e,0xbf0ebe48,0xbf7bbf55,0xbf55bf7b,0xbe48bf0e,0x3f0e3e48,0x3f7b3f55,0x3f553f7b,0x3e483f0e,0xbf0ebe48,0xbf7bbf55,0xbf55bf7b,0xbe48bf0e,
0x3f553f7b,0x3e483f0e,0xbf0ebe48,0xbf7bbf55,0xbf55bf7b,0xbe48bf0e,0x3f0e3e48,0x3f7b3f55,0x3f553f7b,0x3e483f0e,0xbf0ebe48,0xbf7bbf55,0xbf55bf7b,0xbe48bf0e,0x3f0e3e48,0x3f7b3f55,
0xbf80bf5c,0xbf18bf67,0x3eacbe16,0x3f783f3e,0x3f2c3e79,0x3f7d3f71,0x3edb3f4e,0xbf04bd49,0xbd49bf04,0x3f4e3edb,0x3f713f7d,0x3e793f2c,0x3f3e3f78,0xbe163eac,0xbf67bf18,0xbf5cbf80,
0xbd49bf04,0x3f4e3edb,0x3f713f7d,0x3e793f2c,0x3f3e3f78,0xbe163eac,0xbf67bf18,0xbf5cbf80,0x3f803f5c,0x3f183f67,0xbeac3e16,0xbf78bf3e,0xbf2cbe79,0xbf7dbf71,0xbedbbf4e,0x3f043d49,
0xbf46be95,0xbf62bf7f,0x3dc9bef1,0x3f753f22,0x3f223f75,0xbef13dc9,0xbf7fbf62,0xbe95bf46,0x3f463e95,0x3f623f7f,0xbdc93ef1,0xbf75bf22,0xbf22bf75,0x3ef1bdc9,0x3f7f3f62,0x3e953f46,
0xbf22bf75,0x3ef1bdc9,0x3f7f3f62,0x3e953f46,0xbf46be95,0xbf62bf7f,0x3dc9bef1,0x3f753f22,0x3f223f75,0xbef13dc9,0xbf7fbf62,0xbe95bf46,0x3f463e95,0x3f623f7f,0xbdc93ef1,0xbf75bf22,
0xbf78bf67,0x3d49bf18,0x3f7d3f2c,0x3eac3f5c,0xbf04bf71,0x3f3e3e16,0x3f4e3f80,0xbedb3e79,0x3e79bedb,0x3f803f4e,0x3e163f3e,0xbf71bf04,0x3f5c3eac,0x3f2c3f7d,0xbf183d49,0xbf67bf78,
0x3e79bedb,0x3f803f4e,0x3e163f3e,0xbf71bf04,0x3f5c3eac,0x3f2c3f7d,0xbf183d49,0xbf67bf78,0x3f783f67,0xbd493f18,0xbf7dbf2c,0xbeacbf5c,0x3f043f71,0xbf3ebe16,0xbf4ebf80,0x3edbbe79,
0x3ec43f6d,0xbf6dbec4,0xbec4bf6d,0x3f6d3ec4,0x3ec43f6d,0xbf6dbec4,0xbec4bf6d,0x3f6d3ec4,0x3ec43f6d,0xbf6dbec4,0xbec4bf6d,0x3f6d3ec4,0x3ec43f6d,0xbf6dbec4,0xbec4bf6d,0x3f6d3ec4,
0x3f6d3ec4,0x3ec43f6d,0xbf6dbec4,0xbec4bf6d,0x3f6d3ec4,0x3ec43f6d,0xbf6dbec4,0xbec4bf6d,0x3f6d3ec4,0x3ec43f6d,0xbf6dbec4,0xbec4bf6d,0x3f6d3ec4,0x3ec43f6d,0xbf6dbec4,0xbec4bf6d,
0xbf043eac,0xbf3ebf7d,0x3f4e3d49,0x3edb3f78,0x3e793f67,0xbf80bf18,0x3e16bf2c,0x3f713f5c,0xbf5cbf71,0x3f2cbe16,0x3f183f80,0xbf67be79,0xbf78bedb,0xbd49bf4e,0x3f7d3f3e,0xbeac3f04,
0x3f5c3f71,0xbf2c3e16,0xbf18bf80,0x3f673e79,0x3f783edb,0x3d493f4e,0xbf7dbf3e,0x3eacbf04,0xbf043eac,0xbf3ebf7d,0x3f4e3d49,0x3edb3f78,0x3e793f67,0xbf80bf18,0x3e16bf2c,0x3f713f5c,
0xbdc9bf62,0x3f753f46,0xbf223e95,0xbef1bf7f,0x3f7f3ef1,0xbe953f22,0xbf46bf75,0x3f623dc9,0x3dc93f62,0xbf75bf46,0x3f22be95,0x3ef13f7f,0xbf7fbef1,0x3e95bf22,0x3f463f75,0xbf62bdc9,
0xbf7fbef1,0x3e95bf22,0x3f463f75,0xbf62bdc9,0xbdc9bf62,0x3f753f46,0xbf223e95,0xbef1bf7f,0x3f7f3ef1,0xbe953f22,0xbf46bf75,0x3f623dc9,0x3dc93f62,0xbf75bf46,0x3f22be95,0x3ef13f7f,
0xbf3e3e79,0xbe16bf71,0x3f673f4e,0xbf5c3d49,0x3f803f04,0xbf183edb,0xbeacbf7d,0x3f783f2c,0xbf2cbf78,0x3f7d3eac,0xbedb3f18,0xbf04bf80,0xbd493f5c,0xbf4ebf67,0x3f713e16,0xbe793f3e,
0x3f2c3f78,0xbf7dbeac,0x3edbbf18,0x3f043f80,0x3d49bf5c,0x3f4e3f67,0xbf71be16,0x3e79bf3e,0xbf3e3e79,0xbe16bf71,0x3f673f4e,0xbf5c3d49,0x3f803f04,0xbf183edb,0xbeacbf7d,0x3f783f2c,
0x3f7b3f0e,0xbf553e48,0x3e48bf55,0x3f0e3f7b,0xbf7bbf0e,0x3f55be48,0xbe483f55,0xbf0ebf7b,0x3f7b3f0e,0xbf553e48,0x3e48bf55,0x3f0e3f7b,0xbf7bbf0e,0x3f55be48,0xbe483f55,0xbf0ebf7b,
0xbe483f55,0xbf0ebf7b,0x3f7b3f0e,0xbf553e48,0x3e48bf55,0x3f0e3f7b,0xbf7bbf0e,0x3f55be48,0xbe483f55,0xbf0ebf7b,0x3f7b3f0e,0xbf553e48,0x3e48bf55,0x3f0e3f7b,0xbf7bbf0e,0x3f55be48,
0xbedbbf7d,0x3f5c3f3e,0xbf80be79,0x3f4ebeac,0x3f713f18,0xbf78bd49,0x3f2cbf04,0xbe163f67,0x3f67be16,0xbf043f2c,0xbd49bf78,0x3f183f71,0xbeac3f4e,0xbe79bf80,0x3f3e3f5c,0xbf7dbedb,
0x3f67be16,0xbf043f2c,0xbd49bf78,0x3f183f71,0xbeac3f4e,0xbe79bf80,0x3f3e3f5c,0xbf7dbedb,0x3edb3f7d,0xbf5cbf3e,0x3f803e79,0xbf4e3eac,0xbf71bf18,0x3f783d49,0xbf2c3f04,0x3e16bf67,
0xbf62bf22,0x3f7f3e95,0xbf753dc9,0x3f46bef1,0xbef13f46,0x3dc9bf75,0x3e953f7f,0xbf22bf62,0x3f623f22,0xbf7fbe95,0x3f75bdc9,0xbf463ef1,0x3ef1bf46,0xbdc93f75,0xbe95bf7f,0x3f223f62,
0x3ef1bf46,0xbdc93f75,0xbe95bf7f,0x3f223f62,0xbf62bf22,0x3f7f3e95,0xbf753dc9,0x3f46bef1,0xbef13f46,0x3dc9bf75,0x3e953f7f,0xbf22bf62,0x3f623f22,0xbf7fbe95,0x3f75bdc9,0xbf463ef1,
0xbe16bf80,0x3eac3f78,0xbf04bf67,0x3f2c3f4e,0x3f18bf3e,0xbedb3f5c,0x3e79bf71,0xbd493f7d,0x3f7dbd49,0xbf713e79,0x3f5cbedb,0xbf3e3f18,0x3f4e3f2c,0xbf67bf04,0x3f783eac,0xbf80be16,
0x3f7dbd49,0xbf713e79,0x3f5cbedb,0xbf3e3f18,0x3f4e3f2c,0xbf67bf04,0x3f783eac,0xbf80be16,0x3e163f80,0xbeacbf78,0x3f043f67,0xbf2cbf4e,0xbf183f3e,0x3edbbf5c,0xbe793f71,0x3d49bf7d,
0xbf353f35,0x3f35bf35,0xbf353f35,0x3f35bf35,0xbf353f35,0x3f35bf35,0xbf353f35,0x3f35bf35,0xbf353f35,0x3f35bf35,0xbf353f35,0x3f35bf35,0xbf353f35,0x3f35bf35,0xbf353f35,0x3f35bf35,
0x3f353f35,0xbf35bf35,0x3f353f35,0xbf35bf35,0x3f353f35,0xbf35bf35,0x3f353f35,0xbf35bf35,0x3f353f35,0xbf35bf35,0x3f353f35,0xbf35bf35,0x3f353f35,0xbf35bf35,0x3f353f35,0xbf35bf35,
0xbf7dbd49,0x3f713e79,0xbf5cbedb,0x3f3e3f18,0xbf4e3f2c,0x3f67bf04,0xbf783eac,0x3f80be16,0x3e16bf80,0xbeac3f78,0x3f04bf67,0xbf2c3f4e,0xbf18bf3e,0x3edb3f5c,0xbe79bf71,0x3d493f7d,
0xbe163f80,0x3eacbf78,0xbf043f67,0x3f2cbf4e,0x3f183f3e,0xbedbbf5c,0x3e793f71,0xbd49bf7d,0xbf7dbd49,0x3f713e79,0xbf5cbedb,0x3f3e3f18,0xbf4e3f2c,0x3f67bf04,0xbf783eac,0x3f80be16,
0x3f62bf22,0xbf7f3e95,0x3f753dc9,0xbf46bef1,0x3ef13f46,0xbdc9bf75,0xbe953f7f,0x3f22bf62,0xbf623f22,0x3f7fbe95,0xbf75bdc9,0x3f463ef1,0xbef1bf46,0x3dc93f75,0x3e95bf7f,0xbf223f62,
0xbef1bf46,0x3dc93f75,0x3e95bf7f,0xbf223f62,0x3f62bf22,0xbf7f3e95,0x3f753dc9,0xbf46bef1,0x3ef13f46,0xbdc9bf75,0xbe953f7f,0x3f22bf62,0xbf623f22,0x3f7fbe95,0xbf75bdc9,0x3f463ef1,
0xbf67be16,0x3f043f2c,0x3d49bf78,0xbf183f71,0x3eac3f4e,0x3e79bf80,0xbf3e3f5c,0x3f7dbedb,0x3edbbf7d,0xbf5c3f3e,0x3f80be79,0xbf4ebeac,0xbf713f18,0x3f78bd49,0xbf2cbf04,0x3e163f67,
0xbedb3f7d,0x3f5cbf3e,0xbf803e79,0x3f4e3eac,0x3f71bf18,0xbf783d49,0x3f2c3f04,0xbe16bf67,0xbf67be16,0x3f043f2c,0x3d49bf78,0xbf183f71,0x3eac3f4e,0x3e79bf80,0xbf3e3f5c,0x3f7dbedb,
0x3e483f55,0x3f0ebf7b,0xbf7b3f0e,0x3f553e48,0xbe48bf55,0xbf0e3f7b,0x3f7bbf0e,0xbf55be48,0x3e483f55,0x3f0ebf7b,0xbf7b3f0e,0x3f553e48,0xbe48bf55,0xbf0e3f7b,0x3f7bbf0e,0xbf55be48,
0xbf7b3f0e,0x3f553e48,0xbe48bf55,0xbf0e3f7b,0x3f7bbf0e,0xbf55be48,0x3e483f55,0x3f0ebf7b,0xbf7b3f0e,0x3f553e48,0xbe48bf55,0xbf0e3f7b,0x3f7bbf0e,0xbf55be48,0x3e483f55,0x3f0ebf7b,
0x3f2cbf78,0xbf7d3eac,0x3edb3f18,0x3f04bf80,0x3d493f5c,0x3f4ebf67,0xbf713e16,0x3e793f3e,0x3f3e3e79,0x3e16bf71,0xbf673f4e,0x3f5c3d49,0xbf803f04,0x3f183edb,0x3eacbf7d,0xbf783f2c,
0x3f3e3e79,0x3e16bf71,0xbf673f4e,0x3f5c3d49,0xbf803f04,0x3f183edb,0x3eacbf7d,0xbf783f2c,0xbf2c3f78,0x3f7dbeac,0xbedbbf18,0xbf043f80,0xbd49bf5c,0xbf4e3f67,0x3f71be16,0xbe79bf3e,
0x3dc9bf62,0xbf753f46,0x3f223e95,0x3ef1bf7f,0xbf7f3ef1,0x3e953f22,0x3f46bf75,0xbf623dc9,0xbdc93f62,0x3f75bf46,0xbf22be95,0xbef13f7f,0x3f7fbef1,0xbe95bf22,0xbf463f75,0x3f62bdc9,
0x3f7fbef1,0xbe95bf22,0xbf463f75,0x3f62bdc9,0x3dc9bf62,0xbf753f46,0x3f223e95,0x3ef1bf7f,0xbf7f3ef1,0x3e953f22,0x3f46bf75,0xbf623dc9,0xbdc93f62,0x3f75bf46,0xbf22be95,0xbef13f7f,
0x3f5cbf71,0xbf2cbe16,0xbf183f80,0x3f67be79,0x3f78bedb,0x3d49bf4e,0xbf7d3f3e,0x3eac3f04,0x3f043eac,0x3f3ebf7d,0xbf4e3d49,0xbedb3f78,0xbe793f67,0x3f80bf18,0xbe16bf2c,0xbf713f5c,
0x3f043eac,0x3f3ebf7d,0xbf4e3d49,0xbedb3f78,0xbe793f67,0x3f80bf18,0xbe16bf2c,0xbf713f5c,0xbf5c3f71,0x3f2c3e16,0x3f18bf80,0xbf673e79,0xbf783edb,0xbd493f4e,0x3f7dbf3e,0xbeacbf04,
0xbf6d3ec4,0xbec43f6d,0x3f6dbec4,0x3ec4bf6d,0xbf6d3ec4,0xbec43f6d,0x3f6dbec4,0x3ec4bf6d,0xbf6d3ec4,0xbec43f6d,0x3f6dbec4,0x3ec4bf6d,0xbf6d3ec4,0xbec43f6d,0x3f6dbec4,0x3ec4bf6d,
0xbec43f6d,0x3f6dbec4,0x3ec4bf6d,0xbf6d3ec4,0xbec43f6d,0x3f6dbec4,0x3ec4bf6d,0xbf6d3ec4,0xbec43f6d,0x3f6dbec4,0x3ec4bf6d,0xbf6d3ec4,0xbec43f6d,0x3f6dbec4,0x3ec4bf6d,0xbf6d3ec4,
0xbe79bedb,0xbf803f4e,0xbe163f3e,0x3f71bf04,0xbf5c3eac,0xbf2c3f7d,0x3f183d49,0x3f67bf78,0x3f78bf67,0xbd49bf18,0xbf7d3f2c,0xbeac3f5c,0x3f04bf71,0xbf3e3e16,0xbf4e3f80,0x3edb3e79,
0xbf783f67,0x3d493f18,0x3f7dbf2c,0x3eacbf5c,0xbf043f71,0x3f3ebe16,0x3f4ebf80,0xbedbbe79,0xbe79bedb,0xbf803f4e,0xbe163f3e,0x3f71bf04,0xbf5c3eac,0xbf2c3f7d,0x3f183d49,0x3f67bf78,
0x3f46be95,0x3f62bf7f,0xbdc9bef1,0xbf753f22,0xbf223f75,0x3ef13dc9,0x3f7fbf62,0x3e95bf46,0xbf463e95,0xbf623f7f,0x3dc93ef1,0x3f75bf22,0x3f22bf75,0xbef1bdc9,0xbf7f3f62,0xbe953f46,
0x3f22bf75,0xbef1bdc9,0xbf7f3f62,0xbe953f46,0x3f46be95,0x3f62bf7f,0xbdc9bef1,0xbf753f22,0xbf223f75,0x3ef13dc9,0x3f7fbf62,0x3e95bf46,0xbf463e95,0xbf623f7f,0x3dc93ef1,0x3f75bf22,
0x3d49bf04,0xbf4e3edb,0xbf713f7d,0xbe793f2c,0xbf3e3f78,0x3e163eac,0x3f67bf18,0x3f5cbf80,0x3f80bf5c,0x3f18bf67,0xbeacbe16,0xbf783f3e,0xbf2c3e79,0xbf7d3f71,0xbedb3f4e,0x3f04bd49,
0xbf803f5c,0xbf183f67,0x3eac3e16,0x3f78bf3e,0x3f2cbe79,0x3f7dbf71,0x3edbbf4e,0xbf043d49,0x3d49bf04,0xbf4e3edb,0xbf713f7d,0xbe793f2c,0xbf3e3f78,0x3e163eac,0x3f67bf18,0x3f5cbf80,
0xbf553f7b,0xbe483f0e,0x3f0ebe48,0x3f7bbf55,0x3f55bf7b,0x3e48bf0e,0xbf0e3e48,0xbf7b3f55,0xbf553f7b,0xbe483f0e,0x3f0ebe48,0x3f7bbf55,0x3f55bf7b,0x3e48bf0e,0xbf0e3e48,0xbf7b3f55,
0xbf0e3e48,0xbf7b3f55,0xbf553f7b,0xbe483f0e,0x3f0ebe48,0x3f7bbf55,0x3f55bf7b,0x3e48bf0e,0xbf0e3e48,0xbf7b3f55,0xbf553f7b,0xbe483f0e,0x3f0ebe48,0x3f7bbf55,0x3f55bf7b,0x3e48bf0e,
0x3f71bf4e,0x3f78bf80,0x3f2cbf5c,0x3e16bedb,0xbf673f7d,0xbf043f3e,0x3d493e79,0x3f18beac,0xbeac3f18,0x3e793d49,0x3f3ebf04,0x3f7dbf67,0xbedb3e16,0xbf5c3f2c,0xbf803f78,0xbf4e3f71,
0xbeac3f18,0x3e793d49,0x3f3ebf04,0x3f7dbf67,0xbedb3e16,0xbf5c3f2c,0xbf803f78,0xbf4e3f71,0xbf713f4e,0xbf783f80,0xbf2c3f5c,0xbe163edb,0x3f67bf7d,0x3f04bf3e,0xbd49be79,0xbf183eac,
0x3f75bf7f,0x3f46bf62,0x3ef1bf22,0x3dc9be95,0xbe953dc9,0xbf223ef1,0xbf623f46,0xbf7f3f75,0xbf753f7f,0xbf463f62,0xbef13f22,0xbdc93e95,0x3e95bdc9,0x3f22bef1,0x3f62bf46,0x3f7fbf75,
0x3e95bdc9,0x3f22bef1,0x3f62bf46,0x3f7fbf75,0x3f75bf7f,0x3f46bf62,0x3ef1bf22,0x3dc9be95,0xbe953dc9,0xbf223ef1,0xbf623f46,0xbf7f3f75,0xbf753f7f,0xbf463f62,0xbef13f22,0xbdc93e95,
0x3f4ebf3e,0x3f67bf5c,0x3f78bf71,0x3f80bf7d,0x3e16bd49,0x3eacbe79,0x3f04bedb,0x3f2cbf18,0xbf183f2c,0xbedb3f04,0xbe793eac,0xbd493e16,0xbf7d3f80,0xbf713f78,0xbf5c3f67,0xbf3e3f4e,
0xbf183f2c,0xbedb3f04,0xbe793eac,0xbd493e16,0xbf7d3f80,0xbf713f78,0xbf5c3f67,0xbf3e3f4e,0xbf4e3f3e,0xbf673f5c,0xbf783f71,0xbf803f7d,0xbe163d49,0xbeac3e79,0xbf043edb,0xbf2c3f18,
0xa554248d,0xa5f725b0,0xa731261f,0xa742a68d,0xa754a654,0xa765a60d,0xa777a58e,0xa784a137,0xa78d258d,0xa796260d,0xa79f280d,0x2731268d,0xa7b12816,0x270d26d4,0xa7c2281f,0x26d4270d,
0xbf803f80,0xbf803f80,0xbf803f80,0xbf803f80,0xbf803f80,0xbf803f80,0xbf803f80,0xbf803f80,0xbf803f80,0xbf803f80,0xbf803f80,0xbf803f80,0xbf803f80,0xbf803f80,0xbf803f80,0xbf803f80,
0x3f4ebf3e,0x3f67bf5c,0x3f78bf71,0x3f80bf7d,0x3e16bd49,0x3eacbe79,0x3f04bedb,0x3f2cbf18,0x3f18bf2c,0x3edbbf04,0x3e79beac,0x3d49be16,0x3f7dbf80,0x3f71bf78,0x3f5cbf67,0x3f3ebf4e,
0xbf183f2c,0xbedb3f04,0xbe793eac,0xbd493e16,0xbf7d3f80,0xbf713f78,0xbf5c3f67,0xbf3e3f4e,0x3f4ebf3e,0x3f67bf5c,0x3f78bf71,0x3f80bf7d,0x3e16bd49,0x3eacbe79,0x3f04bedb,0x3f2cbf18,
0xbe953dc9,0xbf223ef1,0xbf623f46,0xbf7f3f75,0xbf753f7f,0xbf463f62,0xbef13f22,0xbdc93e95,0x3e95bdc9,0x3f22bef1,0x3f62bf46,0x3f7fbf75,0x3f75bf7f,0x3f46bf62,0x3ef1bf22,0x3dc9be95,
0x3f75bf7f,0x3f46bf62,0x3ef1bf22,0x3dc9be95,0xbe953dc9,0xbf223ef1,0xbf623f46,0xbf7f3f75,0xbf753f7f,0xbf463f62,0xbef13f22,0xbdc93e95,0x3e95bdc9,0x3f22bef1,0x3f62bf46,0x3f7fbf75,
0x3f71bf4e,0x3f78bf80,0x3f2cbf5c,0x3e16bedb,0xbf673f7d,0xbf043f3e,0x3d493e79,0x3f18beac,0x3eacbf18,0xbe79bd49,0xbf3e3f04,0xbf7d3f67,0x3edbbe16,0x3f5cbf2c,0x3f80bf78,0x3f4ebf71,
0xbeac3f18,0x3e793d49,0x3f3ebf04,0x3f7dbf67,0xbedb3e16,0xbf5c3f2c,0xbf803f78,0xbf4e3f71,0x3f71bf4e,0x3f78bf80,0x3f2cbf5c,0x3e16bedb,0xbf673f7d,0xbf043f3e,0x3d493e79,0x3f18beac,
0xbf553f7b,0xbe483f0e,0x3f0ebe48,0x3f7bbf55,0x3f55bf7b,0x3e48bf0e,0xbf0e3e48,0xbf7b3f55,0xbf553f7b,0xbe483f0e,0x3f0ebe48,0x3f7bbf55,0x3f55bf7b,0x3e48bf0e,0xbf0e3e48,0xbf7b3f55,
0x3f0ebe48,0x3f7bbf55,0x3f55bf7b,0x3e48bf0e,0xbf0e3e48,0xbf7b3f55,0xbf553f7b,0xbe483f0e,0x3f0ebe48,0x3f7bbf55,0x3f55bf7b,0x3e48bf0e,0xbf0e3e48,0xbf7b3f55,0xbf553f7b,0xbe483f0e,
0x3d49bf04,0xbf4e3edb,0xbf713f7d,0xbe793f2c,0xbf3e3f78,0x3e163eac,0x3f67bf18,0x3f5cbf80,0xbf803f5c,0xbf183f67,0x3eac3e16,0x3f78bf3e,0x3f2cbe79,0x3f7dbf71,0x3edbbf4e,0xbf043d49,
0xbf803f5c,0xbf183f67,0x3eac3e16,0x3f78bf3e,0x3f2cbe79,0x3f7dbf71,0x3edbbf4e,0xbf043d49,0xbd493f04,0x3f4ebedb,0x3f71bf7d,0x3e79bf2c,0x3f3ebf78,0xbe16beac,0xbf673f18,0xbf5c3f80,
0x3f22bf75,0xbef1bdc9,0xbf7f3f62,0xbe953f46,0x3f46be95,0x3f62bf7f,0xbdc9bef1,0xbf753f22,0xbf223f75,0x3ef13dc9,0x3f7fbf62,0x3e95bf46,0xbf463e95,0xbf623f7f,0x3dc93ef1,0x3f75bf22,
0xbf463e95,0xbf623f7f,0x3dc93ef1,0x3f75bf22,0x3f22bf75,0xbef1bdc9,0xbf7f3f62,0xbe953f46,0x3f46be95,0x3f62bf7f,0xbdc9bef1,0xbf753f22,0xbf223f75,0x3ef13dc9,0x3f7fbf62,0x3e95bf46,
0xbe79bedb,0xbf803f4e,0xbe163f3e,0x3f71bf04,0xbf5c3eac,0xbf2c3f7d,0x3f183d49,0x3f67bf78,0xbf783f67,0x3d493f18,0x3f7dbf2c,0x3eacbf5c,0xbf043f71,0x3f3ebe16,0x3f4ebf80,0xbedbbe79,
0xbf783f67,0x3d493f18,0x3f7dbf2c,0x3eacbf5c,0xbf043f71,0x3f3ebe16,0x3f4ebf80,0xbedbbe79,0x3e793edb,0x3f80bf4e,0x3e16bf3e,0xbf713f04,0x3f5cbeac,0x3f2cbf7d,0xbf18bd49,0xbf673f78,
0x3f6dbec4,0x3ec4bf6d,0xbf6d3ec4,0xbec43f6d,0x3f6dbec4,0x3ec4bf6d,0xbf6d3ec4,0xbec43f6d,0x3f6dbec4,0x3ec4bf6d,0xbf6d3ec4,0xbec43f6d,0x3f6dbec4,0x3ec4bf6d,0xbf6d3ec4,0xbec43f6d,
0xbec43f6d,0x3f6dbec4,0x3ec4bf6d,0xbf6d3ec4,0xbec43f6d,0x3f6dbec4,0x3ec4bf6d,0xbf6d3ec4,0xbec43f6d,0x3f6dbec4,0x3ec4bf6d,0xbf6d3ec4,0xbec43f6d,0x3f6dbec4,0x3ec4bf6d,0xbf6d3ec4,
0x3f5cbf71,0xbf2cbe16,0xbf183f80,0x3f67be79,0x3f78bedb,0x3d49bf4e,0xbf7d3f3e,0x3eac3f04,0xbf04beac,0xbf3e3f7d,0x3f4ebd49,0x3edbbf78,0x3e79bf67,0xbf803f18,0x3e163f2c,0x3f71bf5c,
0x3f043eac,0x3f3ebf7d,0xbf4e3d49,0xbedb3f78,0xbe793f67,0x3f80bf18,0xbe16bf2c,0xbf713f5c,0x3f5cbf71,0xbf2cbe16,0xbf183f80,0x3f67be79,0x3f78bedb,0x3d49bf4e,0xbf7d3f3e,0x3eac3f04,
0xbf7f3ef1,0x3e953f22,0x3f46bf75,0xbf623dc9,0xbdc93f62,0x3f75bf46,0xbf22be95,0xbef13f7f,0x3f7fbef1,0xbe95bf22,0xbf463f75,0x3f62bdc9,0x3dc9bf62,0xbf753f46,0x3f223e95,0x3ef1bf7f,
0x3dc9bf62,0xbf753f46,0x3f223e95,0x3ef1bf7f,0xbf7f3ef1,0x3e953f22,0x3f46bf75,0xbf623dc9,0xbdc93f62,0x3f75bf46,0xbf22be95,0xbef13f7f,0x3f7fbef1,0xbe95bf22,0xbf463f75,0x3f62bdc9,
0x3f2cbf78,0xbf7d3eac,0x3edb3f18,0x3f04bf80,0x3d493f5c,0x3f4ebf67,0xbf713e16,0x3e793f3e,0xbf3ebe79,0xbe163f71,0x3f67bf4e,0xbf5cbd49,0x3f80bf04,0xbf18bedb,0xbeac3f7d,0x3f78bf2c,
0x3f3e3e79,0x3e16bf71,0xbf673f4e,0x3f5c3d49,0xbf803f04,0x3f183edb,0x3eacbf7d,0xbf783f2c,0x3f2cbf78,0xbf7d3eac,0x3edb3f18,0x3f04bf80,0x3d493f5c,0x3f4ebf67,0xbf713e16,0x3e793f3e,
0x3e483f55,0x3f0ebf7b,0xbf7b3f0e,0x3f553e48,0xbe48bf55,0xbf0e3f7b,0x3f7bbf0e,0xbf55be48,0x3e483f55,0x3f0ebf7b,0xbf7b3f0e,0x3f553e48,0xbe48bf55,0xbf0e3f7b,0x3f7bbf0e,0xbf55be48,
0x3f7bbf0e,0xbf55be48,0x3e483f55,0x3f0ebf7b,0xbf7b3f0e,0x3f553e48,0xbe48bf55,0xbf0e3f7b,0x3f7bbf0e,0xbf55be48,0x3e483f55,0x3f0ebf7b,0xbf7b3f0e,0x3f553e48,0xbe48bf55,0xbf0e3f7b,
0xbf67be16,0x3f043f2c,0x3d49bf78,0xbf183f71,0x3eac3f4e,0x3e79bf80,0xbf3e3f5c,0x3f7dbedb,0xbedb3f7d,0x3f5cbf3e,0xbf803e79,0x3f4e3eac,0x3f71bf18,0xbf783d49,0x3f2c3f04,0xbe16bf67,
0xbedb3f7d,0x3f5cbf3e,0xbf803e79,0x3f4e3eac,0x3f71bf18,0xbf783d49,0x3f2c3f04,0xbe16bf67,0x3f673e16,0xbf04bf2c,0xbd493f78,0x3f18bf71,0xbeacbf4e,0xbe793f80,0x3f3ebf5c,0xbf7d3edb,
0xbef1bf46,0x3dc93f75,0x3e95bf7f,0xbf223f62,0x3f62bf22,0xbf7f3e95,0x3f753dc9,0xbf46bef1,0x3ef13f46,0xbdc9bf75,0xbe953f7f,0x3f22bf62,0xbf623f22,0x3f7fbe95,0xbf75bdc9,0x3f463ef1,
0xbf623f22,0x3f7fbe95,0xbf75bdc9,0x3f463ef1,0xbef1bf46,0x3dc93f75,0x3e95bf7f,0xbf223f62,0x3f62bf22,0xbf7f3e95,0x3f753dc9,0xbf46bef1,0x3ef13f46,0xbdc9bf75,0xbe953f7f,0x3f22bf62,
0xbf7dbd49,0x3f713e79,0xbf5cbedb,0x3f3e3f18,0xbf4e3f2c,0x3f67bf04,0xbf783eac,0x3f80be16,0xbe163f80,0x3eacbf78,0xbf043f67,0x3f2cbf4e,0x3f183f3e,0xbedbbf5c,0x3e793f71,0xbd49bf7d,
0xbe163f80,0x3eacbf78,0xbf043f67,0x3f2cbf4e,0x3f183f3e,0xbedbbf5c,0x3e793f71,0xbd49bf7d,0x3f7d3d49,0xbf71be79,0x3f5c3edb,0xbf3ebf18,0x3f4ebf2c,0xbf673f04,0x3f78beac,0xbf803e16,
0x3f35bf35,0xbf353f35,0x3f35bf35,0xbf353f35,0x3f35bf35,0xbf353f35,0x3f35bf35,0xbf353f35,0x3f35bf35,0xbf353f35,0x3f35bf35,0xbf353f35,0x3f35bf35,0xbf353f35,0x3f35bf35,0xbf353f35,
0x3f353f35,0xbf35bf35,0x3f353f35,0xbf35bf35,0x3f353f35,0xbf35bf35,0x3f353f35,0xbf35bf35,0x3f353f35,0xbf35bf35,0x3f353f35,0xbf35bf35,0x3f353f35,0xbf35bf35,0x3f353f35,0xbf35bf35,
0xbe16bf80,0x3eac3f78,0xbf04bf67,0x3f2c3f4e,0x3f18bf3e,0xbedb3f5c,0x3e79bf71,0xbd493f7d,0xbf7d3d49,0x3f71be79,0xbf5c3edb,0x3f3ebf18,0xbf4ebf2c,0x3f673f04,0xbf78beac,0x3f803e16,
0x3f7dbd49,0xbf713e79,0x3f5cbedb,0xbf3e3f18,0x3f4e3f2c,0xbf67bf04,0x3f783eac,0xbf80be16,0xbe16bf80,0x3eac3f78,0xbf04bf67,0x3f2c3f4e,0x3f18bf3e,0xbedb3f5c,0x3e79bf71,0xbd493f7d,
0xbef13f46,0x3dc9bf75,0x3e953f7f,0xbf22bf62,0x3f623f22,0xbf7fbe95,0x3f75bdc9,0xbf463ef1,0x3ef1bf46,0xbdc93f75,0xbe95bf7f,0x3f223f62,0xbf62bf22,0x3f7f3e95,0xbf753dc9,0x3f46bef1,
0xbf62bf22,0x3f7f3e95,0xbf753dc9,0x3f46bef1,0xbef13f46,0x3dc9bf75,0x3e953f7f,0xbf22bf62,0x3f623f22,0xbf7fbe95,0x3f75bdc9,0xbf463ef1,0x3ef1bf46,0xbdc93f75,0xbe95bf7f,0x3f223f62,
0xbedbbf7d,0x3f5c3f3e,0xbf80be79,0x3f4ebeac,0x3f713f18,0xbf78bd49,0x3f2cbf04,0xbe163f67,0xbf673e16,0x3f04bf2c,0x3d493f78,0xbf18bf71,0x3eacbf4e,0x3e793f80,0xbf3ebf5c,0x3f7d3edb,
0x3f67be16,0xbf043f2c,0xbd49bf78,0x3f183f71,0xbeac3f4e,0xbe79bf80,0x3f3e3f5c,0xbf7dbedb,0xbedbbf7d,0x3f5c3f3e,0xbf80be79,0x3f4ebeac,0x3f713f18,0xbf78bd49,0x3f2cbf04,0xbe163f67,
0x3f7b3f0e,0xbf553e48,0x3e48bf55,0x3f0e3f7b,0xbf7bbf0e,0x3f55be48,0xbe483f55,0xbf0ebf7b,0x3f7b3f0e,0xbf553e48,0x3e48bf55,0x3f0e3f7b,0xbf7bbf0e,0x3f55be48,0xbe483f55,0xbf0ebf7b,
0x3e48bf55,0x3f0e3f7b,0xbf7bbf0e,0x3f55be48,0xbe483f55,0xbf0ebf7b,0x3f7b3f0e,0xbf553e48,0x3e48bf55,0x3f0e3f7b,0xbf7bbf0e,0x3f55be48,0xbe483f55,0xbf0ebf7b,0x3f7b3f0e,0xbf553e48,
0xbf3e3e79,0xbe16bf71,0x3f673f4e,0xbf5c3d49,0x3f803f04,0xbf183edb,0xbeacbf7d,0x3f783f2c,0x3f2c3f78,0xbf7dbeac,0x3edbbf18,0x3f043f80,0x3d49bf5c,0x3f4e3f67,0xbf71be16,0x3e79bf3e,
0x3f2c3f78,0xbf7dbeac,0x3edbbf18,0x3f043f80,0x3d49bf5c,0x3f4e3f67,0xbf71be16,0x3e79bf3e,0x3f3ebe79,0x3e163f71,0xbf67bf4e,0x3f5cbd49,0xbf80bf04,0x3f18bedb,0x3eac3f7d,0xbf78bf2c,
0xbf7fbef1,0x3e95bf22,0x3f463f75,0xbf62bdc9,0xbdc9bf62,0x3f753f46,0xbf223e95,0xbef1bf7f,0x3f7f3ef1,0xbe953f22,0xbf46bf75,0x3f623dc9,0x3dc93f62,0xbf75bf46,0x3f22be95,0x3ef13f7f,
0x3dc93f62,0xbf75bf46,0x3f22be95,0x3ef13f7f,0xbf7fbef1,0x3e95bf22,0x3f463f75,0xbf62bdc9,0xbdc9bf62,0x3f753f46,0xbf223e95,0xbef1bf7f,0x3f7f3ef1,0xbe953f22,0xbf46bf75,0x3f623dc9,
0xbf043eac,0xbf3ebf7d,0x3f4e3d49,0x3edb3f78,0x3e793f67,0xbf80bf18,0x3e16bf2c,0x3f713f5c,0x3f5c3f71,0xbf2c3e16,0xbf18bf80,0x3f673e79,0x3f783edb,0x3d493f4e,0xbf7dbf3e,0x3eacbf04,
0x3f5c3f71,0xbf2c3e16,0xbf18bf80,0x3f673e79,0x3f783edb,0x3d493f4e,0xbf7dbf3e,0x3eacbf04,0x3f04beac,0x3f3e3f7d,0xbf4ebd49,0xbedbbf78,0xbe79bf67,0x3f803f18,0xbe163f2c,0xbf71bf5c,
0xbec4bf6d,0x3f6d3ec4,0x3ec43f6d,0xbf6dbec4,0xbec4bf6d,0x3f6d3ec4,0x3ec43f6d,0xbf6dbec4,0xbec4bf6d,0x3f6d3ec4,0x3ec43f6d,0xbf6dbec4,0xbec4bf6d,0x3f6d3ec4,0x3ec43f6d,0xbf6dbec4,
0x3f6d3ec4,0x3ec43f6d,0xbf6dbec4,0xbec4bf6d,0x3f6d3ec4,0x3ec43f6d,0xbf6dbec4,0xbec4bf6d,0x3f6d3ec4,0x3ec43f6d,0xbf6dbec4,0xbec4bf6d,0x3f6d3ec4,0x3ec43f6d,0xbf6dbec4,0xbec4bf6d,
0xbf78bf67,0x3d49bf18,0x3f7d3f2c,0x3eac3f5c,0xbf04bf71,0x3f3e3e16,0x3f4e3f80,0xbedb3e79,0xbe793edb,0xbf80bf4e,0xbe16bf3e,0x3f713f04,0xbf5cbeac,0xbf2cbf7d,0x3f18bd49,0x3f673f78,
0x3e79bedb,0x3f803f4e,0x3e163f3e,0xbf71bf04,0x3f5c3eac,0x3f2c3f7d,0xbf183d49,0xbf67bf78,0xbf78bf67,0x3d49bf18,0x3f7d3f2c,0x3eac3f5c,0xbf04bf71,0x3f3e3e16,0x3f4e3f80,0xbedb3e79,
0x3f223f75,0xbef13dc9,0xbf7fbf62,0xbe95bf46,0x3f463e95,0x3f623f7f,0xbdc93ef1,0xbf75bf22,0xbf22bf75,0x3ef1bdc9,0x3f7f3f62,0x3e953f46,0xbf46be95,0xbf62bf7f,0x3dc9bef1,0x3f753f22,
0xbf46be95,0xbf62bf7f,0x3dc9bef1,0x3f753f22,0x3f223f75,0xbef13dc9,0xbf7fbf62,0xbe95bf46,0x3f463e95,0x3f623f7f,0xbdc93ef1,0xbf75bf22,0xbf22bf75,0x3ef1bdc9,0x3f7f3f62,0x3e953f46,
0xbf80bf5c,0xbf18bf67,0x3eacbe16,0x3f783f3e,0x3f2c3e79,0x3f7d3f71,0x3edb3f4e,0xbf04bd49,0x3d493f04,0xbf4ebedb,0xbf71bf7d,0xbe79bf2c,0xbf3ebf78,0x3e16beac,0x3f673f18,0x3f5c3f80,
0xbd49bf04,0x3f4e3edb,0x3f713f7d,0x3e793f2c,0x3f3e3f78,0xbe163eac,0xbf67bf18,0xbf5cbf80,0xbf80bf5c,0xbf18bf67,0x3eacbe16,0x3f783f3e,0x3f2c3e79,0x3f7d3f71,0x3edb3f4e,0xbf04bd49,
0x3f0e3e48,0x3f7b3f55,0x3f553f7b,0x3e483f0e,0xbf0ebe48,0xbf7bbf55,0xbf55bf7b,0xbe48bf0e,0x3f0e3e48,0x3f7b3f55,0x3f553f7b,0x3e483f0e,0xbf0ebe48,0xbf7bbf55,0xbf55bf7b,0xbe48bf0e,
0xbf55bf7b,0xbe48bf0e,0x3f0e3e48,0x3f7b3f55,0x3f553f7b,0x3e483f0e,0xbf0ebe48,0xbf7bbf55,0xbf55bf7b,0xbe48bf0e,0x3f0e3e48,0x3f7b3f55,0x3f553f7b,0x3e483f0e,0xbf0ebe48,0xbf7bbf55,
0x3eac3f18,0xbe793d49,0xbf3ebf04,0xbf7dbf67,0x3edb3e16,0x3f5c3f2c,0x3f803f78,0x3f4e3f71,0x3f713f4e,0x3f783f80,0x3f2c3f5c,0x3e163edb,0xbf67bf7d,0xbf04bf3e,0x3d49be79,0x3f183eac,
0x3f713f4e,0x3f783f80,0x3f2c3f5c,0x3e163edb,0xbf67bf7d,0xbf04bf3e,0x3d49be79,0x3f183eac,0xbeacbf18,0x3e79bd49,0x3f3e3f04,0x3f7d3f67,0xbedbbe16,0xbf5cbf2c,0xbf80bf78,0xbf4ebf71,
0xbe95bdc9,0xbf22bef1,0xbf62bf46,0xbf7fbf75,0xbf75bf7f,0xbf46bf62,0xbef1bf22,0xbdc9be95,0x3e953dc9,0x3f223ef1,0x3f623f46,0x3f7f3f75,0x3f753f7f,0x3f463f62,0x3ef13f22,0x3dc93e95,
0x3f753f7f,0x3f463f62,0x3ef13f22,0x3dc93e95,0xbe95bdc9,0xbf22bef1,0xbf62bf46,0xbf7fbf75,0xbf75bf7f,0xbf46bf62,0xbef1bf22,0xbdc9be95,0x3e953dc9,0x3f223ef1,0x3f623f46,0x3f7f3f75,
0x3f183f2c,0x3edb3f04,0x3e793eac,0x3d493e16,0x3f7d3f80,0x3f713f78,0x3f5c3f67,0x3f3e3f4e,0x3f4e3f3e,0x3f673f5c,0x3f783f71,0x3f803f7d,0x3e163d49,0x3eac3e79,0x3f043edb,0x3f2c3f18,
0x3f4e3f3e,0x3f673f5c,0x3f783f71,0x3f803f7d,0x3e163d49,0x3eac3e79,0x3f043edb,0x3f2c3f18,0xbf18bf2c,0xbedbbf04,0xbe79beac,0xbd49be16,0xbf7dbf80,0xbf71bf78,0xbf5cbf67,0xbf3ebf4e,
0x38fb37c9,0x39a13960,0x39fc39cf,0x3a273a13,0xba7eba80,0xba73ba7a,0xba5fba6a,0xba42ba51,0x3a4a3a39,0x3a653a58,0x3a773a6f,0x3a7f3a7c,0xba1dba31,0xb9e6ba09,0xb989b9b8,0xb897b92f,
0x3a7e3a80,0x3a733a7a,0x3a5f3a6a,0x3a423a51,0x38fb37c9,0x39a13960,0x39fc39cf,0x3a273a13,0x3a1d3a31,0x39e63a09,0x398939b8,0x3897392f,0x3a4a3a39,0x3a653a58,0x3a773a6f,0x3a7f3a7c,
0xba6fba7f,0xba13ba4a,0xb7c9b9a1,0x3a093989,0x39b83897,0x3a513a1d,0x3a803a73,0x3a583a77,0x3a6a3a42,0x3a7c3a7e,0x3a393a65,0x396039fc,0x39cf3a27,0xb92f38fb,0xba31b9e6,0xba7aba5f,
0xb9b8b897,0xba51ba1d,0xba80ba73,0xba58ba77,0xba6fba7f,0xba13ba4a,0xb7c9b9a1,0x3a093989,0xb9cfba27,0x392fb8fb,0x3a3139e6,0x3a7a3a5f,0x3a6a3a42,0x3a7c3a7e,0x3a393a65,0x396039fc,
0xba7cba4a,0xba31ba73,0x3960b989,0x3a6f3a27,0x392f3a1d,0xba39b9a1,0xba7aba77,0xb9b8ba42,0x3a1338fb,0x3a803a65,0x3a093a5f,0xb9cf3897,0xba51ba7e,0x37c9b9e6,0x3a5839fc,0x3a6a3a7f,
0xb92fba1d,0x3a3939a1,0x3a7a3a77,0x39b83a42,0xba7cba4a,0xba31ba73,0x3960b989,0x3a6f3a27,0x3a513a7e,0xb7c939e6,0xba58b9fc,0xba6aba7f,0x3a1338fb,0x3a803a65,0x3a093a5f,0xb9cf3897,
0xba7fba51,0xb8fbba39,0x3a733a09,0x39fc3a6f,0x3897ba13,0x3a7e3a31,0x39a13a58,0xba5fb9b8,0xba27ba7c,0x3a1db7c9,0x3a653a7a,0xb98939cf,0x3a42392f,0x3a4a3a80,0xb9e63960,0xba77ba6a,
0xb8973a13,0xba7eba31,0xb9a1ba58,0x3a5f39b8,0xba7fba51,0xb8fbba39,0x3a733a09,0x39fc3a6f,0xba42b92f,0xba4aba80,0x39e6b960,0x3a773a6a,0xba27ba7c,0x3a1db7c9,0x3a653a7a,0xb98939cf,
0x39e63a7a,0xba77b9cf,0xb897ba51,0x3a7e3a39,0x3a653960,0x39893a6a,0xba7fba13,0x38fbba31,0xb9a13a09,0xba5fba6f,0x3a27b92f,0x3a1d3a80,0x3a733a58,0xb9fc39b8,0xba42ba7c,0x3a4a37c9,
0x3a653960,0x39893a6a,0xba7fba13,0x38fbba31,0xb9e6ba7a,0x3a7739cf,0x38973a51,0xba7eba39,0x3a733a58,0xb9fc39b8,0xba42ba7c,0x3a4a37c9,0x39a1ba09,0x3a5f3a6f,0xba27392f,0xba1dba80,
0xba7ab989,0x39b8ba27,0x3a133a7e,0xba80b9e6,0xb960ba77,0x3a6f3a42,0xba5138fb,0xb7c9ba65,0x3a09b9fc,0x39cf3a7f,0xba7cba1d,0x3a31b9a1,0x3a583a5f,0xba6ab897,0x392fba4a,0x3a393a73,
0xb960ba77,0x3a6f3a42,0xba5138fb,0xb7c9ba65,0x3a7a3989,0xb9b83a27,0xba13ba7e,0x3a8039e6,0x3a583a5f,0xba6ab897,0x392fba4a,0x3a393a73,0xba0939fc,0xb9cfba7f,0x3a7c3a1d,0xba3139a1,
0x3a39b9e6,0xb9603a5f,0xb9b8ba7f,0x3a513a4a,0xba31ba65,0x3a7a39fc,0xba6f3897,0x3a13ba1d,0xb7c93a73,0xba09ba77,0x3a6a3a27,0xba7cb8fb,0x3a8039a1,0xba583989,0x39cfba42,0x392f3a7e,
0xba31ba65,0x3a7a39fc,0xba6f3897,0x3a13ba1d,0xba3939e6,0x3960ba5f,0x39b83a7f,0xba51ba4a,0x3a8039a1,0xba583989,0x39cfba42,0x392f3a7e,0x37c9ba73,0x3a093a77,0xba6aba27,0x3a7c38fb,
0xba5f39cf,0x3a42ba13,0xba1d3a39,0x39e6ba58,0xb9fcba6a,0x3a273a51,0xba4aba31,0x3a653a09,0xba77b9b8,0x3a7f392f,0xba7e37c9,0x3a73b960,0x3989ba6f,0xb8973a7c,0xb8fbba80,0x39a13a7a,
0xb9fcba6a,0x3a273a51,0xba4aba31,0x3a653a09,0x3a5fb9cf,0xba423a13,0x3a1dba39,0xb9e63a58,0x3989ba6f,0xb8973a7c,0xb8fbba80,0x39a13a7a,0x3a7739b8,0xba7fb92f,0x3a7eb7c9,0xba733960,
0x3a5f39cf,0xba42ba13,0x3a1d3a39,0xb9e6ba58,0x39fcba6a,0xba273a51,0x3a4aba31,0xba653a09,0x39893a6f,0xb897ba7c,0xb8fb3a80,0x39a1ba7a,0x3a77b9b8,0xba7f392f,0x3a7e37c9,0xba73b960,
0xb9fc3a6a,0x3a27ba51,0xba4a3a31,0x3a65ba09,0x3a5f39cf,0xba42ba13,0x3a1d3a39,0xb9e6ba58,0xba7739b8,0x3a7fb92f,0xba7eb7c9,0x3a733960,0x39893a6f,0xb897ba7c,0xb8fb3a80,0x39a1ba7a,
0x3a31ba65,0xba7a39fc,0x3a6f3897,0xba13ba1d,0x3a3939e6,0xb960ba5f,0xb9b83a7f,0x3a51ba4a,0x37c93a73,0x3a09ba77,0xba6a3a27,0x3a7cb8fb,0xba8039a1,0x3a583989,0xb9cfba42,0xb92f3a7e,
0xba39b9e6,0x39603a5f,0x39b8ba7f,0xba513a4a,0x3a31ba65,0xba7a39fc,0x3a6f3897,0xba13ba1d,0x3a80b9a1,0xba58b989,0x39cf3a42,0x392fba7e,0x37c93a73,0x3a09ba77,0xba6a3a27,0x3a7cb8fb,
0x3960ba77,0xba6f3a42,0x3a5138fb,0x37c9ba65,0xba7a3989,0x39b83a27,0x3a13ba7e,0xba8039e6,0x3a0939fc,0x39cfba7f,0xba7c3a1d,0x3a3139a1,0x3a58ba5f,0xba6a3897,0x392f3a4a,0x3a39ba73,
0x3a7ab989,0xb9b8ba27,0xba133a7e,0x3a80b9e6,0x3960ba77,0xba6f3a42,0x3a5138fb,0x37c9ba65,0xba583a5f,0x3a6ab897,0xb92fba4a,0xba393a73,0x3a0939fc,0x39cfba7f,0xba7c3a1d,0x3a3139a1,
0x39e6ba7a,0xba7739cf,0xb8973a51,0x3a7eba39,0x3a65b960,0x3989ba6a,0xba7f3a13,0x38fb3a31,0x3a73ba58,0xb9fcb9b8,0xba423a7c,0x3a4ab7c9,0x39a13a09,0x3a5fba6f,0xba27b92f,0xba1d3a80,
0xba653960,0xb9893a6a,0x3a7fba13,0xb8fbba31,0x39e6ba7a,0xba7739cf,0xb8973a51,0x3a7eba39,0xb9a1ba09,0xba5f3a6f,0x3a27392f,0x3a1dba80,0x3a73ba58,0xb9fcb9b8,0xba423a7c,0x3a4ab7c9,
0xba7f3a51,0xb8fb3a39,0x3a73ba09,0x39fcba6f,0x38973a13,0x3a7eba31,0x39a1ba58,0xba5f39b8,0xba42392f,0xba4a3a80,0x39e63960,0x3a77ba6a,0xba273a7c,0x3a1d37c9,0x3a65ba7a,0xb989b9cf,
0x38973a13,0x3a7eba31,0x39a1ba58,0xba5f39b8,0x3a7fba51,0x38fbba39,0xba733a09,0xb9fc3a6f,0xba273a7c,0x3a1d37c9,0x3a65ba7a,0xb989b9cf,0x3a42b92f,0x3a4aba80,0xb9e6b960,0xba773a6a,
0x392fba1d,0xba3939a1,0xba7a3a77,0xb9b83a42,0x3a7cba4a,0x3a31ba73,0xb960b989,0xba6f3a27,0x3a13b8fb,0x3a80ba65,0x3a09ba5f,0xb9cfb897,0xba513a7e,0x37c939e6,0x3a58b9fc,0x3a6aba7f,
0x3a7cba4a,0x3a31ba73,0xb960b989,0xba6f3a27,0xb92f3a1d,0x3a39b9a1,0x3a7aba77,0x39b8ba42,0xba513a7e,0x37c939e6,0x3a58b9fc,0x3a6aba7f,0xba1338fb,0xba803a65,0xba093a5f,0x39cf3897,
0x39b8b897,0x3a51ba1d,0x3a80ba73,0x3a58ba77,0x3a6fba7f,0x3a13ba4a,0x37c9b9a1,0xba093989,0xba6a3a42,0xba7c3a7e,0xba393a65,0xb96039fc,0xb9cf3a27,0x392f38fb,0x3a31b9e6,0x3a7aba5f,
0x3a6fba7f,0x3a13ba4a,0x37c9b9a1,0xba093989,0xb9b83897,0xba513a1d,0xba803a73,0xba583a77,0xb9cf3a27,0x392f38fb,0x3a31b9e6,0x3a7aba5f,0x3a6aba42,0x3a7cba7e,0x3a39ba65,0x3960b9fc,
0xb8fb37c9,0xb9a13960,0xb9fc39cf,0xba273a13,0x3a7eba80,0x3a73ba7a,0x3a5fba6a,0x3a42ba51,0x3a1dba31,0x39e6ba09,0x3989b9b8,0x3897b92f,0x3a4aba39,0x3a65ba58,0x3a77ba6f,0x3a7fba7c,
0x3a7eba80,0x3a73ba7a,0x3a5fba6a,0x3a42ba51,0x38fbb7c9,0x39a1b960,0x39fcb9cf,0x3a27ba13,0x3a4aba39,0x3a65ba58,0x3a77ba6f,0x3a7fba7c,0xba1d3a31,0xb9e63a09,0xb98939b8,0xb897392f,
0xba4a3a39,0xba653a58,0xba773a6f,0xba7f3a7c,0x3a1dba31,0x39e6ba09,0x3989b9b8,0x3897b92f,0xba7e3a80,0xba733a7a,0xba5f3a6a,0xba423a51,0xb8fb37c9,0xb9a13960,0xb9fc39cf,0xba273a13,
0xba1d3a31,0xb9e63a09,0xb98939b8,0xb897392f,0xba4a3a39,0xba653a58,0xba773a6f,0xba7f3a7c,0x38fbb7c9,0x39a1b960,0x39fcb9cf,0x3a27ba13,0xba7e3a80,0xba733a7a,0xba5f3a6a,0xba423a51,
0x39cfba27,0xb92fb8fb,0xba3139e6,0xba7a3a5f,0xba6a3a42,0xba7c3a7e,0xba393a65,0xb96039fc,0xba6f3a7f,0xba133a4a,0xb7c939a1,0x3a09b989,0x39b8b897,0x3a51ba1d,0x3a80ba73,0x3a58ba77,
0x3a6aba42,0x3a7cba7e,0x3a39ba65,0x3960b9fc,0x39cfba27,0xb92fb8fb,0xba3139e6,0xba7a3a5f,0xb9b83897,0xba513a1d,0xba803a73,0xba583a77,0xba6f3a7f,0xba133a4a,0xb7c939a1,0x3a09b989,
0x3a51ba7e,0xb7c9b9e6,0xba5839fc,0xba6a3a7f,0x3a13b8fb,0x3a80ba65,0x3a09ba5f,0xb9cfb897,0xba7c3a4a,0xba313a73,0x39603989,0x3a6fba27,0x392fba1d,0xba3939a1,0xba7a3a77,0xb9b83a42,
0xba1338fb,0xba803a65,0xba093a5f,0x39cf3897,0x3a51ba7e,0xb7c9b9e6,0xba5839fc,0xba6a3a7f,0xb92f3a1d,0x3a39b9a1,0x3a7aba77,0x39b8ba42,0xba7c3a4a,0xba313a73,0x39603989,0x3a6fba27,
0x3a27ba7c,0xba1db7c9,0xba653a7a,0x398939cf,0xba42392f,0xba4a3a80,0x39e63960,0x3a77ba6a,0xb897ba13,0xba7e3a31,0xb9a13a58,0x3a5fb9b8,0xba7f3a51,0xb8fb3a39,0x3a73ba09,0x39fcba6f,
0x3a42b92f,0x3a4aba80,0xb9e6b960,0xba773a6a,0x3a27ba7c,0xba1db7c9,0xba653a7a,0x398939cf,0x3a7fba51,0x38fbba39,0xba733a09,0xb9fc3a6f,0xb897ba13,0xba7e3a31,0xb9a13a58,0x3a5fb9b8,
0x39a13a09,0x3a5fba6f,0xba27b92f,0xba1d3a80,0xba733a58,0x39fc39b8,0x3a42ba7c,0xba4a37c9,0x3a65b960,0x3989ba6a,0xba7f3a13,0x38fb3a31,0xb9e63a7a,0x3a77b9cf,0x3897ba51,0xba7e3a39,
0xba733a58,0x39fc39b8,0x3a42ba7c,0xba4a37c9,0xb9a1ba09,0xba5f3a6f,0x3a27392f,0x3a1dba80,0xb9e63a7a,0x3a77b9cf,0x3897ba51,0xba7e3a39,0xba653960,0xb9893a6a,0x3a7fba13,0xb8fbba31,
0x3a58ba5f,0xba6a3897,0x392f3a4a,0x3a39ba73,0xba09b9fc,0xb9cf3a7f,0x3a7cba1d,0xba31b9a1,0xba7a3989,0x39b83a27,0x3a13ba7e,0xba8039e6,0xb9603a77,0x3a6fba42,0xba51b8fb,0xb7c93a65,
0xba09b9fc,0xb9cf3a7f,0x3a7cba1d,0xba31b9a1,0xba583a5f,0x3a6ab897,0xb92fba4a,0xba393a73,0xb9603a77,0x3a6fba42,0xba51b8fb,0xb7c93a65,0x3a7ab989,0xb9b8ba27,0xba133a7e,0x3a80b9e6,
0xba8039a1,0x3a583989,0xb9cfba42,0xb92f3a7e,0xb7c9ba73,0xba093a77,0x3a6aba27,0xba7c38fb,0x3a3939e6,0xb960ba5f,0xb9b83a7f,0x3a51ba4a,0xba313a65,0x3a7ab9fc,0xba6fb897,0x3a133a1d,
0xb7c9ba73,0xba093a77,0x3a6aba27,0xba7c38fb,0x3a80b9a1,0xba58b989,0x39cf3a42,0x392fba7e,0xba313a65,0x3a7ab9fc,0xba6fb897,0x3a133a1d,0xba39b9e6,0x39603a5f,0x39b8ba7f,0xba513a4a,
0x3a77b9b8,0xba7f392f,0x3a7e37c9,0xba73b960,0xb989ba6f,0x38973a7c,0x38fbba80,0xb9a13a7a,0x39fcba6a,0xba273a51,0x3a4aba31,0xba653a09,0xba5fb9cf,0x3a423a13,0xba1dba39,0x39e63a58,
0xb989ba6f,0x38973a7c,0x38fbba80,0xb9a13a7a,0xba7739b8,0x3a7fb92f,0xba7eb7c9,0x3a733960,0xba5fb9cf,0x3a423a13,0xba1dba39,0x39e63a58,0xb9fc3a6a,0x3a27ba51,0xba4a3a31,0x3a65ba09,
0xb9893a6f,0x3897ba7c,0x38fb3a80,0xb9a1ba7a,0xba77b9b8,0x3a7f392f,0xba7e37c9,0x3a73b960,0x39fc3a6a,0xba27ba51,0x3a4a3a31,0xba65ba09,0xba5f39cf,0x3a42ba13,0xba1d3a39,0x39e6ba58,
0x3a7739b8,0xba7fb92f,0x3a7eb7c9,0xba733960,0xb9893a6f,0x3897ba7c,0x38fb3a80,0xb9a1ba7a,0x3a5fb9cf,0xba423a13,0x3a1dba39,0xb9e63a58,0x39fc3a6a,0xba27ba51,0x3a4a3a31,0xba65ba09,
0xba80b9a1,0x3a58b989,0xb9cf3a42,0xb92fba7e,0xb7c93a73,0xba09ba77,0x3a6a3a27,0xba7cb8fb,0x3a313a65,0xba7ab9fc,0x3a6fb897,0xba133a1d,0x3a39b9e6,0xb9603a5f,0xb9b8ba7f,0x3a513a4a,
0x37c9ba73,0x3a093a77,0xba6aba27,0x3a7c38fb,0xba80b9a1,0x3a58b989,0xb9cf3a42,0xb92fba7e,0xba3939e6,0x3960ba5f,0x39b83a7f,0xba51ba4a,0x3a313a65,0xba7ab9fc,0x3a6fb897,0xba133a1d,
0xba58ba5f,0x3a6a3897,0xb92f3a4a,0xba39ba73,0x3a09b9fc,0x39cf3a7f,0xba7cba1d,0x3a31b9a1,0x39603a77,0xba6fba42,0x3a51b8fb,0x37c93a65,0xba7ab989,0x39b8ba27,0x3a133a7e,0xba80b9e6,
0xba0939fc,0xb9cfba7f,0x3a7c3a1d,0xba3139a1,0xba58ba5f,0x3a6a3897,0xb92f3a4a,0xba39ba73,0x3a7a3989,0xb9b83a27,0xba13ba7e,0x3a8039e6,0x39603a77,0xba6fba42,0x3a51b8fb,0x37c93a65,
0xba73ba58,0x39fcb9b8,0x3a423a7c,0xba4ab7c9,0xb9a13a09,0xba5fba6f,0x3a27b92f,0x3a1d3a80,0xba65b960,0xb989ba6a,0x3a7f3a13,0xb8fb3a31,0x39e63a7a,0xba77b9cf,0xb897ba51,0x3a7e3a39,
0x39a1ba09,0x3a5f3a6f,0xba27392f,0xba1dba80,0xba73ba58,0x39fcb9b8,0x3a423a7c,0xba4ab7c9,0xb9e6ba7a,0x3a7739cf,0x38973a51,0xba7eba39,0xba65b960,0xb989ba6a,0x3a7f3a13,0xb8fb3a31,
0x3a42392f,0x3a4a3a80,0xb9e63960,0xba77ba6a,0x3a273a7c,0xba1d37c9,0xba65ba7a,0x3989b9cf,0x3897ba13,0x3a7e3a31,0x39a13a58,0xba5fb9b8,0x3a7f3a51,0x38fb3a39,0xba73ba09,0xb9fcba6f,
0x3a273a7c,0xba1d37c9,0xba65ba7a,0x3989b9cf,0xba42b92f,0xba4aba80,0x39e6b960,0x3a773a6a,0x3a7f3a51,0x38fb3a39,0xba73ba09,0xb9fcba6f,0xb8973a13,0xba7eba31,0xb9a1ba58,0x3a5f39b8,
0xba51ba7e,0x37c9b9e6,0x3a5839fc,0x3a6a3a7f,0xba13b8fb,0xba80ba65,0xba09ba5f,0x39cfb897,0x392f3a1d,0xba39b9a1,0xba7aba77,0xb9b8ba42,0x3a7c3a4a,0x3a313a73,0xb9603989,0xba6fba27,
0xba13b8fb,0xba80ba65,0xba09ba5f,0x39cfb897,0x3a513a7e,0xb7c939e6,0xba58b9fc,0xba6aba7f,0x3a7c3a4a,0x3a313a73,0xb9603989,0xba6fba27,0xb92fba1d,0x3a3939a1,0x3a7a3a77,0x39b83a42,
0x39cf3a27,0xb92f38fb,0xba31b9e6,0xba7aba5f,0xba6aba42,0xba7cba7e,0xba39ba65,0xb960b9fc,0x39b83897,0x3a513a1d,0x3a803a73,0x3a583a77,0x3a6f3a7f,0x3a133a4a,0x37c939a1,0xba09b989,
0xba6aba42,0xba7cba7e,0xba39ba65,0xb960b9fc,0xb9cfba27,0x392fb8fb,0x3a3139e6,0x3a7a3a5f,0x3a6f3a7f,0x3a133a4a,0x37c939a1,0xba09b989,0xb9b8b897,0xba51ba1d,0xba80ba73,0xba58ba77,
0xba1dba31,0xb9e6ba09,0xb989b9b8,0xb897b92f,0xba4aba39,0xba65ba58,0xba77ba6f,0xba7fba7c,0xba7eba80,0xba73ba7a,0xba5fba6a,0xba42ba51,0xb8fbb7c9,0xb9a1b960,0xb9fcb9cf,0xba27ba13,
0xba4aba39,0xba65ba58,0xba77ba6f,0xba7fba7c,0x3a1d3a31,0x39e63a09,0x398939b8,0x3897392f,0xb8fbb7c9,0xb9a1b960,0xb9fcb9cf,0xba27ba13,0x3a7e3a80,0x3a733a7a,0x3a5f3a6a,0x3a423a51,
0x3d973cc9,0xbf7fbf80,0x3ee63ecf,0xbf65bf6a,0x3e2f3dfb,0xbf7cbf7e,0x3f093efc,0xbf58bf5f,0x3e893e60,0xbf77bf7a,0x3f1d3f13,0xbf4abf51,0x3eb83ea1,0xbf6fbf73,0x3f313f27,0xbf39bf42,
0x3eb83dfb,0xbf6fbf7e,0x3f393f5f,0x3f313efc,0x3f423f13,0xbf27bf51,0x3ea13f09,0x3f733f58,0x3f7a3f65,0xbe60bee6,0xbe2f3d97,0x3f7c3f7f,0x3f773f80,0x3e893cc9,0xbf1dbecf,0x3f4a3f6a,
0x3f1d3e60,0xbf4abf7a,0xbf5fbf13,0x3efc3f51,0x3f803f65,0xbcc9bee6,0xbf6fbf7f,0xbeb83d97,0x3f273f6a,0x3f423ecf,0xbea1bf31,0xbf73bf39,0xbe2f3e89,0x3f7c3f77,0x3f093dfb,0xbf58bf7e,
0x3f513ea1,0xbf13bf73,0xbe60bf42,0xbf7abf27,0x3f4a3f80,0x3f1d3cc9,0x3f5f3ecf,0xbefcbf6a,0xbeb83e89,0x3f6f3f77,0x3f393f7e,0x3f313dfb,0xbf7fbf58,0xbd973f09,0xbee63e2f,0x3f653f7c,
0x3f733ecf,0xbea1bf6a,0x3f7f3f39,0x3d97bf31,0x3e603f5f,0x3f7a3efc,0xbe2f3f1d,0x3f7c3f4a,0xbf7ebf13,0x3dfb3f51,0xbf77bf58,0xbe893f09,0xbcc9bf42,0xbf80bf27,0x3eb8bee6,0xbf6fbf65,
0x3f803efc,0xbcc9bf5f,0xbeb83f1d,0x3f6f3f4a,0xbee63f09,0x3f653f58,0xbf27bf7c,0xbf423e2f,0xbf13bf7f,0xbf513d97,0x3f7a3ea1,0xbe60bf73,0x3f7e3ecf,0xbdfbbf6a,0xbe893f31,0x3f773f39,
0x3f773f13,0x3e89bf51,0xbf4abf58,0xbf1d3f09,0xbf6a3d97,0x3ecf3f7f,0x3f803ea1,0xbcc9bf73,0x3ee6bf31,0xbf65bf39,0xbf423eb8,0x3f273f6f,0x3e603f7e,0x3f7a3dfb,0x3e2fbf5f,0xbf7cbefc,
0x3f583f27,0x3f09bf42,0x3f51bee6,0xbf13bf65,0xbf77becf,0xbe893f6a,0xbf1d3f31,0x3f4a3f39,0x3f803dfb,0xbcc9bf7e,0x3eb8bf5f,0xbf6fbefc,0xbf733e2f,0x3ea13f7c,0xbd973f7a,0x3f7f3e60,
0x3f273f39,0x3f42bf31,0x3ea13f6f,0x3f73beb8,0xbf13bf4a,0xbf513f1d,0xbe60bf77,0xbf7a3e89,0x3efc3f58,0x3f5fbf09,0x3dfb3f7c,0x3f7ebe2f,0xbecfbf65,0xbf6a3ee6,0xbcc9bf7f,0xbf803d97,
0x3ecf3f4a,0x3f6abf1d,0xbf803e89,0x3cc93f77,0x3d97bf7c,0xbf7f3e2f,0x3f653e60,0x3ee6bf7a,0xbf093f73,0x3f583ea1,0xbf13bf27,0xbf513f42,0x3f5fbf31,0xbefcbf39,0x3dfb3f6f,0x3f7ebeb8,
0x3dfb3f58,0x3f7ebf09,0x3e89bf7c,0xbf773e2f,0x3f31bf73,0xbf39bea1,0xbf6a3f42,0x3ecf3f27,0xbf7f3eb8,0xbd973f6f,0x3f653cc9,0x3ee6bf80,0x3f133efc,0x3f51bf5f,0xbe60bf4a,0xbf7a3f1d,
0xbe2f3f65,0x3f7cbee6,0x3f58bd97,0x3f09bf7f,0x3f7ebf31,0xbdfbbf39,0x3e89bf6f,0xbf773eb8,0xbecfbefc,0xbf6a3f5f,0xbf803f1d,0x3cc93f4a,0xbf423f7a,0x3f273e60,0x3ea13f13,0x3f73bf51,
0xbee63f6f,0x3f65beb8,0xbf423f80,0x3f273cc9,0x3f58be89,0x3f09bf77,0x3f133dfb,0x3f51bf7e,0x3f1dbf7c,0xbf4a3e2f,0x3f5fbf7a,0xbefcbe60,0xbf393d97,0xbf313f7f,0xbecfbea1,0xbf6a3f73,
0xbf313f77,0x3f39be89,0xbecfbdfb,0xbf6a3f7e,0x3ea13e60,0x3f73bf7a,0xbf7f3f51,0xbd973f13,0x3f7cbf42,0x3e2fbf27,0xbf093f65,0x3f58bee6,0x3f1dbf6f,0xbf4a3eb8,0x3efc3cc9,0x3f5fbf80,
0xbf5f3f7c,0x3efcbe2f,0x3f7ebf7a,0xbdfbbe60,0xbeb83f27,0x3f6fbf42,0x3f31bf65,0xbf393ee6,0x3ea13cc9,0x3f73bf80,0x3d97becf,0xbf7f3f6a,0x3f58bf1d,0x3f09bf4a,0xbf133e89,0xbf513f77,
0xbf7a3f7f,0x3e60bd97,0xbe2f3ea1,0x3f7cbf73,0xbf5f3f6f,0x3efcbeb8,0x3dfb3cc9,0x3f7ebf80,0xbf313f4a,0x3f39bf1d,0x3ecfbe89,0x3f6abf77,0xbee63f13,0x3f65bf51,0x3f27bf09,0x3f42bf58,
0xbf7f3f80,0xbd973cc9,0xbf653f6a,0xbee63ecf,0xbf7c3f7e,0xbe2f3dfb,0xbf583f5f,0xbf093efc,0xbf773f7a,0xbe893e60,0xbf4a3f51,0xbf1d3f13,0xbf6f3f73,0xbeb83ea1,0xbf393f42,0xbf313f27,
0xbf6f3f7e,0xbeb83dfb,0x3f31befc,0xbf393f5f,0xbf273f51,0xbf423f13,0x3f73bf58,0xbea13f09,0xbe603ee6,0xbf7a3f65,0x3f7cbf7f,0x3e2f3d97,0x3e89bcc9,0xbf773f80,0x3f4abf6a,0x3f1dbecf,
0xbf4a3f7a,0xbf1d3e60,0x3efcbf51,0x3f5fbf13,0xbcc93ee6,0xbf803f65,0xbeb8bd97,0x3f6fbf7f,0x3f42becf,0xbf273f6a,0xbf733f39,0x3ea1bf31,0x3f7cbf77,0x3e2f3e89,0xbf583f7e,0xbf093dfb,
0xbf133f73,0xbf513ea1,0xbf7a3f27,0x3e60bf42,0x3f1dbcc9,0xbf4a3f80,0xbefc3f6a,0xbf5f3ecf,0x3f6fbf77,0x3eb83e89,0x3f31bdfb,0xbf393f7e,0xbd97bf09,0x3f7fbf58,0x3f65bf7c,0x3ee63e2f,
0xbea13f6a,0xbf733ecf,0x3d973f31,0xbf7f3f39,0x3f7abefc,0xbe603f5f,0x3f7cbf4a,0x3e2f3f1d,0x3dfbbf51,0x3f7ebf13,0xbe89bf09,0x3f77bf58,0xbf803f27,0x3cc9bf42,0xbf6f3f65,0xbeb8bee6,
0xbcc93f5f,0xbf803efc,0x3f6fbf4a,0x3eb83f1d,0x3f65bf58,0x3ee63f09,0xbf42be2f,0x3f27bf7c,0xbf51bd97,0x3f13bf7f,0xbe603f73,0xbf7a3ea1,0xbdfb3f6a,0xbf7e3ecf,0x3f77bf39,0x3e893f31,
0x3e893f51,0xbf773f13,0xbf1dbf09,0x3f4abf58,0x3ecfbf7f,0x3f6a3d97,0xbcc93f73,0xbf803ea1,0xbf653f39,0xbee6bf31,0x3f27bf6f,0x3f423eb8,0x3f7abdfb,0xbe603f7e,0xbf7c3efc,0xbe2fbf5f,
0x3f093f42,0xbf583f27,0xbf133f65,0xbf51bee6,0xbe89bf6a,0x3f77becf,0x3f4abf39,0x3f1d3f31,0xbcc93f7e,0xbf803dfb,0xbf6f3efc,0xbeb8bf5f,0x3ea1bf7c,0x3f733e2f,0x3f7fbe60,0x3d973f7a,
0x3f423f31,0xbf273f39,0x3f733eb8,0xbea13f6f,0xbf51bf1d,0x3f13bf4a,0xbf7abe89,0x3e60bf77,0x3f5f3f09,0xbefc3f58,0x3f7e3e2f,0xbdfb3f7c,0xbf6abee6,0x3ecfbf65,0xbf80bd97,0x3cc9bf7f,
0x3f6a3f1d,0xbecf3f4a,0x3cc9bf77,0x3f803e89,0xbf7fbe2f,0xbd97bf7c,0x3ee63f7a,0xbf653e60,0x3f58bea1,0x3f093f73,0xbf51bf42,0x3f13bf27,0xbefc3f39,0xbf5fbf31,0x3f7e3eb8,0xbdfb3f6f,
0x3f7e3f09,0xbdfb3f58,0xbf77be2f,0xbe89bf7c,0xbf393ea1,0xbf31bf73,0x3ecfbf27,0x3f6a3f42,0xbd97bf6f,0x3f7f3eb8,0x3ee63f80,0xbf653cc9,0x3f513f5f,0xbf133efc,0xbf7abf1d,0x3e60bf4a,
0x3f7c3ee6,0x3e2f3f65,0x3f093f7f,0xbf58bd97,0xbdfb3f39,0xbf7ebf31,0xbf77beb8,0xbe89bf6f,0xbf6abf5f,0x3ecfbefc,0x3cc9bf4a,0x3f803f1d,0x3f27be60,0x3f423f7a,0x3f733f51,0xbea13f13,
0x3f653eb8,0x3ee63f6f,0x3f27bcc9,0x3f423f80,0x3f093f77,0xbf58be89,0x3f513f7e,0xbf133dfb,0xbf4abe2f,0xbf1dbf7c,0xbefc3e60,0xbf5fbf7a,0xbf31bf7f,0x3f393d97,0xbf6abf73,0x3ecfbea1,
0x3f393e89,0x3f313f77,0xbf6abf7e,0x3ecfbdfb,0x3f733f7a,0xbea13e60,0xbd97bf13,0x3f7f3f51,0x3e2f3f27,0xbf7cbf42,0x3f583ee6,0x3f093f65,0xbf4abeb8,0xbf1dbf6f,0x3f5f3f80,0xbefc3cc9,
0x3efc3e2f,0x3f5f3f7c,0xbdfb3e60,0xbf7ebf7a,0x3f6f3f42,0x3eb83f27,0xbf39bee6,0xbf31bf65,0x3f733f80,0xbea13cc9,0xbf7fbf6a,0xbd97becf,0x3f093f4a,0xbf58bf1d,0xbf51bf77,0x3f133e89,
0x3e603d97,0x3f7a3f7f,0x3f7c3f73,0x3e2f3ea1,0x3efc3eb8,0x3f5f3f6f,0x3f7e3f80,0xbdfb3cc9,0x3f393f1d,0x3f313f4a,0x3f6a3f77,0xbecfbe89,0x3f653f51,0x3ee63f13,0x3f423f58,0xbf27bf09,
0x3f423f39,0xbf27bf31,0x3f733f6f,0xbea1beb8,0x3f513f4a,0xbf13bf1d,0x3f7a3f77,0xbe60be89,0x3f5f3f58,0xbefcbf09,0x3f7e3f7c,0xbdfbbe2f,0x3f6a3f65,0xbecfbee6,0x3f803f7f,0xbcc9bd97,
0xbf6abf4a,0x3ecf3f1d,0xbcc9be89,0xbf80bf77,0xbf7fbf7c,0xbd973e2f,0x3ee63e60,0xbf65bf7a,0xbf58bf73,0xbf09bea1,0x3f513f27,0xbf13bf42,0xbefcbf31,0xbf5fbf39,0x3f7e3f6f,0xbdfbbeb8,
0x3f7e3f58,0xbdfbbf09,0xbf77bf7c,0xbe893e2f,0x3f393f73,0x3f313ea1,0xbecfbf42,0xbf6abf27,0xbd973eb8,0x3f7f3f6f,0x3ee63cc9,0xbf65bf80,0xbf51befc,0x3f133f5f,0x3f7a3f4a,0xbe60bf1d,
0xbf7cbf65,0xbe2f3ee6,0xbf093d97,0x3f583f7f,0xbdfbbf31,0xbf7ebf39,0xbf77bf6f,0xbe893eb8,0x3f6a3efc,0xbecfbf5f,0xbcc9bf1d,0xbf80bf4a,0x3f273f7a,0x3f423e60,0x3f733f13,0xbea1bf51,
0x3f653f6f,0x3ee6beb8,0x3f273f80,0x3f423cc9,0xbf093e89,0x3f583f77,0xbf51bdfb,0x3f133f7e,0xbf4abf7c,0xbf1d3e2f,0xbefcbf7a,0xbf5fbe60,0x3f31bd97,0xbf39bf7f,0x3f6a3ea1,0xbecfbf73,
0xbf39bf77,0xbf313e89,0x3f6a3dfb,0xbecfbf7e,0x3f733e60,0xbea1bf7a,0xbd973f51,0x3f7f3f13,0xbe2f3f42,0x3f7c3f27,0xbf58bf65,0xbf093ee6,0xbf4abf6f,0xbf1d3eb8,0x3f5f3cc9,0xbefcbf80,
0x3efc3f7c,0x3f5fbe2f,0xbdfbbf7a,0xbf7ebe60,0xbf6fbf27,0xbeb83f42,0x3f393f65,0x3f31bee6,0x3f733cc9,0xbea1bf80,0xbf7fbecf,0xbd973f6a,0xbf093f1d,0x3f583f4a,0x3f51be89,0xbf13bf77,
0xbe60bf7f,0xbf7a3d97,0xbf7cbea1,0xbe2f3f73,0x3efc3f6f,0x3f5fbeb8,0x3f7e3cc9,0xbdfbbf80,0xbf39bf4a,0xbf313f1d,0xbf6a3e89,0x3ecf3f77,0x3f653f13,0x3ee6bf51,0x3f42bf09,0xbf27bf58,
0xbd973f80,0x3f7f3cc9,0xbee63f6a,0x3f653ecf,0x3e2fbf7e,0xbf7cbdfb,0x3f09bf5f,0xbf58befc,0xbe893f7a,0x3f773e60,0xbf1d3f51,0x3f4a3f13,0x3eb8bf73,0xbf6fbea1,0x3f31bf42,0xbf39bf27,
0x3eb8bf7e,0xbf6fbdfb,0x3f393efc,0x3f31bf5f,0xbf423f51,0x3f273f13,0xbea1bf58,0xbf733f09,0x3f7abee6,0xbe60bf65,0xbe2f3f7f,0x3f7cbd97,0xbf77bcc9,0xbe893f80,0x3f1dbf6a,0xbf4abecf,
0xbf1d3f7a,0x3f4a3e60,0x3f5fbf51,0xbefcbf13,0x3f80bee6,0xbcc9bf65,0xbf6f3d97,0xbeb83f7f,0xbf27becf,0xbf423f6a,0x3ea13f39,0x3f73bf31,0xbe2f3f77,0x3f7cbe89,0x3f09bf7e,0xbf58bdfb,
0x3f51bf73,0xbf13bea1,0xbe60bf27,0xbf7a3f42,0xbf4abcc9,0xbf1d3f80,0xbf5f3f6a,0x3efc3ecf,0xbeb83f77,0x3f6fbe89,0x3f393dfb,0x3f31bf7e,0x3f7fbf09,0x3d97bf58,0x3ee6bf7c,0xbf653e2f,
0xbf733f6a,0x3ea13ecf,0xbf7f3f31,0xbd973f39,0x3e603efc,0x3f7abf5f,0xbe2f3f4a,0x3f7cbf1d,0x3f7ebf51,0xbdfbbf13,0x3f77bf09,0x3e89bf58,0xbcc9bf27,0xbf803f42,0x3eb8bf65,0xbf6f3ee6,
0x3f80bf5f,0xbcc9befc,0xbeb83f4a,0x3f6fbf1d,0x3ee6bf58,0xbf653f09,0x3f27be2f,0x3f42bf7c,0xbf133d97,0xbf513f7f,0x3f7abf73,0xbe60bea1,0xbf7e3f6a,0x3dfb3ecf,0x3e89bf39,0xbf773f31,
0xbf773f51,0xbe893f13,0x3f4abf09,0x3f1dbf58,0xbf6a3f7f,0x3ecfbd97,0x3f80bf73,0xbcc9bea1,0xbee63f39,0x3f65bf31,0x3f42bf6f,0xbf273eb8,0x3e603dfb,0x3f7abf7e,0x3e2fbefc,0xbf7c3f5f,
0x3f58bf42,0x3f09bf27,0x3f51bf65,0xbf133ee6,0x3f77bf6a,0x3e89becf,0x3f1dbf39,0xbf4a3f31,0x3f80bf7e,0xbcc9bdfb,0x3eb8befc,0xbf6f3f5f,0x3f73bf7c,0xbea13e2f,0x3d97be60,0xbf7f3f7a,
0xbf273f31,0xbf423f39,0xbea13eb8,0xbf733f6f,0xbf133f1d,0xbf513f4a,0xbe603e89,0xbf7a3f77,0xbefc3f09,0xbf5f3f58,0xbdfb3e2f,0xbf7e3f7c,0xbecf3ee6,0xbf6a3f65,0xbcc93d97,0xbf803f7f,
0x3ecfbf1d,0x3f6abf4a,0xbf803f77,0x3cc9be89,0xbd97be2f,0x3f7fbf7c,0xbf653f7a,0xbee63e60,0xbf093ea1,0x3f58bf73,0xbf133f42,0xbf513f27,0xbf5f3f39,0x3efcbf31,0xbdfb3eb8,0xbf7e3f6f,
0xbdfb3f09,0xbf7e3f58,0xbe89be2f,0x3f77bf7c,0x3f31bea1,0xbf393f73,0xbf6a3f27,0x3ecfbf42,0x3f7fbf6f,0x3d973eb8,0xbf653f80,0xbee63cc9,0x3f13bf5f,0x3f51befc,0xbe603f1d,0xbf7a3f4a,
0xbe2fbee6,0x3f7cbf65,0x3f58bf7f,0x3f093d97,0xbf7e3f39,0x3dfbbf31,0xbe89beb8,0x3f77bf6f,0xbecf3f5f,0xbf6a3efc,0xbf803f4a,0x3cc9bf1d,0x3f42be60,0xbf273f7a,0xbea13f51,0xbf733f13,
0x3ee63eb8,0xbf653f6f,0x3f42bcc9,0xbf273f80,0x3f58bf77,0x3f093e89,0x3f13bf7e,0x3f51bdfb,0xbf1dbe2f,0x3f4abf7c,0xbf5f3e60,0x3efcbf7a,0xbf393f7f,0xbf31bd97,0xbecf3f73,0xbf6a3ea1,
0xbf31be89,0x3f39bf77,0xbecf3f7e,0xbf6a3dfb,0xbea13f7a,0xbf733e60,0x3f7fbf13,0x3d973f51,0x3f7cbf27,0x3e2f3f42,0xbf09bee6,0x3f58bf65,0xbf1dbeb8,0x3f4abf6f,0xbefc3f80,0xbf5f3cc9,
0x3f5f3e2f,0xbefc3f7c,0xbf7e3e60,0x3dfbbf7a,0xbeb8bf42,0x3f6fbf27,0x3f313ee6,0xbf393f65,0xbea13f80,0xbf733cc9,0xbd97bf6a,0x3f7fbecf,0x3f58bf4a,0x3f093f1d,0xbf133f77,0xbf51be89,
0xbf7abd97,0x3e60bf7f,0xbe2fbf73,0x3f7cbea1,0x3f5f3eb8,0xbefc3f6f,0xbdfb3f80,0xbf7e3cc9,0xbf31bf1d,0x3f39bf4a,0x3ecfbf77,0x3f6a3e89,0x3ee63f51,0xbf653f13,0xbf273f58,0xbf42bf09,
0x3f7fbcc9,0x3d973f80,0x3f65becf,0x3ee63f6a,0xbf7c3dfb,0xbe2fbf7e,0xbf583efc,0xbf09bf5f,0x3f77be60,0x3e893f7a,0x3f4abf13,0x3f1d3f51,0xbf6f3ea1,0xbeb8bf73,0xbf393f27,0xbf31bf42,
0xbf6f3dfb,0xbeb8bf7e,0x3f313f5f,0xbf393efc,0x3f27bf13,0x3f423f51,0xbf73bf09,0x3ea1bf58,0xbe603f65,0xbf7abee6,0x3f7c3d97,0x3e2f3f7f,0xbe89bf80,0x3f77bcc9,0xbf4a3ecf,0xbf1dbf6a,
0x3f4abe60,0x3f1d3f7a,0xbefc3f13,0xbf5fbf51,0xbcc93f65,0xbf80bee6,0xbeb8bf7f,0x3f6f3d97,0xbf42bf6a,0x3f27becf,0x3f733f31,0xbea13f39,0x3f7c3e89,0x3e2f3f77,0xbf583dfb,0xbf09bf7e,
0xbf133ea1,0xbf51bf73,0xbf7abf42,0x3e60bf27,0xbf1dbf80,0x3f4abcc9,0x3efcbecf,0x3f5f3f6a,0x3f6f3e89,0x3eb83f77,0x3f313f7e,0xbf393dfb,0x3d973f58,0xbf7fbf09,0xbf65be2f,0xbee6bf7c,
0x3ea1becf,0x3f733f6a,0xbd97bf39,0x3f7f3f31,0x3f7a3f5f,0xbe603efc,0x3f7c3f1d,0x3e2f3f4a,0xbdfb3f13,0xbf7ebf51,0x3e893f58,0xbf77bf09,0xbf80bf42,0x3cc9bf27,0xbf6fbee6,0xbeb8bf65,
0xbcc93efc,0xbf80bf5f,0x3f6f3f1d,0x3eb83f4a,0xbf65bf09,0xbee6bf58,0x3f423f7c,0xbf27be2f,0xbf51bf7f,0x3f133d97,0xbe603ea1,0xbf7abf73,0x3dfbbecf,0x3f7e3f6a,0xbf77bf31,0xbe89bf39,
0xbe89bf13,0x3f773f51,0x3f1d3f58,0xbf4abf09,0x3ecf3d97,0x3f6a3f7f,0xbcc93ea1,0xbf80bf73,0x3f653f31,0x3ee63f39,0xbf27beb8,0xbf42bf6f,0x3f7a3f7e,0xbe603dfb,0xbf7cbf5f,0xbe2fbefc,
0x3f093f27,0xbf58bf42,0xbf13bee6,0xbf51bf65,0x3e893ecf,0xbf77bf6a,0xbf4abf31,0xbf1dbf39,0xbcc93dfb,0xbf80bf7e,0xbf6fbf5f,0xbeb8befc,0xbea1be2f,0xbf73bf7c,0xbf7fbf7a,0xbd97be60,
0x3f6e3f7a,0x3f1f3f28,0x3ec23ed0,0x3e2f3e48,0x3f583f63,0x3f0e3f17,0x3ea63eb4,0x3df93e15,0x3f443f4e,0x3efd3f06,0x3e8b3e99,0x3d953dc7,0x3f313f3a,0x3edf3eee,0x3e623e7c,0x3cc63d46,
0x3f583f62,0x3f133f1b,0x3eb53ec2,0x3e243e3b,0x3f453f4f,0x3f043f0b,0x3e9b3ea8,0x3de93e0c,0x3f333f3c,0x3eeb3ef9,0x3e823e8f,0x3d8b3dba,0x3f233f2b,0x3ecf3edd,0x3e533e6c,0x3cb93d39,
0x3f443f4d,0x3f073f0e,0x3ea83eb4,0x3e183e2e,0x3f343f3c,0x3ef33f00,0x3e903e9c,0x3dd93e02,0x3f243f2c,0x3ed93ee6,0x3e723e84,0x3d823dad,0x3f153f1c,0x3ec03ecc,0x3e453e5b,0x3cad3d2d,
0x3f323f39,0x3ef73f02,0x3e9b3ea6,0x3e0d3e22,0x3f233f2a,0x3edf3eeb,0x3e853e90,0x3dc93df1,0x3f153f1c,0x3ec83ed3,0x3e603e75,0x3d713da1,0x3f083f0f,0x3eb13ebc,0x3e363e4b,0x3ca03d20,
0x3f203f27,0x3ee13eec,0x3e8e3e98,0x3e023e15,0x3f133f1a,0x3ecc3ed6,0x3e743e84,0x3db93dde,0x3f073f0d,0x3eb73ec1,0x3e4e3e61,0x3d5e3d94,0x3ef83f02,0x3ea23eac,0x3e283e3b,0x3c943d14,
0x3f103f15,0x3ecc3ed6,0x3e813e8a,0x3ded3e08,0x3f053f0a,0x3eb93ec2,0x3e5f3e71,0x3da93dcb,0x3ef43eff,0x3ea63eaf,0x3e3c3e4d,0x3d4b3d87,0x3ee03eea,0x3e933e9d,0x3e193e2a,0x3c873d07,
0x3f003f05,0x3eb73ec0,0x3e6a3e7a,0x3dd73df6,0x3eed3ef6,0x3ea63eaf,0x3e4a3e5a,0x3d993db8,0x3edb3ee4,0x3e963e9e,0x3e2a3e3a,0x3d383d75,0x3ec93ed2,0x3e853e8d,0x3e0b3e1a,0x3c753cf5,
0x3ee23eeb,0x3ea33eab,0x3e513e5f,0x3dc13ddd,0x3ed23eda,0x3e943e9c,0x3e353e43,0x3d8a3da5,0x3ec23eca,0x3e853e8d,0x3e183e26,0x3d253d5c,0x3eb33eba,0x3e6e3e7c,0x3df93e0a,0x3c5c3cdc,
0x3ec63ecd,0x3e903e96,0x3e393e45,0x3dab3dc3,0x3eb83ebf,0x3e833e89,0x3e203e2c,0x3d743d92,0x3eaa3eb1,0x3e6b3e78,0x3e073e13,0x3d123d43,0x3e9d3ea3,0x3e523e5f,0x3ddc3df5,0x3c433cc3,
0x3eaa3eb0,0x3e793e82,0x3e203e2b,0x3d953daa,0x3e9f3ea4,0x3e623e6d,0x3e0b3e15,0x3d543d7f,0x3e933e99,0x3e4c3e57,0x3dea3e00,0x3cff3d2a,0x3e883e8d,0x3e363e41,0x3dbf3dd5,0x3c2a3caa,
0x3e903e94,0x3e533e5c,0x3e083e11,0x3d7d3d91,0x3e863e8b,0x3e403e49,0x3dec3dfe,0x3d353d59,0x3e793e81,0x3e2d3e37,0x3dc73dda,0x3cd93d11,0x3e663e6f,0x3e1b3e24,0x3da33db5,0x3c113c91,
0x3e6b3e73,0x3e2d3e35,0x3de13df0,0x3d513d6f,0x3e5c3e63,0x3e1e3e26,0x3dc33dd2,0x3d153d33,0x3e4c3e54,0x3e0f3e16,0x3da53db4,0x3cb33cef,0x3e3d3e44,0x3dff3e07,0x3d863d95,0x3bef3c6f,
0x3e393e3f,0x3e083e0e,0x3db13dbd,0x3d253d3d,0x3e2c3e32,0x3df93e02,0x3d993da5,0x3cec3d0d,0x3e203e26,0x3de13ded,0x3d823d8e,0x3c8d3cbd,0x3e143e1a,0x3dc93dd5,0x3d543d6c,0x3bbc3c3d,
0x3e073e0b,0x3dc73dd0,0x3d823d8a,0x3cf23d0a,0x3dfc3e02,0x3db63dbf,0x3d613d72,0x3cad3ccf,0x3dea3df3,0x3da53dad,0x3d3e3d50,0x3c4f3c8a,0x3dd93de2,0x3d933d9c,0x3d1c3d2d,0x3b8a3c0a,
0x3dab3db0,0x3d7d3d84,0x3d253d30,0x3c9a3cb0,0x3da03da5,0x3d673d72,0x3d0f3d1a,0x3c5c3c84,0x3d953d9a,0x3d513d5c,0x3cf23d04,0x3c043c30,0x3d8a3d8f,0x3d3b3d46,0x3cc63cdc,0x3b303bb0,
0x3d123d17,0x3cd93ce2,0x3c8d3c97,0x3c043c17,0x3d093d0d,0x3cc63ccf,0x3c753c84,0x3bbc3be2,0x3cff3d04,0x3cb33cbd,0x3c4f3c62,0x3b623b97,0x3cec3cf5,0x3ca03caa,0x3c2a3c3d,0x3a973b17,
0xbc43bc49,0xbc11bc17,0xbbbcbbc9,0xbb30bb49,0xbc36bc3d,0xbc04bc0a,0xbba3bbb0,0xbafbbb17,0xbc2abc30,0xbbefbbfb,0xbb8abb97,0xba97bac9,0xbc1dbc23,0xbbd6bbe2,0xbb62bb7b,0xb9c9ba49,
0xbd74bd7c,0xbd35bd3d,0xbcecbcfb,0xbc5cbc7b,0xbd64bd6c,0xbd25bd2d,0xbcccbcdc,0xbc1dbc3d,0xbd54bd5c,0xbd15bd1d,0xbcadbcbd,0xbbbcbbfb,0xbd45bd4c,0xbd06bd0d,0xbc8dbc9d,0xbafbbb7b,
0xbddcbde3,0xbda3bdaa,0xbd54bd62,0xbcc6bce2,0xbdcebdd5,0xbd95bd9c,0xbd38bd46,0xbc8dbcaa,0xbdbfbdc7,0xbd86bd8e,0xbd1cbd2a,0xbc2abc62,0xbdb1bdb8,0xbd71bd7f,0xbcffbd0d,0xbb62bbe2,
0xbe20be25,0xbdecbdf6,0xbd99bda4,0xbd0fbd23,0xbe15be1a,0xbdd7bde2,0xbd85bd8f,0xbcccbcf5,0xbe0bbe10,0xbdc3bdcd,0xbd61bd75,0xbc75bca3,0xbe00be05,0xbdaebdb8,0xbd38bd4c,0xbba3bc23,
0xbe52be59,0xbe1bbe22,0xbdc9bdd6,0xbd3bbd56,0xbe44be4b,0xbe0dbe14,0xbdaebdbb,0xbd06bd20,0xbe36be3d,0xbdffbe06,0xbd93bda1,0xbca0bcd6,0xbe28be2f,0xbde4bdf1,0xbd71bd86,0xbbd6bc56,
0xbe83be87,0xbe40be48,0xbdf9be05,0xbd67bd84,0xbe74be7c,0xbe2fbe37,0xbdd7bde8,0xbd25bd46,0xbe62be6b,0xbe1ebe26,0xbdb6bdc7,0xbcc6bd04,0xbe51be5a,0xbe0dbe15,0xbd95bda5,0xbc04bc84,
0xbe9dbea2,0xbe66be70,0xbe14be1e,0xbd8abd9d,0xbe92be97,0xbe51be5b,0xbe00be0a,0xbd45bd6c,0xbe88be8d,0xbe3dbe47,0xbdd9bded,0xbcecbd1d,0xbe7abe82,0xbe28be32,0xbdb1bdc5,0xbc1dbc9d,
0xbeb8bebe,0xbe86be8c,0xbe2cbe38,0xbda0bdb7,0xbeabbeb1,0xbe74be80,0xbe15be21,0xbd64bd89,0xbe9fbea5,0xbe5cbe68,0xbdfcbe09,0xbd09bd36,0xbe92be98,0xbe44be50,0xbdcebde5,0xbc36bcb6,
0xbed4bedb,0xbe99bea0,0xbe45be52,0xbdb6bdd0,0xbec5becc,0xbe8bbe92,0xbe2abe37,0xbd82bd9c,0xbeb6bebd,0xbe7bbe84,0xbe0fbe1d,0xbd1cbd50,0xbea8beaf,0xbe60be6d,0xbdeabe02,0xbc4fbccf,
0xbef1befa,0xbeadbeb5,0xbe5dbe6d,0xbdccbde9,0xbedfbee8,0xbe9dbea5,0xbe3fbe4e,0xbd92bdaf,0xbecebed7,0xbe8dbe95,0xbe21be30,0xbd2ebd69,0xbebebec6,0xbe7cbe86,0xbe03be12,0xbc68bce9,
0xbf08bf0d,0xbec2becb,0xbe76be84,0xbde2be01,0xbefbbf03,0xbeafbeb9,0xbe54be65,0xbda1bdc2,0xbee7bef1,0xbe9ebea7,0xbe33be44,0xbd41bd81,0xbed4bede,0xbe8cbe95,0xbe12be22,0xbc81bd01,
0xbf18bf1e,0xbed7bee1,0xbe88be91,0xbdf9be0e,0xbf0cbf12,0xbec2becc,0xbe6abe7c,0xbdb1bdd5,0xbf01bf06,0xbeaebeb8,0xbe45be57,0xbd54bd8e,0xbeecbef6,0xbe9bbea4,0xbe20be32,0xbc8dbd0d,
0xbf29bf30,0xbeecbef8,0xbe94be9f,0xbe07be1b,0xbf1bbf22,0xbed5bee1,0xbe7fbe8a,0xbdc1bde8,0xbf0ebf15,0xbebfbeca,0xbe57be6b,0xbd67bd9a,0xbf02bf08,0xbea9beb4,0xbe2fbe43,0xbc9abd1a,
0xbf3bbf43,0xbf01bf08,0xbea1bead,0xbe13be28,0xbf2bbf33,0xbee9bef6,0xbe8bbe96,0xbdd1bdfb,0xbf1dbf24,0xbed0bedc,0xbe69be7f,0xbd7abda7,0xbf0fbf15,0xbeb8bec4,0xbe3dbe53,0xbca7bd27,
0xbf4ebf57,0xbf0dbf14,0xbeaebebb,0xbe1ebe35,0xbf3cbf45,0xbefdbf06,0xbe96bea2,0xbde1be07,0xbf2bbf34,0xbee2beef,0xbe7bbe89,0xbd86bdb4,0xbf1cbf23,0xbec8bed5,0xbe4cbe63,0xbcb3bd33,
0xbf63bf6e,0xbf19bf21,0xbebbbec9,0xbe29be42,0xbf4ebf58,0xbf09bf11,0xbea1beae,0xbdf1be11,0xbf3bbf45,0xbef4bf01,0xbe87be94,0xbd90bdc0,0xbf29bf32,0xbed7bee5,0xbe5bbe74,0xbcc0bd40,
0xbcc68000,0xbe62be48,0xbedfbed0,0xbf31bf28,0xbd95bd46,0xbe8bbe7c,0xbefdbeee,0xbf44bf3a,0xbdf9bdc7,0xbea6be99,0xbf0ebf06,0xbf58bf4e,0xbe2fbe15,0xbec2beb4,0xbf1fbf17,0xbf6ebf63,
0xbcb98000,0xbe53be3b,0xbecfbec2,0xbf23bf1b,0xbd8bbd39,0xbe82be6c,0xbeebbedd,0xbf33bf2b,0xbde9bdba,0xbe9bbe8f,0xbf04bef9,0xbf45bf3c,0xbe24be0c,0xbeb5bea8,0xbf13bf0b,0xbf58bf4f,
0xbcad8000,0xbe45be2e,0xbec0beb4,0xbf15bf0e,0xbd82bd2d,0xbe72be5b,0xbed9becc,0xbf24bf1c,0xbdd9bdad,0xbe90be84,0xbef3bee6,0xbf34bf2c,0xbe18be02,0xbea8be9c,0xbf07bf00,0xbf44bf3c,
0xbca08000,0xbe36be22,0xbeb1bea6,0xbf08bf02,0xbd71bd20,0xbe60be4b,0xbec8bebc,0xbf15bf0f,0xbdc9bda1,0xbe85be75,0xbedfbed3,0xbf23bf1c,0xbe0dbdf1,0xbe9bbe90,0xbef7beeb,0xbf32bf2a,
0xbc948000,0xbe28be15,0xbea2be98,0xbef8beec,0xbd5ebd14,0xbe4ebe3b,0xbeb7beac,0xbf07bf02,0xbdb9bd94,0xbe74be61,0xbeccbec1,0xbf13bf0d,0xbe02bdde,0xbe8ebe84,0xbee1bed6,0xbf20bf1a,
0xbc878000,0xbe19be08,0xbe93be8a,0xbee0bed6,0xbd4bbd07,0xbe3cbe2a,0xbea6be9d,0xbef4beea,0xbda9bd87,0xbe5fbe4d,0xbeb9beaf,0xbf05beff,0xbdedbdcb,0xbe81be71,0xbeccbec2,0xbf10bf0a,
0xbc758000,0xbe0bbdf6,0xbe85be7a,0xbec9bec0,0xbd38bcf5,0xbe2abe1a,0xbe96be8d,0xbedbbed2,0xbd99bd75,0xbe4abe3a,0xbea6be9e,0xbeedbee4,0xbdd7bdb8,0xbe6abe5a,0xbeb7beaf,0xbf00bef6,
0xbc5c8000,0xbdf9bddd,0xbe6ebe5f,0xbeb3beab,0xbd25bcdc,0xbe18be0a,0xbe85be7c,0xbec2beba,0xbd8abd5c,0xbe35be26,0xbe94be8d,0xbed2beca,0xbdc1bda5,0xbe51be43,0xbea3be9c,0xbee2beda,
0xbc438000,0xbddcbdc3,0xbe52be45,0xbe9dbe96,0xbd12bcc3,0xbe07bdf5,0xbe6bbe5f,0xbeaabea3,0xbd74bd43,0xbe20be13,0xbe83be78,0xbeb8beb1,0xbdabbd92,0xbe39be2c,0xbe90be89,0xbec6bebf,
0xbc2a8000,0xbdbfbdaa,0xbe36be2b,0xbe88be82,0xbcffbcaa,0xbdeabdd5,0xbe4cbe41,0xbe93be8d,0xbd54bd2a,0xbe0bbe00,0xbe62be57,0xbe9fbe99,0xbd95bd7f,0xbe20be15,0xbe79be6d,0xbeaabea4,
0xbc118000,0xbda3bd91,0xbe1bbe11,0xbe66be5c,0xbcd9bc91,0xbdc7bdb5,0xbe2dbe24,0xbe79be6f,0xbd35bd11,0xbdecbdda,0xbe40be37,0xbe86be81,0xbd7dbd59,0xbe08bdfe,0xbe53be49,0xbe90be8b,
0xbbef8000,0xbd86bd6f,0xbdffbdf0,0xbe3dbe35,0xbcb3bc6f,0xbda5bd95,0xbe0fbe07,0xbe4cbe44,0xbd15bcef,0xbdc3bdb4,0xbe1ebe16,0xbe5cbe54,0xbd51bd33,0xbde1bdd2,0xbe2dbe26,0xbe6bbe63,
0xbbbc8000,0xbd54bd3d,0xbdc9bdbd,0xbe14be0e,0xbc8dbc3d,0xbd82bd6c,0xbde1bdd5,0xbe20be1a,0xbcecbcbd,0xbd99bd8e,0xbdf9bded,0xbe2cbe26,0xbd25bd0d,0xbdb1bda5,0xbe08be02,0xbe39be32,
0xbb8a8000,0xbd1cbd0a,0xbd93bd8a,0xbdd9bdd0,0xbc4fbc0a,0xbd3ebd2d,0xbda5bd9c,0xbdeabde2,0xbcadbc8a,0xbd61bd50,0xbdb6bdad,0xbdfcbdf3,0xbcf2bccf,0xbd82bd72,0xbdc7bdbf,0xbe07be02,
0xbb308000,0xbcc6bcb0,0xbd3bbd30,0xbd8abd84,0xbc04bbb0,0xbcf2bcdc,0xbd51bd46,0xbd95bd8f,0xbc5cbc30,0xbd0fbd04,0xbd67bd5c,0xbda0bd9a,0xbc9abc84,0xbd25bd1a,0xbd7dbd72,0xbdabbda5,
0xba978000,0xbc2abc17,0xbca0bc97,0xbcecbce2,0xbb62bb17,0xbc4fbc3d,0xbcb3bcaa,0xbcffbcf5,0xbbbcbb97,0xbc75bc62,0xbcc6bcbd,0xbd09bd04,0xbc04bbe2,0xbc8dbc84,0xbcd9bccf,0xbd12bd0d,
0x39c90000,0x3b623b49,0x3bd63bc9,0x3c1d3c17,0x3a973a49,0x3b8a3b7b,0x3bef3be2,0x3c2a3c23,0x3afb3ac9,0x3ba33b97,0x3c043bfb,0x3c363c30,0x3b303b17,0x3bbc3bb0,0x3c113c0a,0x3c433c3d,
0x3afb0000,0x3c8d3c7b,0x3d063cfb,0x3d453d3d,0x3bbc3b7b,0x3cad3c9d,0x3d153d0d,0x3d543d4c,0x3c1d3bfb,0x3ccc3cbd,0x3d253d1d,0x3d643d5c,0x3c5c3c3d,0x3cec3cdc,0x3d353d2d,0x3d743d6c,
0x3b620000,0x3cff3ce2,0x3d713d62,0x3db13daa,0x3c2a3be2,0x3d1c3d0d,0x3d863d7f,0x3dbf3db8,0x3c8d3c62,0x3d383d2a,0x3d953d8e,0x3dce3dc7,0x3cc63caa,0x3d543d46,0x3da33d9c,0x3ddc3dd5,
0x3ba30000,0x3d383d23,0x3dae3da4,0x3e003df6,0x3c753c23,0x3d613d4c,0x3dc33db8,0x3e0b3e05,0x3ccc3ca3,0x3d853d75,0x3dd73dcd,0x3e153e10,0x3d0f3cf5,0x3d993d8f,0x3dec3de2,0x3e203e1a,
0x3bd60000,0x3d713d56,0x3de43dd6,0x3e283e22,0x3ca03c56,0x3d933d86,0x3dff3df1,0x3e363e2f,0x3d063cd6,0x3dae3da1,0x3e0d3e06,0x3e443e3d,0x3d3b3d20,0x3dc93dbb,0x3e1b3e14,0x3e523e4b,
0x3c040000,0x3d953d84,0x3e0d3e05,0x3e513e48,0x3cc63c84,0x3db63da5,0x3e1e3e15,0x3e623e5a,0x3d253d04,0x3dd73dc7,0x3e2f3e26,0x3e743e6b,0x3d673d46,0x3df93de8,0x3e403e37,0x3e833e7c,
0x3c1d0000,0x3db13d9d,0x3e283e1e,0x3e7a3e70,0x3cec3c9d,0x3dd93dc5,0x3e3d3e32,0x3e883e82,0x3d453d1d,0x3e003ded,0x3e513e47,0x3e923e8d,0x3d8a3d6c,0x3e143e0a,0x3e663e5b,0x3e9d3e97,
0x3c360000,0x3dce3db7,0x3e443e38,0x3e923e8c,0x3d093cb6,0x3dfc3de5,0x3e5c3e50,0x3e9f3e98,0x3d643d36,0x3e153e09,0x3e743e68,0x3eab3ea5,0x3da03d89,0x3e2c3e21,0x3e863e80,0x3eb83eb1,
0x3c4f0000,0x3dea3dd0,0x3e603e52,0x3ea83ea0,0x3d1c3ccf,0x3e0f3e02,0x3e7b3e6d,0x3eb63eaf,0x3d823d50,0x3e2a3e1d,0x3e8b3e84,0x3ec53ebd,0x3db63d9c,0x3e453e37,0x3e993e92,0x3ed43ecc,
0x3c680000,0x3e033de9,0x3e7c3e6d,0x3ebe3eb5,0x3d2e3ce9,0x3e213e12,0x3e8d3e86,0x3ece3ec6,0x3d923d69,0x3e3f3e30,0x3e9d3e95,0x3edf3ed7,0x3dcc3daf,0x3e5d3e4e,0x3ead3ea5,0x3ef13ee8,
0x3c810000,0x3e123e01,0x3e8c3e84,0x3ed43ecb,0x3d413d01,0x3e333e22,0x3e9e3e95,0x3ee73ede,0x3da13d81,0x3e543e44,0x3eaf3ea7,0x3efb3ef1,0x3de23dc2,0x3e763e65,0x3ec23eb9,0x3f083f03,
0x3c8d0000,0x3e203e0e,0x3e9b3e91,0x3eec3ee1,0x3d543d0d,0x3e453e32,0x3eae3ea4,0x3f013ef6,0x3db13d8e,0x3e6a3e57,0x3ec23eb8,0x3f0c3f06,0x3df93dd5,0x3e883e7c,0x3ed73ecc,0x3f183f12,
0x3c9a0000,0x3e2f3e1b,0x3ea93e9f,0x3f023ef8,0x3d673d1a,0x3e573e43,0x3ebf3eb4,0x3f0e3f08,0x3dc13d9a,0x3e7f3e6b,0x3ed53eca,0x3f1b3f15,0x3e073de8,0x3e943e8a,0x3eec3ee1,0x3f293f22,
0x3ca70000,0x3e3d3e28,0x3eb83ead,0x3f0f3f08,0x3d7a3d27,0x3e693e53,0x3ed03ec4,0x3f1d3f15,0x3dd13da7,0x3e8b3e7f,0x3ee93edc,0x3f2b3f24,0x3e133dfb,0x3ea13e96,0x3f013ef6,0x3f3b3f33,
0x3cb30000,0x3e4c3e35,0x3ec83ebb,0x3f1c3f14,0x3d863d33,0x3e7b3e63,0x3ee23ed5,0x3f2b3f23,0x3de13db4,0x3e963e89,0x3efd3eef,0x3f3c3f34,0x3e1e3e07,0x3eae3ea2,0x3f0d3f06,0x3f4e3f45,
0x3cc00000,0x3e5b3e42,0x3ed73ec9,0x3f293f21,0x3d903d40,0x3e873e74,0x3ef43ee5,0x3f3b3f32,0x3df13dc0,0x3ea13e94,0x3f093f01,0x3f4e3f45,0x3e293e11,0x3ebb3eae,0x3f193f11,0x3f633f58,
0x3f7f3f80,0x3f653f6b,0x3f2a3f33,0x3eaa3ec1,0x3f7c3f7e,0x3f593f60,0x3f163f20,0x3e753e92,0x3f773f7a,0x3f4b3f53,0x3f023f0c,0x3e143e45,0x3f6f3f73,0x3f3b3f44,0x3ed83eee,0x3d463dc6,
0x3f7c3f7e,0x3f5d3f63,0x3f213f2a,0x3e9f3eb5,0x3f773f7a,0x3f503f57,0x3f0e3f18,0x3e663e89,0x3f713f74,0x3f423f49,0x3ef43f04,0x3e0b3e38,0x3f683f6c,0x3f323f3a,0x3ecb3ee0,0x3d393db9,
0x3f773f7a,0x3f533f59,0x3f173f20,0x3e953eaa,0x3f713f74,0x3f463f4d,0x3f053f0f,0x3e563e80,0x3f693f6d,0x3f383f3f,0x3ee53ef8,0x3e013e2c,0x3f5f3f64,0x3f283f30,0x3ebe3ed2,0x3d2d3dad,
0x3f703f73,0x3f483f4f,0x3f0e3f16,0x3e8a3e9e,0x3f683f6c,0x3f3b3f42,0x3ef93f05,0x3e473e6e,0x3f5f3f64,0x3f2d3f34,0x3ed63ee8,0x3df03e20,0x3f543f5a,0x3f1e3f26,0x3eb13ec3,0x3d203da0,
0x3f663f6a,0x3f3d3f43,0x3f043f0c,0x3e803e92,0x3f5d3f62,0x3f303f36,0x3ee73ef8,0x3e383e5c,0x3f543f59,0x3f223f29,0x3ec63ed7,0x3ddd3e13,0x3f493f4e,0x3f133f1b,0x3ea33eb5,0x3d143d94,
0x3f5a3f5f,0x3f303f36,0x3ef33f01,0x3e6a3e86,0x3f513f56,0x3f233f2a,0x3ed53ee4,0x3e283e49,0x3f473f4c,0x3f163f1d,0x3eb63ec5,0x3dca3e07,0x3f3c3f42,0x3f083f0f,0x3e963ea6,0x3d073d87,
0x3f4d3f51,0x3f233f28,0x3ede3eec,0x3e553e73,0x3f433f48,0x3f163f1d,0x3ec23ed0,0x3e193e37,0x3f393f3e,0x3f0a3f10,0x3ea53eb4,0x3db83df4,0x3f2e3f34,0x3ef93f03,0x3e883e97,0x3cf53d75,
0x3f3d3f42,0x3f143f1a,0x3ec93ed5,0x3e3f3e5a,0x3f343f39,0x3f093f0f,0x3eaf3ebc,0x3e093e24,0x3f2a3f2f,0x3efa3f03,0x3e953ea2,0x3da53ddb,0x3f1f3f25,0x3ee23eee,0x3e753e88,0x3cdc3d5c,
0x3f2c3f31,0x3f053f0a,0x3eb33ebe,0x3e2a3e42,0x3f233f28,0x3ef53f00,0x3e9c3ea7,0x3df33e12,0x3f193f1e,0x3ee03eea,0x3e843e90,0x3d923dc2,0x3f0f3f14,0x3ec93ed4,0x3e593e71,0x3cc33d43,
0x3f193f1d,0x3eeb3ef4,0x3e9c3ea7,0x3e143e29,0x3f113f15,0x3ed83ee1,0x3e883e92,0x3dd43dfe,0x3f083f0c,0x3ec43ece,0x3e673e7c,0x3d7e3da9,0x3efd3f03,0x3eb13eba,0x3e3e3e53,0x3caa3d2a,
0x3f053f09,0x3eca3ed2,0x3e863e8f,0x3dfc3e10,0x3efb3f01,0x3eb93ec2,0x3e693e7a,0x3db43dd8,0x3eeb3ef3,0x3ea83eb1,0x3e453e57,0x3d593d90,0x3edb3ee3,0x3e973ea0,0x3e223e34,0x3c913d10,
0x3ee03ee6,0x3ea83eaf,0x3e5e3e6d,0x3dd13dee,0x3ed23ed9,0x3e9a3ea1,0x3e413e4f,0x3d953db3,0x3ec43ecb,0x3e8c3e93,0x3e233e32,0x3d333d6f,0x3eb63ebd,0x3e7b3e85,0x3e063e15,0x3c6f3cef,
0x3eb33eb8,0x3e863e8c,0x3e303e3b,0x3da53dbc,0x3ea83ead,0x3e753e80,0x3e193e24,0x3d6b3d8d,0x3e9c3ea2,0x3e5e3e6a,0x3e013e0d,0x3d0d3d3c,0x3e913e97,0x3e473e53,0x3dd43deb,0x3c3c3cbc,
0x3e843e89,0x3e453e4e,0x3e013e0a,0x3d723d8a,0x3e783e80,0x3e343e3d,0x3de03df1,0x3d2d3d4f,0x3e673e70,0x3e233e2c,0x3dbe3dcf,0x3ccf3d0a,0x3e563e5f,0x3e123e1b,0x3d9b3dad,0x3c0a3c8a,
0x3e2a3e2f,0x3dfc3e04,0x3da53db0,0x3d1a3d30,0x3e1f3e24,0x3de63df1,0x3d8f3d9a,0x3cdc3d04,0x3e143e19,0x3dd13ddb,0x3d723d84,0x3c843cb0,0x3e093e0e,0x3dbb3dc6,0x3d463d5c,0x3bb03c30,
0x3d923d97,0x3d593d62,0x3d0d3d17,0x3c843c97,0x3d893d8d,0x3d463d4f,0x3cf53d04,0x3c3c3c62,0x3d7e3d84,0x3d333d3c,0x3ccf3ce2,0x3be23c17,0x3d6b3d75,0x3d203d2a,0x3caa3cbc,0x3b173b97,
0xbcc3bcc9,0xbc91bc97,0xbc3cbc49,0xbbb0bbc9,0xbcb6bcbc,0xbc84bc8a,0xbc23bc30,0xbb7bbb97,0xbcaabcb0,0xbc6fbc7b,0xbc0abc17,0xbb17bb49,0xbc9dbca3,0xbc56bc62,0xbbe2bbfb,0xba49bac9,
0xbdf3bdfb,0xbdb4bdbc,0xbd6bbd7b,0xbcdcbcfb,0xbde3bdeb,0xbda5bdad,0xbd4cbd5c,0xbc9dbcbc,0xbdd4bddb,0xbd95bd9d,0xbd2dbd3c,0xbc3cbc7b,0xbdc4bdcc,0xbd85bd8d,0xbd0dbd1d,0xbb7bbbfb,
0xbe59be60,0xbe22be29,0xbdd4bde2,0xbd46bd62,0xbe4cbe53,0xbe14be1b,0xbdb8bdc6,0xbd0dbd2a,0xbe3ebe45,0xbe06be0d,0xbd9bbda9,0xbcaabce2,0xbe30be37,0xbdf0bdfe,0xbd7ebd8d,0xbbe2bc62,
0xbe9cbea1,0xbe69be73,0xbe19be23,0xbd8fbda3,0xbe92be97,0xbe55be5f,0xbe04be0e,0xbd4cbd75,0xbe88be8d,0xbe41be4b,0xbde0bdf4,0xbcf5bd23,0xbe7dbe83,0xbe2dbe37,0xbdb8bdcc,0xbc23bca3,
0xbec9becf,0xbe97be9e,0xbe47be54,0xbdbbbdd5,0xbebdbec3,0xbe8abe91,0xbe2dbe3a,0xbd85bda0,0xbeb1beb7,0xbe7bbe84,0xbe12be20,0xbd20bd56,0xbea4beaa,0xbe61be6e,0xbdf0be05,0xbc56bcd6,
0xbef5befc,0xbeb9bec1,0xbe75be82,0xbde6be04,0xbee7beee,0xbeaabeb2,0xbe55be65,0xbda5bdc6,0xbed8bedf,0xbe9abea2,0xbe34be45,0xbd46bd84,0xbec9bed0,0xbe8abe92,0xbe14be24,0xbc84bd04,
0xbf0fbf13,0xbedbbee3,0xbe91be9b,0xbe09be1c,0xbf07bf0b,0xbec9bed2,0xbe7dbe88,0xbdc4bdeb,0xbefdbf03,0xbeb6bec0,0xbe56be6a,0xbd6bbd9d,0xbeecbef5,0xbea4bead,0xbe30be43,0xbc9dbd1d,
0xbf23bf27,0xbefbbf02,0xbea8beb2,0xbe1fbe35,0xbf1abf1e,0xbee7bef1,0xbe92be9d,0xbde3be08,0xbf11bf15,0xbed2bedc,0xbe78be87,0xbd89bdb6,0xbf07bf0c,0xbebdbec8,0xbe4cbe62,0xbcb6bd36,
0xbf35bf39,0xbf0dbf12,0xbebebeca,0xbe34be4e,0xbf2bbf30,0xbf02bf07,0xbea5beb2,0xbe01be1b,0xbf22bf27,0xbeedbef8,0xbe8dbe99,0xbd9bbdcf,0xbf17bf1d,0xbed6bee1,0xbe67be80,0xbccfbd4f,
0xbf45bf4a,0xbf1bbf21,0xbed3bee1,0xbe4abe66,0xbf3cbf41,0xbf10bf16,0xbeb9bec6,0xbe11be2e,0xbf32bf37,0xbf03bf0a,0xbe9dbeab,0xbdaebde8,0xbf27bf2c,0xbeeebefa,0xbe81be8f,0xbce8bd68,
0xbf54bf58,0xbf29bf2f,0xbee9bef7,0xbe60be7f,0xbf4abf4f,0xbf1dbf23,0xbeccbeda,0xbe20be40,0xbf40bf45,0xbf10bf17,0xbeaebebd,0xbdc1be00,0xbf35bf3b,0xbf02bf09,0xbe8fbe9e,0xbd01bd81,
0xbf61bf65,0xbf37bf3d,0xbefdbf06,0xbe75be8c,0xbf58bf5c,0xbf2abf30,0xbedebeee,0xbe30be53,0xbf4ebf53,0xbf1cbf23,0xbebebece,0xbdd4be0d,0xbf42bf48,0xbf0ebf15,0xbe9cbead,0xbd0dbd8d,
0xbf6bbf6f,0xbf43bf49,0xbf09bf11,0xbe85be98,0xbf63bf67,0xbf36bf3c,0xbef0bf01,0xbe3fbe65,0xbf59bf5e,0xbf28bf2f,0xbecebedf,0xbde6be19,0xbf4fbf54,0xbf19bf20,0xbeaabebc,0xbd1abd9a,
0xbf74bf77,0xbf4ebf54,0xbf13bf1b,0xbe90bea4,0xbf6dbf70,0xbf41bf48,0xbf01bf0a,0xbe4fbe77,0xbf64bf68,0xbf33bf3a,0xbeddbef0,0xbdf9be26,0xbf5abf5f,0xbf23bf2b,0xbeb7beca,0xbd26bda6,
0xbf7abf7c,0xbf58bf5e,0xbf1cbf25,0xbe9abeaf,0xbf74bf77,0xbf4bbf52,0xbf0abf13,0xbe5ebe85,0xbf6dbf71,0xbf3dbf44,0xbeedbf00,0xbe06be32,0xbf63bf68,0xbf2dbf35,0xbec4bed9,0xbd33bdb3,
0xbf7ebf7f,0xbf61bf67,0xbf25bf2e,0xbea5bebb,0xbf7abf7c,0xbf55bf5b,0xbf12bf1c,0xbe6dbe8e,0xbf74bf77,0xbf47bf4e,0xbefcbf08,0xbe0fbe3f,0xbf6cbf70,0xbf37bf3f,0xbed1bee7,0xbd40bdbf,
0xbd468000,0xbed8bec1,0xbf3bbf33,0xbf6fbf6b,0xbe14bdc6,0xbf02beee,0xbf4bbf44,0xbf77bf73,0xbe75be45,0xbf16bf0c,0xbf59bf53,0xbf7cbf7a,0xbeaabe92,0xbf2abf20,0xbf65bf60,0xbf7fbf7e,
0xbd398000,0xbecbbeb5,0xbf32bf2a,0xbf68bf63,0xbe0bbdb9,0xbef4bee0,0xbf42bf3a,0xbf71bf6c,0xbe66be38,0xbf0ebf04,0xbf50bf49,0xbf77bf74,0xbe9fbe89,0xbf21bf18,0xbf5dbf57,0xbf7cbf7a,
0xbd2d8000,0xbebebeaa,0xbf28bf20,0xbf5fbf59,0xbe01bdad,0xbee5bed2,0xbf38bf30,0xbf69bf64,0xbe56be2c,0xbf05bef8,0xbf46bf3f,0xbf71bf6d,0xbe95be80,0xbf17bf0f,0xbf53bf4d,0xbf77bf74,
0xbd208000,0xbeb1be9e,0xbf1ebf16,0xbf54bf4f,0xbdf0bda0,0xbed6bec3,0xbf2dbf26,0xbf5fbf5a,0xbe47be20,0xbef9bee8,0xbf3bbf34,0xbf68bf64,0xbe8abe6e,0xbf0ebf05,0xbf48bf42,0xbf70bf6c,
0xbd148000,0xbea3be92,0xbf13bf0c,0xbf49bf43,0xbdddbd94,0xbec6beb5,0xbf22bf1b,0xbf54bf4e,0xbe38be13,0xbee7bed7,0xbf30bf29,0xbf5dbf59,0xbe80be5c,0xbf04bef8,0xbf3dbf36,0xbf66bf62,
0xbd078000,0xbe96be86,0xbf08bf01,0xbf3cbf36,0xbdcabd87,0xbeb6bea6,0xbf16bf0f,0xbf47bf42,0xbe28be07,0xbed5bec5,0xbf23bf1d,0xbf51bf4c,0xbe6abe49,0xbef3bee4,0xbf30bf2a,0xbf5abf56,
0xbcf58000,0xbe88be73,0xbef9beec,0xbf2ebf28,0xbdb8bd75,0xbea5be97,0xbf0abf03,0xbf39bf34,0xbe19bdf4,0xbec2beb4,0xbf16bf10,0xbf43bf3e,0xbe55be37,0xbedebed0,0xbf23bf1d,0xbf4dbf48,
0xbcdc8000,0xbe75be5a,0xbee2bed5,0xbf1fbf1a,0xbda5bd5c,0xbe95be88,0xbefabeee,0xbf2abf25,0xbe09bddb,0xbeafbea2,0xbf09bf03,0xbf34bf2f,0xbe3fbe24,0xbec9bebc,0xbf14bf0f,0xbf3dbf39,
0xbcc38000,0xbe59be42,0xbec9bebe,0xbf0fbf0a,0xbd92bd43,0xbe84be71,0xbee0bed4,0xbf19bf14,0xbdf3bdc2,0xbe9cbe90,0xbef5beea,0xbf23bf1e,0xbe2abe12,0xbeb3bea7,0xbf05bf00,0xbf2cbf28,
0xbcaa8000,0xbe3ebe29,0xbeb1bea7,0xbefdbef4,0xbd7ebd2a,0xbe67be53,0xbec4beba,0xbf08bf03,0xbdd4bda9,0xbe88be7c,0xbed8bece,0xbf11bf0c,0xbe14bdfe,0xbe9cbe92,0xbeebbee1,0xbf19bf15,
0xbc918000,0xbe22be10,0xbe97be8f,0xbedbbed2,0xbd59bd10,0xbe45be34,0xbea8bea0,0xbeebbee3,0xbdb4bd90,0xbe69be57,0xbeb9beb1,0xbefbbef3,0xbdfcbdd8,0xbe86be7a,0xbecabec2,0xbf05bf01,
0xbc6f8000,0xbe06bdee,0xbe7bbe6d,0xbeb6beaf,0xbd33bcef,0xbe23be15,0xbe8cbe85,0xbec4bebd,0xbd95bd6f,0xbe41be32,0xbe9abe93,0xbed2becb,0xbdd1bdb3,0xbe5ebe4f,0xbea8bea1,0xbee0bed9,
0xbc3c8000,0xbdd4bdbc,0xbe47be3b,0xbe91be8c,0xbd0dbcbc,0xbe01bdeb,0xbe5ebe53,0xbe9cbe97,0xbd6bbd3c,0xbe19be0d,0xbe75be6a,0xbea8bea2,0xbda5bd8d,0xbe30be24,0xbe86be80,0xbeb3bead,
0xbc0a8000,0xbd9bbd8a,0xbe12be0a,0xbe56be4e,0xbccfbc8a,0xbdbebdad,0xbe23be1b,0xbe67be5f,0xbd2dbd0a,0xbde0bdcf,0xbe34be2c,0xbe78be70,0xbd72bd4f,0xbe01bdf1,0xbe45be3d,0xbe84be80,
0xbbb08000,0xbd46bd30,0xbdbbbdb0,0xbe09be04,0xbc84bc30,0xbd72bd5c,0xbdd1bdc6,0xbe14be0e,0xbcdcbcb0,0xbd8fbd84,0xbde6bddb,0xbe1fbe19,0xbd1abd04,0xbda5bd9a,0xbdfcbdf1,0xbe2abe24,
0xbb178000,0xbcaabc97,0xbd20bd17,0xbd6bbd62,0xbbe2bb97,0xbccfbcbc,0xbd33bd2a,0xbd7ebd75,0xbc3cbc17,0xbcf5bce2,0xbd46bd3c,0xbd89bd84,0xbc84bc62,0xbd0dbd04,0xbd59bd4f,0xbd92bd8d,
0x3a490000,0x3be23bc9,0x3c563c49,0x3c9d3c97,0x3b173ac9,0x3c0a3bfb,0x3c6f3c62,0x3caa3ca3,0x3b7b3b49,0x3c233c17,0x3c843c7b,0x3cb63cb0,0x3bb03b97,0x3c3c3c30,0x3c913c8a,0x3cc33cbc,
0x3b7b0000,0x3d0d3cfb,0x3d853d7b,0x3dc43dbc,0x3c3c3bfb,0x3d2d3d1d,0x3d953d8d,0x3dd43dcc,0x3c9d3c7b,0x3d4c3d3c,0x3da53d9d,0x3de33ddb,0x3cdc3cbc,0x3d6b3d5c,0x3db43dad,0x3df33deb,
0x3be20000,0x3d7e3d62,0x3df03de2,0x3e303e29,0x3caa3c62,0x3d9b3d8d,0x3e063dfe,0x3e3e3e37,0x3d0d3ce2,0x3db83da9,0x3e143e0d,0x3e4c3e45,0x3d463d2a,0x3dd43dc6,0x3e223e1b,0x3e593e53,
0x3c230000,0x3db83da3,0x3e2d3e23,0x3e7d3e73,0x3cf53ca3,0x3de03dcc,0x3e413e37,0x3e883e83,0x3d4c3d23,0x3e043df4,0x3e553e4b,0x3e923e8d,0x3d8f3d75,0x3e193e0e,0x3e693e5f,0x3e9c3e97,
0x3c560000,0x3df03dd5,0x3e613e54,0x3ea43e9e,0x3d203cd6,0x3e123e05,0x3e7b3e6e,0x3eb13eaa,0x3d853d56,0x3e2d3e20,0x3e8a3e84,0x3ebd3eb7,0x3dbb3da0,0x3e473e3a,0x3e973e91,0x3ec93ec3,
0x3c840000,0x3e143e04,0x3e8a3e82,0x3ec93ec1,0x3d463d04,0x3e343e24,0x3e9a3e92,0x3ed83ed0,0x3da53d84,0x3e553e45,0x3eaa3ea2,0x3ee73edf,0x3de63dc6,0x3e753e65,0x3eb93eb2,0x3ef53eee,
0x3c9d0000,0x3e303e1c,0x3ea43e9b,0x3eec3ee3,0x3d6b3d1d,0x3e563e43,0x3eb63ead,0x3efd3ef5,0x3dc43d9d,0x3e7d3e6a,0x3ec93ec0,0x3f073f03,0x3e093deb,0x3e913e88,0x3edb3ed2,0x3f0f3f0b,
0x3cb60000,0x3e4c3e35,0x3ebd3eb2,0x3f073f02,0x3d893d36,0x3e783e62,0x3ed23ec8,0x3f113f0c,0x3de33db6,0x3e923e87,0x3ee73edc,0x3f1a3f15,0x3e1f3e08,0x3ea83e9d,0x3efb3ef1,0x3f233f1e,
0x3ccf0000,0x3e673e4e,0x3ed63eca,0x3f173f12,0x3d9b3d4f,0x3e8d3e80,0x3eed3ee1,0x3f223f1d,0x3e013dcf,0x3ea53e99,0x3f023ef8,0x3f2b3f27,0x3e343e1b,0x3ebe3eb2,0x3f0d3f07,0x3f353f30,
0x3ce80000,0x3e813e66,0x3eee3ee1,0x3f273f21,0x3dae3d68,0x3e9d3e8f,0x3f033efa,0x3f323f2c,0x3e113de8,0x3eb93eab,0x3f103f0a,0x3f3c3f37,0x3e4a3e2e,0x3ed33ec6,0x3f1b3f16,0x3f453f41,
0x3d010000,0x3e8f3e7f,0x3f023ef7,0x3f353f2f,0x3dc13d81,0x3eae3e9e,0x3f103f09,0x3f403f3b,0x3e203e00,0x3ecc3ebd,0x3f1d3f17,0x3f4a3f45,0x3e603e40,0x3ee93eda,0x3f293f23,0x3f543f4f,
0x3d0d0000,0x3e9c3e8c,0x3f0e3f06,0x3f423f3d,0x3dd43d8d,0x3ebe3ead,0x3f1c3f15,0x3f4e3f48,0x3e303e0d,0x3ede3ece,0x3f2a3f23,0x3f583f53,0x3e753e53,0x3efd3eee,0x3f373f30,0x3f613f5c,
0x3d1a0000,0x3eaa3e98,0x3f193f11,0x3f4f3f49,0x3de63d9a,0x3ece3ebc,0x3f283f20,0x3f593f54,0x3e3f3e19,0x3ef03edf,0x3f363f2f,0x3f633f5e,0x3e853e65,0x3f093f01,0x3f433f3c,0x3f6b3f67,
0x3d260000,0x3eb73ea4,0x3f233f1b,0x3f5a3f54,0x3df93da6,0x3edd3eca,0x3f333f2b,0x3f643f5f,0x3e4f3e26,0x3f013ef0,0x3f413f3a,0x3f6d3f68,0x3e903e77,0x3f133f0a,0x3f4e3f48,0x3f743f70,
0x3d330000,0x3ec43eaf,0x3f2d3f25,0x3f633f5e,0x3e063db3,0x3eed3ed9,0x3f3d3f35,0x3f6d3f68,0x3e5e3e32,0x3f0a3f00,0x3f4b3f44,0x3f743f71,0x3e9a3e85,0x3f1c3f13,0x3f583f52,0x3f7a3f77,
0x3d400000,0x3ed13ebb,0x3f373f2e,0x3f6c3f67,0x3e0f3dbf,0x3efc3ee7,0x3f473f3f,0x3f743f70,0x3e6d3e3f,0x3f123f08,0x3f553f4e,0x3f7a3f77,0x3ea53e8e,0x3f253f1c,0x3f613f5b,0x3f7e3f7c
};
#define TS(i)
#define TZ(z, i)

struct Params {
  alignas(64) CUtensorMap x_g1, w1_a, w1_b2, w1_b1, k, v, w1_cs, kvz, h_st, h_st2, w2, h_ld, y_ld, x_ep, out_st, f_ld, y_st;
  const bf16 *x, *shift_k, *ssm_k, *ssm_D, *b1, *b2, *w2p;
  bf16* kvZ;
  const uint32_t* tab;
  uint2 *stats, *cs;
  unsigned* flags;
  unsigned zero;
  unsigned char cnt[64];
  uchar4 map[NCTA];
};

constexpr int G1_W = 28672, G1_X = 16384, G1_NST = 4, OFF_X = G1_NST * G1_W;
constexpr int G2_STAGE = G1_W, G2_B = 16384, G2_NST = 6;
constexpr int CS_STAGE = 57344;
constexpr int RING = G1_NST * (G1_W + G1_X);
constexpr int OFF_C = RING;
constexpr int OFF_SR = OFF_C;
constexpr int OFF_DFT = OFF_C, OFF_G = OFF_C + 8192;
constexpr int KV_SLOT = 35 * 256, KV_V = 19 * 256;
constexpr int OFF_KVS = OFF_C + 20480, OFF_KV = OFF_KVS + 4096;
constexpr int OFF_T0 = OFF_C + 12288, OFF_T1 = OFF_C + 34816, OFF_T2 = OFF_C + 20480, OFF_T3 = OFF_X + 57344;
constexpr int OFF_XT = OFF_C + 20480, XT_STEP = 13312, OFF_YT = OFF_C;
constexpr int OFF_EXT = 224256;
constexpr int OFF_ST1 = OFF_EXT + 3584;
constexpr int OFF_ST2 = OFF_ST1 + 2048;
constexpr int OFF_MISC = OFF_ST2 + 640;
constexpr int OFF_BAR = OFF_MISC + 32;
enum { B_FULL1 = 0  , B_KV = 4  , B_STAT = 6, B_FIRST = 7, B_EMPTY1 = 7  , B_FULL2 = 11  , B_EMPTY2 = 17  , B_G1FREE = 23, B_CX = 24  , B_RD = 29  ,
       B_EPOCH = 34, B_SKEW = 35, B_TAB = 36, B_EP = 37, B_EPY = 38, B_KVS = 39  , B_GO = 42, B_DONE = 43, B_STATFREE = 44, B_HS = 45  ,
       B_KVR = 53, B_LATE = 54, B_DFT = 55, B_HB = 56, B_H1 = 57, B_VD = 58, B_RT = 59, B_COUNT = 60 };
constexpr int OFF_DBG = OFF_BAR + B_COUNT * 8;
constexpr int SMEM_BYTES = OFF_DBG + (DBG_TIME ? 768 : 0);
static_assert(SMEM_BYTES <= 232448, "smem");
static_assert(OFF_XT + XT_STEP + 10240 <= OFF_EXT && OFF_KV + 2 * KV_SLOT <= OFF_EXT && OFF_T1 + 8192 <= OFF_EXT && OFF_T1 >= OFF_KV + KV_SLOT && OFF_T2 + 8192 <= OFF_KV + KV_SLOT, "layout");
static_assert(OFF_EXT % 1024 == 0 && OFF_XT % 1024 == 0 && XT_STEP % 1024 == 0 && OFF_T1 % 1024 == 0 && 5 * G2_STAGE + 26624 <= OFF_T3 && 3 * CS_STAGE <= RING, "layout");

#define DEV __device__ __forceinline__
#define HD __host__ __device__ constexpr
DEV uint32_t smem_u32(const void* p) { return (uint32_t)__cvta_generic_to_shared(p); }
DEV uint64_t make_desc(uint32_t addr, uint32_t lbo, uint32_t sbo, uint32_t swz) {
  uint64_t d;
  asm volatile("mov.b64 %0, {%1, %2};" : "=l"(d) : "r"(((addr & 0x3FFFF) >> 4) | ((lbo >> 4) << 16)), "r"((sbo >> 4) | (swz << 30)));
  return d;
}
DEV void wg_fence() { asm volatile("wgmma.fence.sync.aligned;" ::: "memory"); }
DEV void wg_commit() { asm volatile("wgmma.commit_group.sync.aligned;" ::: "memory"); }
template <int n> DEV void wg_wait() { asm volatile("wgmma.wait_group.sync.aligned %0;" ::"n"(n) : "memory"); }
DEV void mbar_init(uint32_t bar, int cnt) { asm volatile("mbarrier.init.shared::cta.b64 [%0], %1;" ::"r"(bar), "r"(cnt) : "memory"); }
DEV void mbar_expect(uint32_t bar, int bytes) { asm volatile("mbarrier.arrive.expect_tx.shared::cta.b64 _, [%0], %1;" ::"r"(bar), "r"(bytes) : "memory"); }
DEV void mbar_arrive(uint32_t bar) { asm volatile("mbarrier.arrive.shared::cta.b64 _, [%0];" ::"r"(bar) : "memory"); }
DEV void mbar_wait(uint32_t bar, uint32_t parity) {
  asm volatile("{\n.reg .pred p;\nW: mbarrier.try_wait.parity.shared::cta.b64 p, [%0], %1;\n@p bra X;\nbra W;\nX:\n}" ::"r"(bar), "r"(parity) : "memory");
}
DEV void mbar_wait_b(uint32_t bar, uint32_t parity) {
  asm volatile("{\n.reg .pred p;\n.reg .u32 i;\nmov.u32 i, 0;\n"
               "W: mbarrier.try_wait.parity.shared::cta.b64 p, [%0], %1;\n@p bra X;\nadd.u32 i, i, 1;\nsetp.lt.u32 p, i, 262144;\n@p bra W;\ntrap;\nX:\n}"
               ::"r"(bar), "r"(parity) : "memory");
}
DEV void trap_above(int n, int lim) { asm volatile("{\n.reg .pred p;\nsetp.gt.s32 p, %0, %1;\n@p trap;\n}" ::"r"(n), "r"(lim)); }
DEV unsigned flag_load(const unsigned* p) {
  unsigned v;
  asm volatile("ld.acquire.gpu.global.u32 %0, [%1];" : "=r"(v) : "l"(p) : "memory");
  return v;
}
template <bool BOUNDED> DEV void flag_wait(const unsigned* p, unsigned target) {
#pragma unroll 1
  for (int i = 0; !BOUNDED || i < (1 << 22); i++)
    if ((int)(flag_load(p) - target) >= 0) return;
  __trap();
}
DEV void tag_store(uint2* p, float a, float b, unsigned ep) {
  const unsigned long long v = (unsigned long long)__float_as_uint(a) | ((unsigned long long)((__float_as_uint(b) & ~255u) | (ep & 255u)) << 32);
  asm volatile("st.relaxed.gpu.global.u64 [%0], %1;" ::"l"(p), "l"(v) : "memory");
}
DEV uint2 tag_load(const uint2* p) { uint2 v; asm volatile("{\n.reg .b64 t;\nld.relaxed.gpu.global.b64 t, [%2];\nmov.b64 {%0,%1}, t;\n}" : "=r"(v.x), "=r"(v.y) : "l"(p) : "memory"); return v; }
template <int N> DEV void tag_wait(const uint2* const (&p)[N], uint2 (&v)[N], unsigned ep) {
#pragma unroll 1
  for (;;) {
    unsigned bad = 0;
#pragma unroll
    for (int j = 0; j < N; j++) bad |= v[j].y ^ ep;
    if (!__any_sync(0xffffffffu, (bad & 255u) != 0)) break;
#pragma unroll
    for (int j = 0; j < N; j++) v[j] = tag_load(p[j]);
  }
#pragma unroll
  for (int j = 0; j < N; j++) v[j].y &= ~255u;
}
#define REL 4
DEV void pub_fence(int bit) { if (REL & bit) asm volatile("fence.acq_rel.gpu;" ::: "memory"); }
DEV void flag_add_rlx(unsigned* p, unsigned n) { asm volatile("red.relaxed.gpu.global.add.u32 [%0], %1;" ::"l"(p), "r"(n) : "memory"); }
DEV void fence_async_smem() { asm volatile("fence.proxy.async.shared::cta;" ::: "memory"); }
DEV void fence_async_global() { asm volatile("fence.proxy.async.global;" ::: "memory"); }
DEV void bar_sync(int id) { asm volatile("bar.sync %0, 128;" ::"r"(id) : "memory"); }
DEV bool elect() {
  uint32_t p;
  asm volatile("{\n.reg .pred p;\nelect.sync _|p, 0xffffffff;\nselp.u32 %0, 1, 0, p;\n}" : "=r"(p));
  return p;
}
DEV void warp_arrive(uint32_t bar) { __syncwarp(); if (elect()) mbar_arrive(bar); }
DEV void bulk_g2s(uint32_t dst, const void* src, int bytes, uint32_t bar) {
  asm volatile("cp.async.bulk.shared::cluster.global.mbarrier::complete_tx::bytes [%0], [%1], %2, [%3];" ::"r"(dst), "l"(src), "r"(bytes), "r"(bar) : "memory");
}
DEV void bulk_s2g(void* dst, uint32_t src, int bytes) { asm volatile("cp.async.bulk.global.shared::cta.bulk_group [%0], [%1], %2;" ::"l"(dst), "r"(src), "r"(bytes) : "memory"); }
DEV void bulk_prefetch(const void* src, int bytes) { asm volatile("cp.async.bulk.prefetch.L2.global [%0], %1;" ::"l"(src), "r"(bytes) : "memory"); }
DEV void tma2d(uint32_t dst, const CUtensorMap* m, int c0, int c1, uint32_t bar) {
  asm volatile("cp.async.bulk.tensor.2d.shared::cluster.global.mbarrier::complete_tx::bytes [%0], [%1, {%3, %4}], [%2];" ::"r"(dst), "l"(m), "r"(bar), "r"(c0), "r"(c1) : "memory");
}
DEV void tma3d(uint32_t dst, const CUtensorMap* m, int c0, int c1, int c2, uint32_t bar) {
  asm volatile("cp.async.bulk.tensor.3d.shared::cluster.global.mbarrier::complete_tx::bytes [%0], [%1, {%3, %4, %5}], [%2];" ::"r"(dst), "l"(m), "r"(bar), "r"(c0), "r"(c1), "r"(c2) : "memory");
}
DEV void tma2d_st(const CUtensorMap* m, int c0, int c1, uint32_t src) {
  asm volatile("cp.async.bulk.tensor.2d.global.shared::cta.bulk_group [%0, {%2, %3}], [%1];" ::"l"(m), "r"(src), "r"(c0), "r"(c1) : "memory");
}
DEV void bulk_commit() { asm volatile("cp.async.bulk.commit_group;" ::: "memory"); }
DEV void bulk_wait_read() { asm volatile("cp.async.bulk.wait_group.read 0;" ::: "memory"); }
DEV void bulk_wait_all() { asm volatile("cp.async.bulk.wait_group 0;" ::: "memory"); }
DEV void prefetch_map(const CUtensorMap* m) { asm volatile("prefetch.tensormap [%0];" ::"l"(m) : "memory"); }
DEV uint32_t lds32(uint32_t a) { uint32_t v; asm volatile("ld.shared.b32 %0, [%1];" : "=r"(v) : "r"(a) : "memory"); return v; }
DEV uint2 lds64(uint32_t a) { uint2 v; asm volatile("ld.shared.v2.b32 {%0,%1}, [%2];" : "=r"(v.x), "=r"(v.y) : "r"(a) : "memory"); return v; }
DEV uint4 lds128(uint32_t a) { uint4 v; asm volatile("ld.shared.v4.b32 {%0,%1,%2,%3}, [%4];" : "=r"(v.x), "=r"(v.y), "=r"(v.z), "=r"(v.w) : "r"(a) : "memory"); return v; }
DEV void sts32(uint32_t a, uint32_t v) { asm volatile("st.shared.b32 [%0], %1;" ::"r"(a), "r"(v) : "memory"); }
DEV void sts128(uint32_t a, uint4 v) { asm volatile("st.shared.v4.b32 [%0], {%1,%2,%3,%4};" ::"r"(a), "r"(v.x), "r"(v.y), "r"(v.z), "r"(v.w) : "memory"); }
DEV void stsm4(uint32_t a, uint32_t r0, uint32_t r1, uint32_t r2, uint32_t r3) { asm volatile("stmatrix.sync.aligned.m8n8.x4.shared.b16 [%0], {%1,%2,%3,%4};" ::"r"(a), "r"(r0), "r"(r1), "r"(r2), "r"(r3) : "memory"); }
DEV void stsm4t(uint32_t a, uint32_t r0, uint32_t r1, uint32_t r2, uint32_t r3) { asm volatile("stmatrix.sync.aligned.m8n8.x4.trans.shared.b16 [%0], {%1,%2,%3,%4};" ::"r"(a), "r"(r0), "r"(r1), "r"(r2), "r"(r3) : "memory"); }
DEV void ldsm4(uint32_t a, uint32_t (&r)[4]) { asm volatile("ldmatrix.sync.aligned.m8n8.x4.shared.b16 {%0,%1,%2,%3}, [%4];" : "=r"(r[0]), "=r"(r[1]), "=r"(r[2]), "=r"(r[3]) : "r"(a) : "memory"); }
DEV void ldsm4t(uint32_t a, uint32_t (&r)[4]) { asm volatile("ldmatrix.sync.aligned.m8n8.x4.trans.shared.b16 {%0,%1,%2,%3}, [%4];" : "=r"(r[0]), "=r"(r[1]), "=r"(r[2]), "=r"(r[3]) : "r"(a) : "memory"); }
DEV uint32_t pack2(float lo, float hi) { uint32_t r; asm("cvt.rn.bf16x2.f32 %0, %1, %2;" : "=r"(r) : "f"(hi), "f"(lo)); return r; }
DEV uint32_t pack2v(float lo, float hi) { uint32_t r; asm volatile("cvt.rn.bf16x2.f32 %0, %1, %2;" : "=r"(r) : "f"(hi), "f"(lo)); return r; }
DEV float faddv(float a, float b) { float r; asm volatile("add.rn.f32 %0, %1, %2;" : "=f"(r) : "f"(a), "f"(b)); return r; }
DEV float blo(uint32_t u) { return __uint_as_float(u << 16); }
DEV float bhi(uint32_t u) { return __uint_as_float(u & 0xffff0000u); }
DEV float rcp_fast(float x) { float y; asm("rcp.approx.ftz.f32 %0, %1;" : "=f"(y) : "f"(x)); return y; }
DEV float tanh_fast(float x) { float y; asm("tanh.approx.f32 %0, %1;" : "=f"(y) : "f"(x)); return y; }
DEV uint32_t htanh2(uint32_t a) { uint32_t r; asm("tanh.approx.bf16x2 %0, %1;" : "=r"(r) : "r"(a)); return r; }
DEV uint32_t hadd2(uint32_t a, uint32_t b) { uint32_t r; asm("add.rn.bf16x2 %0, %1, %2;" : "=r"(r) : "r"(a), "r"(b)); return r; }
DEV uint32_t hmul2(uint32_t a, uint32_t b) { uint32_t r; asm("mul.rn.bf16x2 %0, %1, %2;" : "=r"(r) : "r"(a), "r"(b)); return r; }
DEV uint32_t hfma2(uint32_t a, uint32_t b, uint32_t c) { uint32_t r; asm("fma.rn.bf16x2 %0, %1, %2, %3;" : "=r"(r) : "r"(a), "r"(b), "r"(c)); return r; }
DEV uint32_t hfms2(uint32_t a, uint32_t b, uint32_t c) { uint32_t r; asm("{\n.reg .b32 t;\nmul.bf16x2 t, %1, %2;\nsub.bf16x2 %0, %3, t;\n}" : "=r"(r) : "r"(a), "r"(b), "r"(c)); return r; }
DEV uint4 ldg128(const void* p) { uint4 v; asm volatile("ld.global.nc.v4.b32 {%0,%1,%2,%3}, [%4];" : "=r"(v.x), "=r"(v.y), "=r"(v.z), "=r"(v.w) : "l"(p)); return v; }
DEV uint32_t ldg32(const void* p) { uint32_t v; asm volatile("ld.global.nc.b32 %0, [%1];" : "=r"(v) : "l"(p)); return v; }
DEV float ldg_bf16(const bf16* p) { unsigned short v; asm volatile("ld.global.nc.u16 %0, [%1];" : "=h"(v) : "l"(p)); return __uint_as_float((uint32_t)v << 16); }
DEV float bf_round(float v) { return __bfloat162float(__float2bfloat16(v)); }
DEV uint32_t gelu2(float a, float b, float c1, float c2) {
  const uint32_t p = pack2(a, b);
  return hfma2(p, htanh2(hmul2(p, hfma2(hmul2(p, p), __float_as_uint(c2), __float_as_uint(c1)))), p);
}

DEV void wgmma_ss_128_01(float* d, uint64_t da, uint64_t db) {
  asm volatile("{\n.reg .pred p;\nsetp.ne.b32 p, 1, 0;\nwgmma.mma_async.sync.aligned.m64n128k16.f32.bf16.bf16 {%0, %1, %2, %3, %4, %5, %6, %7, %8, %9, %10, %11, %12, %13, %14, %15, %16, %17, %18, %19, %20, %21, %22, %23, %24, %25, %26, %27, %28, %29, %30, %31, %32, %33, %34, %35, %36, %37, %38, %39, %40, %41, %42, %43, %44, %45, %46, %47, %48, %49, %50, %51, %52, %53, %54, %55, %56, %57, %58, %59, %60, %61, %62, %63}, %64, %65, p, 1, 1, 0, 1;\n}\n"
    : "+f"(d[0]), "+f"(d[1]), "+f"(d[2]), "+f"(d[3]), "+f"(d[4]), "+f"(d[5]), "+f"(d[6]), "+f"(d[7]), "+f"(d[8]), "+f"(d[9]), "+f"(d[10]), "+f"(d[11]), "+f"(d[12]), "+f"(d[13]), "+f"(d[14]), "+f"(d[15]), "+f"(d[16]), "+f"(d[17]), "+f"(d[18]), "+f"(d[19]), "+f"(d[20]), "+f"(d[21]), "+f"(d[22]), "+f"(d[23]), "+f"(d[24]), "+f"(d[25]), "+f"(d[26]), "+f"(d[27]), "+f"(d[28]), "+f"(d[29]), "+f"(d[30]), "+f"(d[31]), "+f"(d[32]), "+f"(d[33]), "+f"(d[34]), "+f"(d[35]), "+f"(d[36]), "+f"(d[37]), "+f"(d[38]), "+f"(d[39]), "+f"(d[40]), "+f"(d[41]), "+f"(d[42]), "+f"(d[43]), "+f"(d[44]), "+f"(d[45]), "+f"(d[46]), "+f"(d[47]), "+f"(d[48]), "+f"(d[49]), "+f"(d[50]), "+f"(d[51]), "+f"(d[52]), "+f"(d[53]), "+f"(d[54]), "+f"(d[55]), "+f"(d[56]), "+f"(d[57]), "+f"(d[58]), "+f"(d[59]), "+f"(d[60]), "+f"(d[61]), "+f"(d[62]), "+f"(d[63])
    : "l"(da), "l"(db));
}
DEV void wgmma_ss_96_01(float* d, uint64_t da, uint64_t db) {
  asm volatile("{\n.reg .pred p;\nsetp.ne.b32 p, 1, 0;\nwgmma.mma_async.sync.aligned.m64n96k16.f32.bf16.bf16 {%0, %1, %2, %3, %4, %5, %6, %7, %8, %9, %10, %11, %12, %13, %14, %15, %16, %17, %18, %19, %20, %21, %22, %23, %24, %25, %26, %27, %28, %29, %30, %31, %32, %33, %34, %35, %36, %37, %38, %39, %40, %41, %42, %43, %44, %45, %46, %47}, %48, %49, p, 1, 1, 0, 1;\n}\n"
    : "+f"(d[0]), "+f"(d[1]), "+f"(d[2]), "+f"(d[3]), "+f"(d[4]), "+f"(d[5]), "+f"(d[6]), "+f"(d[7]), "+f"(d[8]), "+f"(d[9]), "+f"(d[10]), "+f"(d[11]), "+f"(d[12]), "+f"(d[13]), "+f"(d[14]), "+f"(d[15]), "+f"(d[16]), "+f"(d[17]), "+f"(d[18]), "+f"(d[19]), "+f"(d[20]), "+f"(d[21]), "+f"(d[22]), "+f"(d[23]), "+f"(d[24]), "+f"(d[25]), "+f"(d[26]), "+f"(d[27]), "+f"(d[28]), "+f"(d[29]), "+f"(d[30]), "+f"(d[31]), "+f"(d[32]), "+f"(d[33]), "+f"(d[34]), "+f"(d[35]), "+f"(d[36]), "+f"(d[37]), "+f"(d[38]), "+f"(d[39]), "+f"(d[40]), "+f"(d[41]), "+f"(d[42]), "+f"(d[43]), "+f"(d[44]), "+f"(d[45]), "+f"(d[46]), "+f"(d[47])
    : "l"(da), "l"(db));
}
DEV void wgmma_ss_80_10(float* d, uint64_t da, uint64_t db) {
  asm volatile("{\n.reg .pred p;\nsetp.ne.b32 p, 1, 0;\nwgmma.mma_async.sync.aligned.m64n80k16.f32.bf16.bf16 {%0, %1, %2, %3, %4, %5, %6, %7, %8, %9, %10, %11, %12, %13, %14, %15, %16, %17, %18, %19, %20, %21, %22, %23, %24, %25, %26, %27, %28, %29, %30, %31, %32, %33, %34, %35, %36, %37, %38, %39}, %40, %41, p, 1, 1, 1, 0;\n}\n"
    : "+f"(d[0]), "+f"(d[1]), "+f"(d[2]), "+f"(d[3]), "+f"(d[4]), "+f"(d[5]), "+f"(d[6]), "+f"(d[7]), "+f"(d[8]), "+f"(d[9]), "+f"(d[10]), "+f"(d[11]), "+f"(d[12]), "+f"(d[13]), "+f"(d[14]), "+f"(d[15]), "+f"(d[16]), "+f"(d[17]), "+f"(d[18]), "+f"(d[19]), "+f"(d[20]), "+f"(d[21]), "+f"(d[22]), "+f"(d[23]), "+f"(d[24]), "+f"(d[25]), "+f"(d[26]), "+f"(d[27]), "+f"(d[28]), "+f"(d[29]), "+f"(d[30]), "+f"(d[31]), "+f"(d[32]), "+f"(d[33]), "+f"(d[34]), "+f"(d[35]), "+f"(d[36]), "+f"(d[37]), "+f"(d[38]), "+f"(d[39])
    : "l"(da), "l"(db));
}
DEV void wgmma_ss_8_10(float* d, uint64_t da, uint64_t db) {
  asm volatile("{\n.reg .pred p;\nsetp.ne.b32 p, 1, 0;\nwgmma.mma_async.sync.aligned.m64n8k16.f32.bf16.bf16 {%0, %1, %2, %3}, %4, %5, p, 1, 1, 1, 0;\n}\n"
    : "+f"(d[0]), "+f"(d[1]), "+f"(d[2]), "+f"(d[3])
    : "l"(da), "l"(db));
}
DEV void wgmma_ss_32_10(float* d, uint64_t da, uint64_t db) {
  asm volatile("{\n.reg .pred p;\nsetp.ne.b32 p, 1, 0;\nwgmma.mma_async.sync.aligned.m64n32k16.f32.bf16.bf16 {%0, %1, %2, %3, %4, %5, %6, %7, %8, %9, %10, %11, %12, %13, %14, %15}, %16, %17, p, 1, 1, 1, 0;\n}\n"
    : "+f"(d[0]), "+f"(d[1]), "+f"(d[2]), "+f"(d[3]), "+f"(d[4]), "+f"(d[5]), "+f"(d[6]), "+f"(d[7]), "+f"(d[8]), "+f"(d[9]), "+f"(d[10]), "+f"(d[11]), "+f"(d[12]), "+f"(d[13]), "+f"(d[14]), "+f"(d[15])
    : "l"(da), "l"(db));
}
DEV void wgmma_ssz_32_10(float* d, uint64_t da, uint64_t db) {
  asm volatile("{\n.reg .pred p;\nsetp.ne.b32 p, 0, 0;\nwgmma.mma_async.sync.aligned.m64n32k16.f32.bf16.bf16 {%0, %1, %2, %3, %4, %5, %6, %7, %8, %9, %10, %11, %12, %13, %14, %15}, %16, %17, p, 1, 1, 1, 0;\n}\n"
    : "=f"(d[0]), "=f"(d[1]), "=f"(d[2]), "=f"(d[3]), "=f"(d[4]), "=f"(d[5]), "=f"(d[6]), "=f"(d[7]), "=f"(d[8]), "=f"(d[9]), "=f"(d[10]), "=f"(d[11]), "=f"(d[12]), "=f"(d[13]), "=f"(d[14]), "=f"(d[15])
    : "l"(da), "l"(db));
}
DEV void wgmma_rs_64_0(float* d, const uint32_t* a, uint64_t db) {
  asm volatile("{\n.reg .pred p;\nsetp.ne.b32 p, 1, 0;\nwgmma.mma_async.sync.aligned.m64n64k16.f32.bf16.bf16 {%0, %1, %2, %3, %4, %5, %6, %7, %8, %9, %10, %11, %12, %13, %14, %15, %16, %17, %18, %19, %20, %21, %22, %23, %24, %25, %26, %27, %28, %29, %30, %31}, {%32, %33, %34, %35}, %36, p, 1, 1, 0;\n}\n"
    : "+f"(d[0]), "+f"(d[1]), "+f"(d[2]), "+f"(d[3]), "+f"(d[4]), "+f"(d[5]), "+f"(d[6]), "+f"(d[7]), "+f"(d[8]), "+f"(d[9]), "+f"(d[10]), "+f"(d[11]), "+f"(d[12]), "+f"(d[13]), "+f"(d[14]), "+f"(d[15]), "+f"(d[16]), "+f"(d[17]), "+f"(d[18]), "+f"(d[19]), "+f"(d[20]), "+f"(d[21]), "+f"(d[22]), "+f"(d[23]), "+f"(d[24]), "+f"(d[25]), "+f"(d[26]), "+f"(d[27]), "+f"(d[28]), "+f"(d[29]), "+f"(d[30]), "+f"(d[31])
    : "r"(a[0]), "r"(a[1]), "r"(a[2]), "r"(a[3]), "l"(db));
}
DEV void wgmma_rsz_64_0(float* d, const uint32_t* a, uint64_t db) {
  asm volatile("{\n.reg .pred p;\nsetp.ne.b32 p, 0, 0;\nwgmma.mma_async.sync.aligned.m64n64k16.f32.bf16.bf16 {%0, %1, %2, %3, %4, %5, %6, %7, %8, %9, %10, %11, %12, %13, %14, %15, %16, %17, %18, %19, %20, %21, %22, %23, %24, %25, %26, %27, %28, %29, %30, %31}, {%32, %33, %34, %35}, %36, p, 1, 1, 0;\n}\n"
    : "=f"(d[0]), "=f"(d[1]), "=f"(d[2]), "=f"(d[3]), "=f"(d[4]), "=f"(d[5]), "=f"(d[6]), "=f"(d[7]), "=f"(d[8]), "=f"(d[9]), "=f"(d[10]), "=f"(d[11]), "=f"(d[12]), "=f"(d[13]), "=f"(d[14]), "=f"(d[15]), "=f"(d[16]), "=f"(d[17]), "=f"(d[18]), "=f"(d[19]), "=f"(d[20]), "=f"(d[21]), "=f"(d[22]), "=f"(d[23]), "=f"(d[24]), "=f"(d[25]), "=f"(d[26]), "=f"(d[27]), "=f"(d[28]), "=f"(d[29]), "=f"(d[30]), "=f"(d[31])
    : "r"(a[0]), "r"(a[1]), "r"(a[2]), "r"(a[3]), "l"(db));
}
DEV void wgmma_rs_64_1(float* d, const uint32_t* a, uint64_t db) {
  asm volatile("{\n.reg .pred p;\nsetp.ne.b32 p, 1, 0;\nwgmma.mma_async.sync.aligned.m64n64k16.f32.bf16.bf16 {%0, %1, %2, %3, %4, %5, %6, %7, %8, %9, %10, %11, %12, %13, %14, %15, %16, %17, %18, %19, %20, %21, %22, %23, %24, %25, %26, %27, %28, %29, %30, %31}, {%32, %33, %34, %35}, %36, p, 1, 1, 1;\n}\n"
    : "+f"(d[0]), "+f"(d[1]), "+f"(d[2]), "+f"(d[3]), "+f"(d[4]), "+f"(d[5]), "+f"(d[6]), "+f"(d[7]), "+f"(d[8]), "+f"(d[9]), "+f"(d[10]), "+f"(d[11]), "+f"(d[12]), "+f"(d[13]), "+f"(d[14]), "+f"(d[15]), "+f"(d[16]), "+f"(d[17]), "+f"(d[18]), "+f"(d[19]), "+f"(d[20]), "+f"(d[21]), "+f"(d[22]), "+f"(d[23]), "+f"(d[24]), "+f"(d[25]), "+f"(d[26]), "+f"(d[27]), "+f"(d[28]), "+f"(d[29]), "+f"(d[30]), "+f"(d[31])
    : "r"(a[0]), "r"(a[1]), "r"(a[2]), "r"(a[3]), "l"(db));
}
DEV void wgmma_rsz_64_1(float* d, const uint32_t* a, uint64_t db) {
  asm volatile("{\n.reg .pred p;\nsetp.ne.b32 p, 0, 0;\nwgmma.mma_async.sync.aligned.m64n64k16.f32.bf16.bf16 {%0, %1, %2, %3, %4, %5, %6, %7, %8, %9, %10, %11, %12, %13, %14, %15, %16, %17, %18, %19, %20, %21, %22, %23, %24, %25, %26, %27, %28, %29, %30, %31}, {%32, %33, %34, %35}, %36, p, 1, 1, 1;\n}\n"
    : "=f"(d[0]), "=f"(d[1]), "=f"(d[2]), "=f"(d[3]), "=f"(d[4]), "=f"(d[5]), "=f"(d[6]), "=f"(d[7]), "=f"(d[8]), "=f"(d[9]), "=f"(d[10]), "=f"(d[11]), "=f"(d[12]), "=f"(d[13]), "=f"(d[14]), "=f"(d[15]), "=f"(d[16]), "=f"(d[17]), "=f"(d[18]), "=f"(d[19]), "=f"(d[20]), "=f"(d[21]), "=f"(d[22]), "=f"(d[23]), "=f"(d[24]), "=f"(d[25]), "=f"(d[26]), "=f"(d[27]), "=f"(d[28]), "=f"(d[29]), "=f"(d[30]), "=f"(d[31])
    : "r"(a[0]), "r"(a[1]), "r"(a[2]), "r"(a[3]), "l"(db));
}
DEV void wgmma_rs_128_1(float* d, const uint32_t* a, uint64_t db) {
  asm volatile("{\n.reg .pred p;\nsetp.ne.b32 p, 1, 0;\nwgmma.mma_async.sync.aligned.m64n128k16.f32.bf16.bf16 {%0, %1, %2, %3, %4, %5, %6, %7, %8, %9, %10, %11, %12, %13, %14, %15, %16, %17, %18, %19, %20, %21, %22, %23, %24, %25, %26, %27, %28, %29, %30, %31, %32, %33, %34, %35, %36, %37, %38, %39, %40, %41, %42, %43, %44, %45, %46, %47, %48, %49, %50, %51, %52, %53, %54, %55, %56, %57, %58, %59, %60, %61, %62, %63}, {%64, %65, %66, %67}, %68, p, 1, 1, 1;\n}\n"
    : "+f"(d[0]), "+f"(d[1]), "+f"(d[2]), "+f"(d[3]), "+f"(d[4]), "+f"(d[5]), "+f"(d[6]), "+f"(d[7]), "+f"(d[8]), "+f"(d[9]), "+f"(d[10]), "+f"(d[11]), "+f"(d[12]), "+f"(d[13]), "+f"(d[14]), "+f"(d[15]), "+f"(d[16]), "+f"(d[17]), "+f"(d[18]), "+f"(d[19]), "+f"(d[20]), "+f"(d[21]), "+f"(d[22]), "+f"(d[23]), "+f"(d[24]), "+f"(d[25]), "+f"(d[26]), "+f"(d[27]), "+f"(d[28]), "+f"(d[29]), "+f"(d[30]), "+f"(d[31]), "+f"(d[32]), "+f"(d[33]), "+f"(d[34]), "+f"(d[35]), "+f"(d[36]), "+f"(d[37]), "+f"(d[38]), "+f"(d[39]), "+f"(d[40]), "+f"(d[41]), "+f"(d[42]), "+f"(d[43]), "+f"(d[44]), "+f"(d[45]), "+f"(d[46]), "+f"(d[47]), "+f"(d[48]), "+f"(d[49]), "+f"(d[50]), "+f"(d[51]), "+f"(d[52]), "+f"(d[53]), "+f"(d[54]), "+f"(d[55]), "+f"(d[56]), "+f"(d[57]), "+f"(d[58]), "+f"(d[59]), "+f"(d[60]), "+f"(d[61]), "+f"(d[62]), "+f"(d[63])
    : "r"(a[0]), "r"(a[1]), "r"(a[2]), "r"(a[3]), "l"(db));
}
DEV void wgmma_rs_96_1(float* d, const uint32_t* a, uint64_t db) {
  asm volatile("{\n.reg .pred p;\nsetp.ne.b32 p, 1, 0;\nwgmma.mma_async.sync.aligned.m64n96k16.f32.bf16.bf16 {%0, %1, %2, %3, %4, %5, %6, %7, %8, %9, %10, %11, %12, %13, %14, %15, %16, %17, %18, %19, %20, %21, %22, %23, %24, %25, %26, %27, %28, %29, %30, %31, %32, %33, %34, %35, %36, %37, %38, %39, %40, %41, %42, %43, %44, %45, %46, %47}, {%48, %49, %50, %51}, %52, p, 1, 1, 1;\n}\n"
    : "+f"(d[0]), "+f"(d[1]), "+f"(d[2]), "+f"(d[3]), "+f"(d[4]), "+f"(d[5]), "+f"(d[6]), "+f"(d[7]), "+f"(d[8]), "+f"(d[9]), "+f"(d[10]), "+f"(d[11]), "+f"(d[12]), "+f"(d[13]), "+f"(d[14]), "+f"(d[15]), "+f"(d[16]), "+f"(d[17]), "+f"(d[18]), "+f"(d[19]), "+f"(d[20]), "+f"(d[21]), "+f"(d[22]), "+f"(d[23]), "+f"(d[24]), "+f"(d[25]), "+f"(d[26]), "+f"(d[27]), "+f"(d[28]), "+f"(d[29]), "+f"(d[30]), "+f"(d[31]), "+f"(d[32]), "+f"(d[33]), "+f"(d[34]), "+f"(d[35]), "+f"(d[36]), "+f"(d[37]), "+f"(d[38]), "+f"(d[39]), "+f"(d[40]), "+f"(d[41]), "+f"(d[42]), "+f"(d[43]), "+f"(d[44]), "+f"(d[45]), "+f"(d[46]), "+f"(d[47])
    : "r"(a[0]), "r"(a[1]), "r"(a[2]), "r"(a[3]), "l"(db));
}

struct Dft { uint32_t E[8], tt[8], ts[8]; };
DEV void dft_load(Dft& k, const uint32_t* tab, int tid) {
#pragma unroll
  for (int q = 0; q < 6; q++) {
    const uint4 v = ldg128(tab + 3072 + 512 * q + 4 * tid);
    uint32_t* d = (q < 2 ? k.E : q < 4 ? k.tt : k.ts) + 4 * (q & 1);
    d[0] = v.x; d[1] = v.y; d[2] = v.z; d[3] = v.w;
  }
}
template <int SG> DEV void rotate(const float* d, const Dft& k, uint32_t* o) {
#pragma unroll
  for (int j = 0; j < 8; j++) {
    const uint32_t re = pack2(d[4 * j], d[4 * j + 1]), im = pack2(d[4 * j + 2], d[4 * j + 3]);
    uint32_t a, b;
    if (SG > 0) { a = hfms2(k.tt[j], im, re); b = hfma2(k.ts[j], a, im); a = hfms2(k.tt[j], b, a); }
    else { a = hfma2(k.tt[j], im, re); b = hfms2(k.ts[j], a, im); a = hfma2(k.tt[j], b, a); }
    o[2 * j] = a; o[2 * j + 1] = b;
  }
}
DEV void dft64(float* d, const uint32_t* a, uint64_t db) {
  wgmma_rsz_64_1(d, a, db);
#pragma unroll
  for (int kk = 1; kk < 4; kk++) wgmma_rs_64_1(d, a + 4 * kk, db + kk * (2048 >> 4));
}
DEV bool conv(const Dft& k, uint32_t sb, uint32_t t, float dv, int bar, int w, int lane, unsigned* go, uint32_t ep, uint32_t zero) {
  const uint32_t tag = lds32(t + 1024 * w + 32 * lane + 4 * (lane & 4));
  dv = __uint_as_float(__float_as_uint(dv) | (tag & zero));
  float dh[32], dx[32];
  uint32_t ah[16], ax[16];
  const uint64_t cs = make_desc(sb + OFF_DFT, 16, 1024, 1), bh = make_desc(t + 4096, 16, 1024, 1), bx = make_desc(t, 1024, 256, 3);
  wg_fence();
  wgmma_rsz_64_1(dh, k.E, bh); wgmma_rs_64_1(dh, k.E + 4, bh + (2048 >> 4)); wg_commit();
  wgmma_rsz_64_1(dx, k.E, bx); wgmma_rs_64_1(dx, k.E + 4, bx + (512 >> 4)); wg_commit();
  wg_wait<1>();
  dh[0] = fmaf(dv, blo(k.E[0]), dh[0]); dh[2] = fmaf(dv, blo(k.E[1]), dh[2]);
  rotate<1>(dh, k, ah);
  wg_fence(); dft64(dh, ah, cs); wg_commit();
  if (GO_AT == 1 && go) flag_add_rlx(go, 1);
  wg_wait<1>();
  rotate<1>(dx, k, ax);
  wg_fence(); dft64(dx, ax, cs); wg_commit();
  wg_wait<1>();
#pragma unroll
  for (int j = 0; j < 8; j++) { ah[2 * j] = pack2(dh[4 * j], dh[4 * j + 1]); ah[2 * j + 1] = pack2(dh[4 * j + 2], dh[4 * j + 3]); }
  wg_wait<0>();
#pragma unroll
  for (int j = 0; j < 4; j++) {
    const uint32_t pr = pack2(dx[4 * j], dx[4 * j + 1]), pi = pack2(dx[4 * j + 2], dx[4 * j + 3]);
    const uint32_t qr = pack2(dx[16 + 4 * j], dx[17 + 4 * j]), qi = pack2(dx[18 + 4 * j], dx[19 + 4 * j]);
    const uint32_t rr = ah[2 * j], ri = ah[2 * j + 1], sr = ah[8 + 2 * j], si = ah[9 + 2 * j];
    ax[2 * j] = hfma2(qi, si, hfms2(qr, sr, hfms2(pi, ri, hmul2(pr, rr))));
    ax[2 * j + 1] = hfms2(qi, sr, hfms2(qr, si, hfma2(pi, rr, hmul2(pr, ri))));
    ax[8 + 2 * j] = hfms2(qi, ri, hfma2(qr, rr, hfms2(pi, si, hmul2(pr, sr))));
    ax[9 + 2 * j] = hfma2(qi, rr, hfma2(qr, ri, hfma2(pi, sr, hmul2(pr, si))));
  }
  wg_fence();
  wgmma_rsz_64_0(dx, ax, cs);
#pragma unroll
  for (int kk = 1; kk < 4; kk++) wgmma_rs_64_0(dx, ax + 4 * kk, cs + 2 * kk);
  wg_commit();
  if (GO_AT == 2 && go) flag_add_rlx(go, 1);
  wg_wait<0>();
  rotate<-1>(dx, k, ah);
  const int m = lane >> 3, i = lane & 7;
  const uint32_t za = t + (16 * w + 8 * (m & 1) + i) * 128;
#pragma unroll
  for (int q = 0; q < 4; q++) stsm4(za + (((2 * q + (m >> 1)) ^ i) << 4), ah[4 * q], ah[4 * q + 1], ah[4 * q + 2], ah[4 * q + 3]);
  fence_async_smem();
  uint32_t ok;
  asm volatile("{\n.reg .pred p, q;\nsetp.eq.u32 p, %1, 0;\nbarrier.red.and.aligned.pred q, %2, 128, p;\nselp.u32 %0, 1, 0, q;\n}" : "=r"(ok) : "r"((tag ^ ep) & 1), "r"(bar) : "memory");
  const uint64_t da = make_desc(t, 16, 1024, 1), db = make_desc(sb + OFF_G, 16, 1024, 1);
  wg_fence();
  wgmma_ssz_32_10(dh, da, db);
#pragma unroll
  for (int kk = 1; kk < 4; kk++) wgmma_ss_32_10(dh, da + kk * (2048 >> 4), db + 2 * kk);
  wg_commit();
  if (GO_AT == 3 && go) flag_add_rlx(go, 1);
  wg_wait<0>();
  const uint32_t ya = t + (8 * (m >> 1) + i) * 128 + (((2 * w + (m & 1)) ^ i) << 4);
#pragma unroll
  for (int q = 0; q < 2; q++)
    stsm4t(ya + q * 2048, pack2(dh[8 * q], dh[8 * q + 1]), pack2(dh[8 * q + 2], dh[8 * q + 3]), pack2(dh[8 * q + 4], dh[8 * q + 5]), pack2(dh[8 * q + 6], dh[8 * q + 7]));
  fence_async_smem();
  return __all_sync(0xffffffffu, ok);
}

DEV void g1_issue(const Params& P, uint32_t sb, int s, uint32_t fb, int kb, int rb, int fs) {
  const uint32_t st = sb + s * G1_W;
  mbar_expect(fb, G1_W + G1_X);
  tma2d(sb + OFF_X + s * G1_X, &P.x_g1, 64 * kb, 128 * rb, fb);
  tma3d(st, &P.w1_a, 0, 64 * kb, 3 * fs, fb);
  tma3d(st + 16384, &P.w1_b2, 0, 64 * kb, 6 * fs + 4, fb);
  tma3d(st + 24576, &P.w1_b1, 0, 64 * kb, 48 + fs, fb);
}
DEV void kv_issue(const Params& P, uint32_t dst, uint32_t bar, int r, int g1) {
  mbar_expect(bar, KV_SLOT);
  tma2d(dst, &P.k, 128 * r, 16 * g1 - 3, bar);
  tma2d(dst + 19 * 256, &P.v, 128 * r, 16 * g1, bar);
}
DEV void h_flag(const Params& P, int rb, int o) {
  const int j0 = (128 * rb) / 80;
  flag_add_rlx(P.flags + FL_H + 32 * (o + j0), 1); flag_add_rlx(P.flags + FL_H + 32 * (o + j0 + 1), 1);
  if (80 * (j0 + 2) < 128 * rb + 128) flag_add_rlx(P.flags + FL_H + 32 * (o + j0 + 2), 1);
}
DEV void h_wait(const Params& P, int tj, int o, unsigned ep) {
  flag_wait<false>(P.flags + FL_H + 32 * (o + tj), ep * (((80 * tj) >> 7) == (min(80 * tj + 79, S_ - 1) >> 7) ? 8 : 16));
  fence_async_global();
}
DEV uint32_t conv_tile(uint32_t sb, int c) { return sb + (c == 1 ? OFF_T1 : c == 2 ? OFF_T2 : c == 3 ? OFF_T3 : OFF_T0); }
DEV void conv_issue_f(const Params& P, uint32_t t, int ch, uint32_t bar) { mbar_expect(bar, 4096); tma2d(t + 4096, &P.f_ld, 0, 32 * ch, bar); }
DEV void conv_issue_x(const Params& P, uint32_t t, int ch, uint32_t bar) {
  mbar_expect(bar, 4096);
  tma3d(t, &P.kvz, 16 * ((ch & ~63) | ((ch & 3) << 4) | ((ch & 63) >> 2)), 0, 0, bar);
}
HD int h_slot(int j) { return SPLIT9 && j ? 3 - j : j; }
DEV int g2_block(int i) { return i < 24 ? 3 * (i & 7) + (i >> 3) : i; }
DEV int ext_col(int n, int fs) { return min(n < 192 ? 192 * fs + n : 1344 + 32 * fs + n, F_ - 2); }
DEV uint32_t ext_off(int n, int k) {
  const int m = n - 128;
  return n < 128 ? (n >> 6) * 1024 + k * 128 + ((((n & 63) >> 3) ^ k) << 4) + (n & 7) * 2
                 : 2048 + (m >> 5) * 512 + k * 64 + ((((m & 31) >> 3) ^ (k >> 1)) << 4) + (m & 7) * 2;
}
DEV uint32_t kv_elem(uint32_t k0, uint32_t k1, uint32_t k2, uint32_t k3, const uint32_t (&w)[4], uint32_t v) {
  return hmul2(hfma2(k3, w[0], hfma2(k2, w[1], hfma2(k1, w[2], hmul2(k0, w[3])))), v);
}
DEV void kv_store(uint32_t z, const uint32_t (&p)[8]) {
  sts128(z, make_uint4(__byte_perm(p[0], p[1], 0x5410), __byte_perm(p[2], p[3], 0x5410), __byte_perm(p[4], p[5], 0x5410), __byte_perm(p[6], p[7], 0x5410)));
  sts128(z + 512, make_uint4(__byte_perm(p[0], p[1], 0x7632), __byte_perm(p[2], p[3], 0x7632), __byte_perm(p[4], p[5], 0x7632), __byte_perm(p[6], p[7], 0x7632)));
}
DEV void kv_out(const Params& P, uint32_t src, int r, int g1) { bulk_s2g(reinterpret_cast<uint8_t*>(P.kvZ) + g1 * 20480 + r * 4096, src, 4096); }
DEV void tap_split(uint4 q, uint32_t (&w)[4]) {
  w[0] = __byte_perm(q.x, q.z, 0x5410); w[1] = __byte_perm(q.x, q.z, 0x7632); w[2] = __byte_perm(q.y, q.w, 0x5410); w[3] = __byte_perm(q.y, q.w, 0x7632);
}

}

__global__ void __launch_bounds__(512, 1) h3_fused_kernel(const __grid_constant__ Params P) {
  extern __shared__ __align__(1024) uint8_t smem_raw[];
  constexpr uint32_t sb = 1024;
#define BAR(i) (sb + OFF_BAR + 8 * (i))
  const int warp = __shfl_sync(0xffffffffu, threadIdx.x >> 5, 0);
  const int wg = warp >> 2;
  const int tid = threadIdx.x & 127, lane = threadIdx.x & 31;
  uint32_t smid, nsmid;
  asm volatile("mov.u32 %0, %%smid;" : "=r"(smid));
  asm volatile("mov.u32 %0, %%nsmid;" : "=r"(nsmid));
  const uint32_t cta = nsmid == NCTA ? smid : blockIdx.x;
  const uchar4 mp = P.map[cta];
  const int g1 = mp.x, g2 = mp.y;
  const bool has1 = g1 < 128, has2 = g2 != 255;
  const int fs = g1 & 7, rb = g1 >> 3;
  const int tj = g2 >> 3, dt = g2 & 7;

  if (warp != 12) {
    if (elect()) {
      if (smem_u32(smem_raw) != sb) __trap();
#pragma unroll 1
      for (int b = B_FIRST + warp - (warp > 12); b < B_COUNT; b += 15) mbar_init(BAR(b), P.cnt[b]);
      fence_async_smem();
    }
    __syncwarp();
    asm volatile("bar.arrive 7, 512;" ::: "memory");
    asm volatile("bar.sync 0, 512;" ::: "memory");
  }

  if (wg < 3) {
    const int w4 = warp & 3, g = lane >> 2, c = lane & 3;
    asm volatile("setmaxnreg.inc.sync.aligned.u32 %0;" ::"n"(R_G));
    Dft dft;
    if (wg < 2) {
      if (has1) {
        float acc[112];
        const uint64_t da0 = make_desc(sb + OFF_X + wg * 8192, 16, 1024, 1), db0 = make_desc(sb, 8192, 1024, 1), dc0 = make_desc(sb + 16384, 4096, 512, 2);
        const bool lead = tid == 0;
#pragma unroll
        for (int i = 0; i < 112; i++) acc[i] = 0.f;
        auto block = [&](int kb) {
          const int s = kb & 3;
          const uint64_t o = s * (G1_W >> 4), da = da0 + s * (G1_X >> 4), db = db0 + o, dc = dc0 + o;
          mbar_wait(BAR(B_FULL1 + s), (kb >> 2) & 1);
          TZ(tid, 64 + 10 * wg + kb);
          wg_fence();
#pragma unroll
          for (int kk = 0; kk < 4; kk++) {
            wgmma_ss_128_01(acc, da + 2 * kk, db + kk * (2048 >> 4));
            wgmma_ss_96_01(acc + 64, da + 2 * kk, dc + kk * (1024 >> 4));
          }
          wg_commit();
        };
#pragma unroll 1
        for (int kb = 0; kb < 10 - SPLIT9; kb++) {
          block(kb);
          wg_wait<1>();
          if (lead && kb && kb < 7) mbar_arrive(BAR(B_EMPTY1 + ((kb - 1) & 3)));
        }
        mbar_wait(BAR(B_TAB), 0);
        TZ(tid, 8 + wg);
        const uint32_t sa = sb + OFF_ST1 + 16 * (64 * wg + 16 * w4 + g);
        const float r0 = __uint_as_float(lds32(sa + 12)), r1 = __uint_as_float(lds32(sa + 128 + 12));
        {
          uint32_t ax[4];
          ax[0] = lds32(sa + 4 * c); ax[1] = lds32(sa + 128 + 4 * c);
          if (c == 3) { ax[0] = 0; ax[1] = 0; }
          asm volatile("mov.b32 %0, 0;" : "=r"(ax[2])); asm volatile("mov.b32 %0, 0;" : "=r"(ax[3]));
          if (SPLIT9) {
            const uint64_t da = da0 + (G1_X >> 4), db = db0 + (G1_W >> 4), dc = dc0 + (G1_W >> 4);
            wg_fence();
            wgmma_rs_128_1(acc, ax, make_desc(sb + OFF_EXT, 1024, 0, 1));
            wgmma_rs_96_1(acc + 64, ax, make_desc(sb + OFF_EXT + 2048, 512, 0, 2));
            mbar_wait(BAR(B_FULL1 + 1), 0);
            TZ(tid, 64 + 10 * wg + 9);
#pragma unroll
            for (int kk = 0; kk < 4; kk++) wgmma_ss_128_01(acc, da + 2 * kk, db + kk * (2048 >> 4));
            wg_commit();
#pragma unroll
            for (int kk = 0; kk < 4; kk++) wgmma_ss_96_01(acc + 64, da + 2 * kk, dc + kk * (1024 >> 4));
            wg_commit();
          } else {
          wg_fence();
          wgmma_rs_128_1(acc, ax, make_desc(sb + OFF_EXT, 1024, 0, 1));
          wgmma_rs_96_1(acc + 64, ax, make_desc(sb + OFF_EXT + 2048, 512, 0, 2));
          wg_commit();
          }
        }
        constexpr float K1 = 0.7978845608028654f, K2 = 0.7978845608028654f * 0.044715f;
        float c10 = K1 * r0, c11 = K1 * r1, c20 = K2 * r0 * r0 * r0, c21 = K2 * r1 * r1 * r1;
        c10 = __uint_as_float(pack2(c10, c10)); c11 = __uint_as_float(pack2(c11, c11)); c20 = __uint_as_float(pack2(c20, c20)); c21 = __uint_as_float(pack2(c21, c21));
        const int hr = 16 * w4 + ((lane >> 3) & 1) * 8 + (lane & 7);
        const uint32_t hs = sb + OFF_X + wg * 8192 + hr * 128, hx = (lane >> 4) ^ (lane & 7);
        const uint32_t hs2 = sb + OFF_X + 3 * G1_X + wg * 4096 + hr * 64, hx2 = (lane >> 4) ^ ((lane >> 1) & 3);
        if (SPLIT9) wg_wait<1>(); else wg_wait<0>();
        TZ(tid, 2 + wg);
        if (!SPLIT9 && tid < 5) mbar_arrive(BAR(tid < 4 ? B_EMPTY2 + tid : B_G1FREE));
        uint32_t zn = 0;
        const uint32_t par = lds32(sb + OFF_MISC) & 1;
#pragma unroll
        for (int i = 0; i < 28; i += 2) {
          if (i == 24) { if (fs >= 6) break; if (wg) mbar_wait(BAR(B_G1FREE), 0); }
          if (i && i % GELU_BF16 == 0) {
            const uint32_t z = LOOKAHEAD ? zn : lds32(sb + OFF_MISC + 24);
            c20 = __uint_as_float(__float_as_uint(c20) + z); c21 = __uint_as_float(__float_as_uint(c21) + z);
          }
          if (LOOKAHEAD && (i + LOOKAHEAD) % GELU_BF16 == 0) zn = lds32(sb + OFF_MISC + 24);
          if (SPLIT9 && i == 16) { wg_wait<0>(); if (tid < 5) mbar_arrive(BAR(tid < 4 ? B_EMPTY2 + tid : B_G1FREE)); }
          if (i == DFT_AT) dft_load(dft, P.tab, tid);
          const float* a = &acc[4 * i];
          uint32_t p0 = gelu2(a[0], a[1], c10, c20), p1 = gelu2(a[2], a[3], c11, c21);
          if (!(i & 7)) { if (c == ((2 * w4) & 3)) p0 = (p0 & ~1u) | par; if (c == ((2 * w4 + 1) & 3)) p1 = (p1 & ~1u) | par; }
          const uint32_t p2 = gelu2(a[4], a[5], c10, c20), p3 = gelu2(a[6], a[7], c11, c21);
          if (i > HS_LAG && !((i - HS_LAG) & 7)) { fence_async_smem(); warp_arrive(BAR(B_HS + 4 * wg + (i >> 3) - 1)); }
          if (i < 24) stsm4(hs + h_slot(i >> 3) * G1_X + ((hx ^ (i & 7)) << 4), p0, p1, p2, p3);
          else stsm4(hs2 + ((hx2 ^ (i & 3)) << 4), p0, p1, p2, p3);
          if ((i == 22 && fs >= 6) || i == 26) { fence_async_smem(); warp_arrive(BAR(B_HS + 4 * wg + (i >> 3))); }
        }
        TZ(tid, 4 + wg);
      } else if (wg == 1) {
        float cs[7][4];
#pragma unroll
        for (int j = 0; j < 7; j++) cs[j][0] = cs[j][1] = cs[j][2] = cs[j][3] = 0.f;
        if (tid < 64) sts32(sb + OFF_EXT + 4 * tid, 0x3f803f80u);
        fence_async_smem();
        bar_sync(4);
        const uint64_t da0 = make_desc(sb, 16, 1024, 1), db = make_desc(sb + OFF_EXT, 128, 128, 0);
        int s = 0, ph = 0;
#pragma unroll 1
        for (int kb = CS_KB; kb < 10; kb++) {
          mbar_wait(BAR(B_FULL1 + s), ph);
          wg_fence();
#pragma unroll 1
          for (int kk = 0; kk < 4; kk++) {
#pragma unroll
            for (int j = 0; j < 7; j++) wgmma_ss_8_10(cs[j], da0 + (s * (CS_STAGE >> 4) + kk * (2048 >> 4)) + j * (8192 >> 4), db);
            wg_commit();
          }
          wg_wait<0>();
          if (tid < 4) mbar_arrive(BAR(B_EMPTY1 + s));
          if (++s == 3) { s = 0; ph ^= 1; }
        }
        mbar_wait(BAR(B_EPOCH), 0);
        const unsigned ep = lds32(sb + OFF_MISC);
#pragma unroll
        for (int j = 0; j < 7; j++) {
          const float a = (c & 1) ? cs[j][2] : cs[j][0], b = __shfl_down_sync(0xffffffffu, a, 4);
          if (c < 2 && !(g & 1)) tag_store(P.cs + CSP + 32 * (7 * (g1 - 128) + j) + 8 * w4 + 4 * c + (g >> 1), a, b, ep);
        }
        TZ(tid, 24);
        if (tid < 2 * G2_NST) mbar_arrive(BAR(B_EMPTY2 + (tid >> 1)));
      }
    } else {
      if (has1) {
        const bf16* skp = P.shift_k + (128 * (w4 >> 1) + 64 * (w4 & 1) + 4 * (lane & 15)) * 4;
        uint4 tap0 = ldg128(skp), tap1 = ldg128(skp + 8);
        auto stats = [&]() {
        mbar_wait(BAR(B_STAT), 0);
        TZ(tid, 19);
        float sum = 0.f, sq = 0.f;
        const uint32_t sa = sb + OFF_SR + (tid >> 3) * 1280 + 16 * (lane & 7);
        uint4 nq[2] = {lds128(sa), lds128(sa + 128)};
#pragma unroll 1
        for (int z = 0; z < 5; z++) {
          const uint4 xq[2] = {nq[0], nq[1]};
          if (z < 4) { nq[0] = lds128(sa + 256 * z + 256); nq[1] = lds128(sa + 256 * z + 384); }
          else warp_arrive(BAR(B_STATFREE) + ((xq[0].x | xq[1].x) & P.zero));
#pragma unroll
          for (int i = 0; i < 2; i++) {
            const uint32_t u[4] = {xq[i].x, xq[i].y, xq[i].z, xq[i].w};
#pragma unroll
            for (int e = 0; e < 4; e++) { const float a = blo(u[e]), b = bhi(u[e]); sum += a + b; sq = fmaf(a, a, fmaf(b, b, sq)); }
          }
        }
#pragma unroll
        for (int o = 1; o < 8; o *= 2) { sum += __shfl_xor_sync(0xffffffffu, sum, o); sq += __shfl_xor_sync(0xffffffffu, sq, o); }
        const float mean = sum * (1.f / D_), var = fmaxf(fmaf(-mean, mean, sq * (1.f / D_)), 0.f);
        if ((lane & 7) == 0) tag_store(P.stats + 16 * g1 + (tid >> 3), mean, rsqrtf(var + 1e-5f), lds32(sb + OFF_MISC));
        TZ(tid, 22);
        };
        const uint32_t slot = sb + OFF_KV + (w4 >> 1) * KV_SLOT;
        const uint32_t ka = slot + 8 * (lane >> 4) * 256 + 128 * (w4 & 1) + 8 * (lane & 15);
        const uint32_t zo = (64 * (w4 & 1) + (lane & 15)) * 32 + (lane >> 4) * 16;
        mbar_wait(BAR(B_EPOCH), 0);
        const uint32_t tagm = lane < 16 ? 0x00010001u : 0u, tagv = (lds32(sb + OFF_MISC) & 1) ? tagm : 0u;
#pragma unroll 1
        for (int r = w4 >> 1; r < 5; r += 2) {
          uint32_t wa[4], wb[4], p[8], q[8];
          uint2 kk[11];
          tap_split(tap0, wa); tap_split(tap1, wb);
          if (r < 3) { skp += 1024; tap0 = ldg128(skp); tap1 = ldg128(skp + 8); }
          mbar_wait(BAR(B_KV + (r & 1)), (r >> 1) & 1);
          TZ(tid & 63, 58 + r);
#pragma unroll
          for (int j = 0; j < 11; j++) kk[j] = lds64(ka + j * 256);
#pragma unroll
          for (int j = 0; j < 8; j++) { const uint2 vv = lds64(ka + (19 + j) * 256); p[j] = vv.x; q[j] = vv.y; }
#pragma unroll
          for (int j = 0; j < 8; j++) {
            p[j] = kv_elem(kk[j].x, kk[j + 1].x, kk[j + 2].x, kk[j + 3].x, wa, p[j]);
            q[j] = kv_elem(kk[j].y, kk[j + 1].y, kk[j + 2].y, kk[j + 3].y, wb, q[j]);
          }
          asm volatile("bar.sync %0, 64;" ::"r"(5 + (r & 1) + ((p[0] | p[1] | p[2] | p[3] | p[4] | p[5] | p[6] | p[7]) & P.zero)) : "memory");
          if (r < 4 && w4 == 0 && elect()) kv_issue(P, slot, BAR(B_KV), r + 2, g1);
          if (r == 2) mbar_wait(BAR(B_KVR), 0);
          const uint32_t z = zo + (r < 4 && w4 < 2 ? sb + OFF_KVS : slot + KV_V);
          p[0] = (p[0] & ~tagm) | tagv; q[0] = (q[0] & ~tagm) | tagv;
          kv_store(z, p); kv_store(z + 1024, q);
          fence_async_smem();
          warp_arrive(BAR(B_KVS + (r >> 1)));
          if (r < 2) stats();
        }
        TZ(tid, 21);
        dft_load(dft, P.tab, tid);
      }
    }

    if (has1) {
      mbar_wait(BAR(B_DFT), 0);
      const uint32_t ep = lds32(sb + OFF_MISC);
      int tries = 0;
#pragma unroll 1
      for (int l = wg == 0 ? CH_W0 : wg == 1 ? CH_W1 : CH_W2; (l & 15) != 15;) {
        const int i = l & 15;
        const float dv = c == 0 ? __uint_as_float(lds32(sb + OFF_MISC + 4 + 4 * i)) : 0.f;
        mbar_wait(BAR(B_CX + i), tries & 1);
        TZ(tid, 30 + 4 * i);
        if (conv(dft, sb, conv_tile(sb, i), dv, 1 + wg, w4, lane, threadIdx.x == 0 && (l >> 4) == 15 && !tries ? P.flags + FL_G2 + 32 * mp.z : nullptr, ep, P.zero)) {
          warp_arrive(BAR(B_RD + i));
          l >>= 4; tries = 0;
        } else {
          bar_sync(1 + wg);
          trap_above(++tries, 100000);
          if (tid == 0) { conv_issue_f(P, conv_tile(sb, i), g1 + 128 * i, BAR(B_CX + i)); conv_issue_x(P, conv_tile(sb, i), g1 + 128 * i, BAR(B_CX + i)); }
        }
        TZ(tid, 32 + 4 * i);
      }
    }
    if (wg == 2 && has2) {
      const uint2* const ps[1] = {P.stats + min(80 * tj + tid, S_ - 1)};
      uint2 sv[1] = {tag_load(ps[0])};
      mbar_wait(BAR(B_EPOCH), 0);
      tag_wait<1>(ps, sv, lds32(sb + OFF_MISC));
      const float r = __uint_as_float(sv[0].y), mr = -__uint_as_float(sv[0].x) * r;
      const float r2 = __shfl_down_sync(0xffffffffu, r, 1), mr2 = __shfl_down_sync(0xffffffffu, mr, 1);
      if (tid < 80 && !(tid & 1)) sts128(sb + OFF_ST2 + 8 * tid, make_uint4(pack2(r, r2), pack2(mr, mr2), __float_as_uint(0.25f * r), __float_as_uint(0.25f * r2)));
      warp_arrive(BAR(B_EP));
    }
    if ((!has2 || wg == 2) && tid == 0) mbar_arrive(BAR(B_DONE));
    if (has2 && wg < 2) {
      float acc[40];
      const uint64_t da0 = make_desc(sb + wg * 8192, 16, 1024, 1), db0 = make_desc(sb + G2_B, 16, 1024, 1);
      const float b20 = 0.5f * ldg_bf16(P.b2 + 128 * dt + 64 * wg + 16 * w4 + g), b21 = 0.5f * ldg_bf16(P.b2 + 128 * dt + 64 * wg + 16 * w4 + g + 8);
      uint32_t ta[3];
#pragma unroll
      for (int q = 0; q < 3; q++) {
        const int r = min(q < 2 ? 32 * q + lane : 64 + (lane & 15), S_ - 1 - 80 * tj);
        ta[q] = sb + G2_B + r * 128 + ((r & 7) << 4) + 4 * ((2 * tj + (r >> 3)) & 3);
      }
      mbar_wait(BAR(B_EPOCH), 0);
      const uint32_t ep = lds32(sb + OFF_MISC);
      if (threadIdx.x == 0) mbar_arrive(BAR(B_GO));
      mbar_wait(BAR(B_GO), 0);
      const bool lead = tid == 0;
      const int mi = lane >> 3, rr = lane & 7;
      const uint32_t xa = sb + OFF_XT + wg * XT_STEP + ((mi >> 1) * 8 + rr) * 128 + (((2 * w4 + (mi & 1)) ^ rr) << 4);
      const uint32_t ya = sb + OFF_YT + (64 * wg + 16 * w4 + (mi & 1) * 8 + rr) * 160 + (mi >> 1) * 16;
      uint32_t xr[5][4], xn[5][4];
      uint2 rq[10];
#pragma unroll
      for (int i = 0; i < 40; i++) acc[i] = 0.f;
      uint32_t bad = 0, tg[6] = {ep, ep, ep, ep, ep, ep};
#pragma unroll 1
      for (int k0 = 0; k0 < 9; k0++) {
        const int s0 = 3 * (k0 & 1);
        const uint64_t da = da0 + s0 * (G2_STAGE >> 4), db = db0 + s0 * (G2_STAGE >> 4);
        const uint32_t fb = BAR(B_FULL2 + s0);
#pragma unroll
        for (int u = 0; u < 3; u++) {
          if (u == SK2 && k0 == 8 && wg == 1) mbar_wait(BAR(B_SKEW), 0);
          mbar_wait(fb + 8 * u, (k0 >> 1) & 1);
          TZ(threadIdx.x, 64 + 32 + 3 * k0 + u);
          wg_fence();
#pragma unroll
          for (int kk = 0; kk < 4; kk++)
            wgmma_ss_80_10(acc, da + (u * (G2_STAGE >> 4) + kk * (2048 >> 4)), db + (u * (G2_STAGE >> 4) + 2 * kk));
          wg_commit();
          if (CHK == 1 && warp == 0) {
            for (int q = 0; q < 6; q++) asm volatile("lop3.b32 %0, %0, %1, %2, 0xf6;" : "+r"(bad) : "r"(tg[q]), "r"(ep));
#pragma unroll
            for (int q = 0; q < 3; q++) {
              tg[q] = lds32(ta[q] + (s0 + u) * G2_STAGE);
              if (k0 == 8) tg[3 + q] = lds32((ta[q] ^ 64) + (s0 + u) * G2_STAGE);
            }
          }
          if (SK2 > 2 || k0 < 8) wg_wait<1>();
          if (u) { if (lead) mbar_arrive(fb + 8 * (G2_NST + u - 1)); }
          else if (lead && k0) mbar_arrive(BAR(B_EMPTY2 + 5) - 8 * s0);
        }
      }
      if (SK2 <= 2 && threadIdx.x == 0) mbar_arrive(BAR(B_SKEW));
      if (CHK < 2 && warp == 0) {
        for (int q = 0; q < 6; q++) asm volatile("lop3.b32 %0, %0, %1, %2, 0xf6;" : "+r"(bad) : "r"(tg[q]), "r"(ep));
        bad = __any_sync(0xffffffffu, bad & 1);
        if (lane == 0) { sts32(sb + OFF_MISC + 28, bad); mbar_arrive(BAR(B_VD)); }
      }
      mbar_wait(BAR(B_EP), 0);
#pragma unroll
      for (int i = 0; i < 10; i++) {
        if (!(i & 1)) ldsm4t(xa + i * 1024, xr[i >> 1]);
        const uint4 st = lds128(sb + OFF_ST2 + 16 * (4 * i + c));
        rq[i] = make_uint2(st.z, st.w);
#pragma unroll
        for (int hf = 0; hf < 2; hf++) xn[i >> 1][2 * (i & 1) + hf] = hfma2(xr[i >> 1][2 * (i & 1) + hf], st.x, st.y);
      }
      mbar_wait(BAR(B_VD), 0);
      const uint32_t again = lds32(sb + OFF_MISC + 28);
      wg_wait<0>();
      if (__any_sync(0xffffffffu, again)) {
#pragma unroll
        for (int i = 0; i < 40; i++) acc[i] = 0.f;
#pragma unroll 1
        for (int kb = 0, n = 0; kb < 27 && n < 100000; n++) {
          asm volatile("bar.sync 9, 256;" ::: "memory");
          if (threadIdx.x == 0) {
            mbar_expect(BAR(B_RT), 26624);
            tma3d(sb, &P.w2, 0, 64 * g2_block(kb), 2 * dt, BAR(B_RT));
            tma2d(sb + G2_B, &P.h_ld, 64 * g2_block(kb), 80 * tj, BAR(B_RT));
          }
          mbar_wait_b(BAR(B_RT), n & 1);
          bad = 0;
#pragma unroll
          for (int q = 0; q < 6; q++) bad |= lds32(ta[q >> 1] ^ (kb >= 24 && (q & 1) ? 64 : 0)) ^ ep;
          if (__any_sync(0xffffffffu, bad & 1)) continue;
          wg_fence();
#pragma unroll
          for (int kk = 0; kk < 4; kk++) wgmma_ss_80_10(acc, da0 + kk * (2048 >> 4), db0 + 2 * kk);
          wg_commit();
          wg_wait<0>();
          kb++;
        }
      }
      TZ(tid, 50 + wg);
      mbar_wait(BAR(B_EPY), 0);
      if (tid == 0) mbar_arrive(BAR(B_DONE));
      TZ(tid, 52 + wg);
#pragma unroll
      for (int i = 0; i < 10; i += 2) {
        uint32_t yr[4], ov[4];
        ldsm4(ya + i * 16, yr);
#pragma unroll
        for (int j = 0; j < 2; j++) {
#pragma unroll
          for (int hf = 0; hf < 2; hf++) {
            const float bb2 = hf ? b21 : b20;
            const float z0 = fmaf(acc[4 * (i + j) + 2 * hf], __uint_as_float(rq[i + j].x), bb2), z1 = fmaf(acc[4 * (i + j) + 2 * hf + 1], __uint_as_float(rq[i + j].y), bb2);
            const uint32_t gt = pack2(fmaf(z0, tanh_fast(z0), z0), fmaf(z1, tanh_fast(z1), z1));
            ov[2 * j + hf] = hfma2(hmul2(xn[i >> 1][2 * j + hf], yr[2 * j + hf]), gt, xr[i >> 1][2 * j + hf]);
          }
        }
        if (i == 4 || i == 8) { fence_async_smem(); warp_arrive(BAR(B_HS + 4 * wg + (i == 8))); }
        stsm4t(xa + i * 1024, ov[0], ov[1], ov[2], ov[3]);
      }
      fence_async_smem();
      warp_arrive(BAR(B_HS + 4 * wg + 2));
      TZ(tid, 6 + wg);
    }
  } else {
    asm volatile("setmaxnreg.dec.sync.aligned.u32 %0;" ::"n"(R_P));
    if (warp >= 14) {
      if (has1) {
        {
          float cs[8];
#pragma unroll
          for (int e = 0; e < 8; e++) cs[e] = 0.f;
          const int q = min(2 * rb, 26) + (lane & 1), kr = lane >> 1;
          const uint32_t stp = rb < 8 ? 2048 : 1024;
          const uint32_t a0 = sb + (warp & 1) * 2 * stp + (rb < 8 ? (q >> 3) * 8192 + kr * 128 + (((q & 7) ^ (kr & 7)) << 4)
                                                  : 16384 + ((q - 16) >> 2) * 4096 + kr * 64 + (((q & 3) ^ ((kr >> 1) & 3)) << 4));
#pragma unroll 1
          for (int kb = 0; kb < CS_KB; kb++) {
            const uint32_t a = a0 + (kb & 3) * G1_W;
            mbar_wait(BAR(B_FULL1 + (kb & 3)), kb >> 2);
            const uint4 u = lds128(a), w = lds128(a + stp);
            warp_arrive(BAR(B_EMPTY1 + (kb & 3)) + ((u.x | w.x) & P.zero));
            cs[0] += blo(u.x) + blo(w.x); cs[1] += bhi(u.x) + bhi(w.x); cs[2] += blo(u.y) + blo(w.y); cs[3] += bhi(u.y) + bhi(w.y);
            cs[4] += blo(u.z) + blo(w.z); cs[5] += bhi(u.z) + bhi(w.z); cs[6] += blo(u.w) + blo(w.w); cs[7] += bhi(u.w) + bhi(w.w);
          }
#pragma unroll
          for (int kb = CS_KB; kb < 6; kb++) { mbar_wait(BAR(B_EMPTY1 + (kb & 3)), 0); if (elect()) mbar_arrive(BAR(B_EMPTY1 + (kb & 3))); }
#pragma unroll
          for (int e = 0; e < 4; e++) {
            const bool up = lane & 4;
            const float o = __shfl_xor_sync(0xffffffffu, up ? cs[e] : cs[e + 4], 4);
            cs[e] = (up ? cs[e + 4] : cs[e]) + o;
          }
#pragma unroll
          for (int e = 0; e < 2; e++) {
            const bool up = lane & 2;
            const float o = __shfl_xor_sync(0xffffffffu, up ? cs[e] : cs[e + 2], 2);
            cs[e] = (up ? cs[e + 2] : cs[e]) + o;
            cs[e] += __shfl_xor_sync(0xffffffffu, cs[e], 8);
            cs[e] += __shfl_xor_sync(0xffffffffu, cs[e], 16);
          }
          const uint32_t xa = sb + OFF_ST2 + 8 * (lane & 7);
          if (warp == 15 && lane < 8) { sts32(xa, __float_as_uint(cs[0])); sts32(xa + 4, __float_as_uint(cs[1])); }
          asm volatile("bar.sync 8, 64;" ::: "memory");
          if (warp == 14) {
            const uint2 o = lds64(xa);
            mbar_wait(BAR(B_EPOCH), 0);
            if (lane < 8 && rb < 14 && (rb < 12 || fs < 6))
              tag_store(P.cs + (ext_col(16 * rb, fs) >> 1) + 4 * (lane & 1) + (lane >> 1), cs[0] + __uint_as_float(o.x), cs[1] + __uint_as_float(o.y), lds32(sb + OFF_MISC));
            TZ(lane, 18);
          }
        }
        if (warp == 15) {
#pragma unroll 1
          for (int j = 0; j < 2; j++) {
            const int n0 = 2 * lane + 64 * j, n1 = min(128 + n0, 222);
            const uint32_t b0 = ldg32(P.b1 + ext_col(n0, fs)), b1 = ldg32(P.b1 + ext_col(n1, fs));
            const uint32_t e0 = sb + OFF_EXT + ext_off(n0, 0), e1 = sb + OFF_EXT + ext_off(n1, 0);
#pragma unroll
            for (int k = 3; k < 8; k++) { sts32((e0 + 128 * k) ^ (k << 4), k < 5 ? b0 : 0u); sts32((e1 + 64 * k) ^ ((k >> 1) << 4), k < 5 ? b1 : 0u); }
          }
        }
      }
      mbar_wait(BAR(B_EPOCH), 0);
      const unsigned ep = lds32(sb + OFF_MISC);
      if (has1) {
        const int l2 = tid - 64, n0 = 2 * l2, n1 = min(128 + 2 * l2, 222), f0 = ext_col(n0, fs), f1 = ext_col(n1, fs);
        const uint32_t e0 = sb + OFF_EXT + ext_off(n0, 0), e1 = sb + OFF_EXT + ext_off(n1, 0);
        const uint2* const pc[4] = {P.cs + (f0 >> 1), P.cs + (f1 >> 1), P.cs + CSP + (f0 >> 1), P.cs + CSP + (f1 >> 1)};
        uint2 v[4] = {tag_load(pc[0]), tag_load(pc[1]), tag_load(pc[2]), tag_load(pc[3])};
        tag_wait<4>(pc, v, ep);
#pragma unroll
        for (int i = 0; i < 2; i++) {
          const float x = __uint_as_float(v[i].x) + __uint_as_float(v[i + 2].x), y = __uint_as_float(v[i].y) + __uint_as_float(v[i + 2].y);
          const uint32_t hi = pack2(x, y), lo = pack2(x - blo(hi), y - bhi(hi));
#pragma unroll
          for (int k = 0; k < 3; k++) sts32(i ? (e1 + 64 * k) ^ ((k >> 1) << 4) : (e0 + 128 * k) ^ (k << 4), k < 2 ? hi : lo);
        }
        TZ(lane, 25);
        fence_async_smem();
        warp_arrive(BAR(B_TAB));
      }
      __syncwarp();
      if (elect()) {
        if (warp == 15) {
          if (CHK == 3) for (int s = 0; s < G2_NST; s++) mbar_arrive(BAR(B_EMPTY2 + s));
          if (has1) {
            prefetch_map(&P.h_st); prefetch_map(&P.h_st2);
#pragma unroll
            for (int j = 0; j < 4; j++) {
              mbar_wait(BAR(B_HS + 4 * (j & 1) + (j & 2)), 0);
              if (j & 1) TS(33 + 4 * (j & 2));
              tma2d_st(&P.h_st, 192 * fs + 64 * (j & 2), 128 * rb + 64 * (j & 1), sb + OFF_X + (j & 2) * G1_X + (j & 1) * 8192);
              if (j == 1) {
                bulk_commit();
                bulk_wait_all();
                h_flag(P, rb, 0);
                mbar_arrive(BAR(B_EMPTY2 + 4));
                TS(26);
              }
            }
            if (fs < 6) {
#pragma unroll
              for (int w = 0; w < 2; w++) {
                mbar_wait(BAR(B_HS + 4 * w + 3), 0);
                tma2d_st(&P.h_st2, 1536 + 32 * fs, 128 * rb + 64 * w, sb + OFF_X + 3 * G1_X + w * 4096);
              }
            }
            bulk_commit();
            bulk_wait_all();
            mbar_arrive(BAR(B_EMPTY2 + 5));
            pub_fence(2);
            h_flag(P, rb, 64);
            TS(14);
          }
          if (has2) {
            h_wait(P, tj, 64, ep);
            mbar_arrive(BAR(B_HB));
            TS(17);
          }
        }
      }
      __syncwarp();
      if (warp == 15 && has2) {
        uint32_t ta[3], bad = 0;
#pragma unroll
        for (int q = 0; q < 3; q++) {
          const int r = min(q < 2 ? 32 * q + lane : 64 + (lane & 15), S_ - 1 - 80 * tj);
          ta[q] = sb + G2_B + r * 128 + ((r & 7) << 4) + 4 * ((2 * tj + (r >> 3)) & 3);
        }
        int s = 0, ph = 0;
#pragma unroll 1
        for (int kb = 0; kb < 27; kb++) {
          mbar_wait(BAR(B_FULL2 + s), ph);
          uint32_t t = 0;
#pragma unroll
          for (int q = 0; q < 3; q++) t |= lds32(ta[q] + s * G2_STAGE) ^ ep;
          if (kb >= 24) {
#pragma unroll
            for (int q = 0; q < 3; q++) t |= lds32((ta[q] ^ 64) + s * G2_STAGE) ^ ep;
          }
          bad |= t;
          if (CHK == 3 && lane == 0) mbar_arrive(BAR(B_EMPTY2 + s) + (t & P.zero));
          if (++s == G2_NST) { s = 0; ph ^= 1; }
        }
        bad = __any_sync(0xffffffffu, bad & 1);
        if (lane == 0) { sts32(sb + OFF_MISC + 28, bad); mbar_arrive(BAR(B_VD)); }
      }
      if (elect()) {
        if (warp == 14 && has2) {
          prefetch_map(&P.h_ld);
          h_wait(P, tj, 0, ep);
          TS(16);
#pragma unroll 1
          for (int k0 = 0; k0 < 9; k0++) {
#pragma unroll
            for (int u = 0; u < 3; u++) {
              const int kb = 3 * k0 + u, s = 3 * (k0 & 1) + u;
              if (u == 0 && k0 == 2) {
                if (USE_GO) flag_wait<false>(P.flags + FL_G2 + 32 * mp.z, ep * mp.w);
                mbar_arrive(BAR(B_GO));
                TS(20);
              }
              if (u == 2 && k0 == 2) mbar_wait(BAR(B_H1), 0);
              if (u == 1 && k0 == 5) mbar_wait(BAR(B_HB), 0);
              mbar_wait(BAR(B_EMPTY2 + s), (k0 >> 1) & 1);
              TS(64 + 96 + kb);
              mbar_expect(BAR(B_FULL2 + s), 10240);
              tma2d(sb + s * G2_STAGE + G2_B, &P.h_ld, 64 * g2_block(kb), 80 * tj, BAR(B_FULL2 + s));
              if (u == YK % 3 && k0 == YK / 3) mbar_arrive(BAR(B_LATE));
            }
          }
        }
        if (has2) {
          const int w = 15 - warp;
          prefetch_map(&P.out_st);
#pragma unroll
          for (int j = 0; j < 5; j++) {
            if (!(j & 1)) mbar_wait(BAR(B_HS + 4 * w + (j >> 1)), has1);
            tma2d_st(&P.out_st, 128 * dt + 64 * w, 80 * tj + 16 * j, sb + OFF_XT + w * XT_STEP + j * 2048);
          }
          bulk_commit();
        }
        mbar_arrive(BAR(B_DONE));
        bulk_wait_read();
        TS(54 + 15 - warp);
      }
    } else if (warp == 13) {
      unsigned ep;
      asm volatile("ld.relaxed.gpu.global.u32 %0, [%1];" : "=r"(ep) : "l"(P.flags + FL_EPOCH) : "memory");
      if (has1 && lane < 5) sts32(sb + OFF_MISC + 4 + 4 * lane, __float_as_uint(ldg_bf16(P.ssm_D + g1 + 128 * lane)));
      ep += 1;
      __syncwarp();
      if (elect()) {
        sts32(sb + OFF_MISC, ep); sts32(sb + OFF_MISC + 24, 0);
        mbar_arrive(BAR(B_EPOCH));
        flag_add_rlx(P.flags + FL_START, 1);
        if (!has1 && has2) flag_add_rlx(P.flags + FL_G2 + 32 * mp.z, 1);
        if (has1) {
          prefetch_map(&P.kvz); prefetch_map(&P.f_ld); prefetch_map(&P.y_st);
#define W(b) mbar_wait_b(BAR(b), 0);
#define KV(r) kv_issue(P, sb + OFF_KV + (r) * KV_SLOT, BAR(B_KV + (r)), r, g1);
#define PUBA kv_out(P, sb + OFF_KVS, 0, g1); kv_out(P, sb + OFF_KV + KV_SLOT + KV_V, 1, g1); bulk_commit(); bulk_wait_read(); \
  kv_issue(P, sb + OFF_KV + KV_SLOT, BAR(B_KV + 1), 3, g1); mbar_arrive(BAR(B_KVR)); bulk_wait_all(); pub_fence(1); flag_add_rlx(P.flags + FL_KV, 1); TS(56);
#define PUBB mbar_wait_b(BAR(B_KVS + 1), 0); kv_out(P, sb + OFF_KVS, 2, g1); kv_out(P, sb + OFF_KV + KV_SLOT + KV_V, 3, g1); bulk_commit(); bulk_wait_read();
#define FLB bulk_wait_all(); pub_fence(1); flag_add_rlx(P.flags + FL_KV + 32, 1); TS(57);
#define PUBC mbar_wait_b(BAR(B_KVS + 2), 0); kv_out(P, sb + OFF_KV + KV_V, 4, g1); bulk_commit(); bulk_wait_read();
#define FLC bulk_wait_all(); pub_fence(1); flag_add_rlx(P.flags + FL_KV + 64, 1); TS(63);
#define KC mbar_expect(BAR(B_DFT), 12288); bulk_g2s(sb + OFF_DFT, P.tab, 12288, BAR(B_DFT));
#define F(c) conv_issue_f(P, conv_tile(sb, c), g1 + 128 * (c), BAR(B_CX + (c)));
#define G(i) flag_wait<true>(P.flags + FL_KV + 32 * (i), ep * 128); fence_async_global(); TS((i) == 2 ? 28 : 23 + 6 * (i));
#define X(c) conv_issue_x(P, conv_tile(sb, c), g1 + 128 * (c), BAR(B_CX + (c)));
#define Y(c) mbar_wait_b(BAR(B_RD + (c)), 0); tma2d_st(&P.y_st, 0, 32 * (g1 + 128 * (c)), conv_tile(sb, c)); bulk_commit();
#define XE mbar_expect(BAR(B_EP), 20480); tma2d(sb + OFF_XT, &P.x_ep, 128 * dt, 80 * tj, BAR(B_EP)); tma2d(sb + OFF_XT + XT_STEP, &P.x_ep, 128 * dt + 64, 80 * tj, BAR(B_EP));
#define R bulk_wait_read();
#define A(b) mbar_arrive(BAR(b));
#define PF(c) bulk_prefetch(P.ssm_k + (g1 + 128 * (c)) * S_, 4096);
#define PW bulk_prefetch(P.w2p + g1 * (F_ * D_ / 128), F_ * D_ / 64);
          AUX_SEQ
#undef W
#undef PUBA
#undef PUBB
#undef PUBC
#undef FLB
#undef FLC
#undef KC
#undef F
#undef G
#undef X
#undef Y
#undef R
#undef XE
#undef A
#undef PF
#undef PW
          bulk_wait_all(); pub_fence(4);
          flag_add_rlx(P.flags + FL_Y, 1);
          TS(12);
          if (g1 == 0) { flag_wait<true>(P.flags + FL_START, ep * NCTA); P.flags[FL_EPOCH] = ep; }
        }
        if (has2) {
          mbar_expect(BAR(B_EPY), 20480);
          prefetch_map(&P.y_ld);
          if (!has1) {
            mbar_expect(BAR(B_EP), 20480);
            tma2d(sb + OFF_XT, &P.x_ep, 128 * dt, 80 * tj, BAR(B_EP));
            tma2d(sb + OFF_XT + XT_STEP, &P.x_ep, 128 * dt + 64, 80 * tj, BAR(B_EP));
          }
          flag_wait<true>(P.flags + FL_Y, ep * 128);
          fence_async_global();
          mbar_wait_b(BAR(B_LATE), 0);
          TS(13);
          tma2d(sb + OFF_YT, &P.y_ld, 80 * tj, 128 * dt, BAR(B_EPY));
        }
        mbar_wait_b(BAR(B_DONE), 0);
      }
    } else {
      const bool lead = elect();
      if (lead) {
        mbar_init(BAR(B_FULL1), 1);
        fence_async_smem();
        if (has1) g1_issue(P, sb, 0, BAR(B_FULL1), 0, rb, fs);
        else { mbar_expect(BAR(B_FULL1), CS_STAGE); tma3d(sb, &P.w1_cs, 0, 64 * CS_KB, 7 * (g1 - 128), BAR(B_FULL1)); }
#pragma unroll
        for (int b = 1; b < B_FIRST; b++) mbar_init(BAR(b), 1);
        fence_async_smem();
      }
      __syncwarp();
      asm volatile("bar.arrive 0, 512;" ::: "memory");
      if (lead) {
        if (has1) {
#define S(kb) g1_issue(P, sb, kb, BAR(B_FULL1 + (kb)), kb, rb, fs);
#define K(r) kv_issue(P, sb + OFF_KV + (r) * KV_SLOT, BAR(B_KV + (r)), r, g1);
#define T mbar_expect(BAR(B_STAT), 20480); bulk_g2s(sb + OFF_SR, P.x + g1 * 16 * D_, 20480, BAR(B_STAT));
          INIT_SEQ
          TS(64 + 20 + 3);
        } else {
#pragma unroll
          for (int kb = 1; kb < 3; kb++) { mbar_expect(BAR(B_FULL1 + kb), CS_STAGE); tma3d(sb + kb * CS_STAGE, &P.w1_cs, 0, 64 * (CS_KB + kb), 7 * (g1 - 128), BAR(B_FULL1 + kb)); }
        }
      }
      __syncwarp();
      asm volatile("bar.sync 7, 512;" ::: "memory");
      if (lead) {
        if (has1) {
#pragma unroll 1
          for (int kb = G1_NST; kb < 10; kb++) {
            const int s = kb & 3;
            mbar_wait(BAR(B_EMPTY1 + s), ((kb >> 2) - 1) & 1);
            TS(64 + 20 + kb);
            g1_issue(P, sb, s, BAR(B_FULL1 + s), kb, rb, fs);
          }
        }
      }
      __syncwarp();
      if (has1) {
        const uint2* const p0 = P.stats + 128 * rb + lane;
        const uint2* const ps[4] = {p0, p0 + 32, p0 + 64, p0 + 96};
        uint2 sv[4] = {tag_load(ps[0]), tag_load(ps[1]), tag_load(ps[2]), tag_load(ps[3])};
        mbar_wait(BAR(B_EPOCH), 0);
        tag_wait<4>(ps, sv, lds32(sb + OFF_MISC));
#pragma unroll
        for (int j = 0; j < 4; j++) {
          const float mn = -__uint_as_float(sv[j].x), mh = bf_round(mn), sd = rcp_fast(__uint_as_float(sv[j].y)), sh = bf_round(sd);
          sts128(sb + OFF_ST1 + 16 * (lane + 32 * j), make_uint4(pack2(mh, mn - mh), pack2(mh, sh), pack2(sd - sh, 0.f), sv[j].y));
        }
        warp_arrive(BAR(B_TAB));
        TZ(lane, 11);
      }
      if (lead) {
        if (!has1) {
#pragma unroll
          for (int kb = CS_KB + 3; kb < 10; kb++) {
            const int s = kb - CS_KB - 3;
            mbar_wait(BAR(B_EMPTY1 + s), 0);
            mbar_expect(BAR(B_FULL1 + s), CS_STAGE);
            tma3d(sb + s * CS_STAGE, &P.w1_cs, 0, 64 * kb, 7 * (g1 - 128), BAR(B_FULL1 + s));
          }
        }
        auto h_second = [&]() {
#pragma unroll
          for (int w = 0; w < 2; w++) {
            mbar_wait(BAR(B_HS + 4 * w + 1), 0);
            tma2d_st(&P.h_st, 192 * fs + 64, 128 * rb + 64 * w, sb + OFF_X + G1_X + w * 8192);
          }
          TS(37);
          bulk_commit();
          bulk_wait_all();
          mbar_arrive(BAR(B_EMPTY2 + 4)); mbar_arrive(BAR(B_EMPTY2 + 5));
          pub_fence(2);
          h_flag(P, rb, 32);
          TS(27);
        };
        if (has2) {
          prefetch_map(&P.w2);
#pragma unroll 1
          for (int k0 = 0; k0 < 9; k0++) {
#pragma unroll
            for (int u = 0; u < 3; u++) {
              const int kb = 3 * k0 + u, s = 3 * (k0 & 1) + u;
              if (u == 1 && k0 == 1 && has1) h_second();
              if (u == 0 && k0 == 2) { mbar_wait(BAR(B_EPOCH), 0); h_wait(P, tj, 32, lds32(sb + OFF_MISC)); mbar_arrive(BAR(B_H1)); TS(15); }
              mbar_wait(BAR(B_EMPTY2 + s), (k0 >> 1) & 1);
              mbar_expect(BAR(B_FULL2 + s), 16384);
              tma3d(sb + s * G2_STAGE, &P.w2, 0, 64 * g2_block(kb), 2 * dt, BAR(B_FULL2 + s));
            }
          }
        }
        mbar_arrive(BAR(B_DONE));
      }
    }
  }

#undef BAR
}

typedef CUresult (*EncodeFn)(CUtensorMap*, CUtensorMapDataType, cuuint32_t, void*, const cuuint64_t*, const cuuint64_t*, const cuuint32_t*,
                             const cuuint32_t*, CUtensorMapInterleave, CUtensorMapSwizzle, CUtensorMapL2promotion, CUtensorMapFloatOOBfill);

static void enc(EncodeFn f, CUtensorMap* m, const void* base, int rank, const cuuint64_t* dims, const cuuint64_t* strides, const cuuint32_t* box, CUtensorMapSwizzle sw) {
  const cuuint32_t es[5] = {1, 1, 1, 1, 1};
  f(m, CU_TENSOR_MAP_DATA_TYPE_BFLOAT16, rank, const_cast<void*>(base), dims, strides, box, es, CU_TENSOR_MAP_INTERLEAVE_NONE, sw,
    CU_TENSOR_MAP_L2_PROMOTION_L2_128B, CU_TENSOR_MAP_FLOAT_OOB_FILL_NONE);
}
static void enc2(EncodeFn f, CUtensorMap* m, const void* base, uint64_t d0, uint64_t d1, uint32_t b0, uint32_t b1, CUtensorMapSwizzle sw) {
  const cuuint64_t dims[2] = {d0, d1}, strides[1] = {d0 * 2};
  const cuuint32_t box[2] = {b0, b1};
  enc(f, m, base, 2, dims, strides, box, sw);
}

extern "C" void kernel_launch(void* const* d_in, const int* in_sizes, int n_in, void* d_out, int out_size) {
  (void)in_sizes; (void)n_in; (void)out_size;
  static EncodeFn fn = nullptr;
  static void *p_h, *p_kvZ, *p_yT, *p_stats, *p_cs, *p_flags, *p_tab;
  if (!fn) {
    cudaDriverEntryPointQueryResult qr;
    void* f = nullptr;
    cudaGetDriverEntryPoint("cuTensorMapEncodeTiled", &f, cudaEnableDefault, &qr);
    fn = (EncodeFn)f;
    cudaFuncSetAttribute(h3_fused_kernel, cudaFuncAttributeMaxDynamicSharedMemorySize, SMEM_BYTES);
    cudaGetSymbolAddress(&p_h, g_h); cudaGetSymbolAddress(&p_kvZ, g_kvZ); cudaGetSymbolAddress(&p_yT, g_yT);
    cudaGetSymbolAddress(&p_stats, g_stats); cudaGetSymbolAddress(&p_cs, g_cs); cudaGetSymbolAddress(&p_flags, g_flags); cudaGetSymbolAddress(&p_tab, g_tab);
  }
  Params P;
  const bf16 *x = (const bf16*)d_in[0], *k = (const bf16*)d_in[1], *v = (const bf16*)d_in[2];
  const bf16 *w1 = (const bf16*)d_in[7], *w2 = (const bf16*)d_in[9];
  P.x = x; P.shift_k = (const bf16*)d_in[3]; P.ssm_k = (const bf16*)d_in[4]; P.ssm_D = (const bf16*)d_in[5];
  P.b1 = (const bf16*)d_in[8]; P.b2 = (const bf16*)d_in[10]; P.w2p = w2;
  P.zero = 0; P.kvZ = (bf16*)p_kvZ; P.tab = (const uint32_t*)p_tab; P.stats = (uint2*)p_stats; P.cs = (uint2*)p_cs; P.flags = (unsigned*)p_flags;
  enc2(fn, &P.x_g1, x, D_, S_, 64, 128, CU_TENSOR_MAP_SWIZZLE_128B);
  {
    const cuuint64_t dims[3] = {64, D_, 27}, strides[2] = {F_ * 2, 128};
    const cuuint32_t box[3] = {64, 64, 2};
    enc(fn, &P.w1_a, w1, 3, dims, strides, box, CU_TENSOR_MAP_SWIZZLE_128B);
    const cuuint32_t box7[3] = {64, 64, 7};
    enc(fn, &P.w1_cs, w1, 3, dims, strides, box7, CU_TENSOR_MAP_SWIZZLE_128B);
    const cuuint64_t dims2[3] = {32, D_, 54}, strides2[2] = {F_ * 2, 64};
    const cuuint32_t box2[3] = {32, 64, 2}, box1[3] = {32, 64, 1};
    enc(fn, &P.w1_b2, w1, 3, dims2, strides2, box2, CU_TENSOR_MAP_SWIZZLE_64B);
    enc(fn, &P.w1_b1, w1, 3, dims2, strides2, box1, CU_TENSOR_MAP_SWIZZLE_64B);
  }
  enc2(fn, &P.h_ld, p_h, F_, S_, 64, 80, CU_TENSOR_MAP_SWIZZLE_128B);
  {
    const cuuint64_t dims[3] = {64, F_, 10}, strides[2] = {D_ * 2, 128};
    const cuuint32_t box[3] = {64, 64, 2};
    enc(fn, &P.w2, w2, 3, dims, strides, box, CU_TENSOR_MAP_SWIZZLE_128B);
  }
  enc2(fn, &P.h_st, p_h, F_, S_, 64, 64, CU_TENSOR_MAP_SWIZZLE_128B);
  enc2(fn, &P.h_st2, p_h, F_, S_, 32, 64, CU_TENSOR_MAP_SWIZZLE_64B);
  enc2(fn, &P.k, k, D_, S_, 128, 19, CU_TENSOR_MAP_SWIZZLE_NONE);
  enc2(fn, &P.v, v, D_, S_, 128, 16, CU_TENSOR_MAP_SWIZZLE_NONE);
  {
    const cuuint64_t dims[3] = {D_ * 16, 32, 4}, strides[2] = {D_ * 128, D_ * 32};
    const cuuint32_t box[3] = {16, 32, 4};
    enc(fn, &P.kvz, p_kvZ, 3, dims, strides, box, CU_TENSOR_MAP_SWIZZLE_32B);
  }
  enc2(fn, &P.f_ld, P.ssm_k, 64, D_ * 32, 64, 32, CU_TENSOR_MAP_SWIZZLE_128B);
  enc2(fn, &P.y_st, p_yT, 64, D_ * 32, 64, 32, CU_TENSOR_MAP_SWIZZLE_128B);
  enc2(fn, &P.y_ld, p_yT, S_, D_, 80, 128, CU_TENSOR_MAP_SWIZZLE_NONE);
  enc2(fn, &P.x_ep, x, D_, S_, 64, 80, CU_TENSOR_MAP_SWIZZLE_128B);
  enc2(fn, &P.out_st, d_out, D_, S_, 64, 16, CU_TENSOR_MAP_SWIZZLE_128B);
  for (int b = 0; b < 64; b++) P.cnt[b] = 1;
  for (int b = 0; b < 5; b++) { P.cnt[B_CX + b] = 2; P.cnt[B_RD + b] = 4; }
  for (int b = 0; b < 4; b++) P.cnt[B_EMPTY1 + b] = 4;
  for (int b = 0; b < 2 * G2_NST; b++) P.cnt[B_FULL2 + b] = CHK == 3 && b >= G2_NST ? 3 : 2;
  P.cnt[B_G1FREE] = P.cnt[B_GO] = 2; P.cnt[B_TAB] = 3; P.cnt[B_EP] = 5; P.cnt[B_DONE] = 6;
  for (int b = 0; b < 8; b++) P.cnt[B_HS + b] = 4;
  P.cnt[B_KVS] = P.cnt[B_KVS + 1] = P.cnt[B_STATFREE] = 4; P.cnt[B_KVS + 2] = 2;
  {
    int mem[9][18], cnt[9] = {0};
    for (int b = 0; b < NCTA; b++) {
      const int tpc = b >> 1;
      const int gp = tpc < 32 ? tpc % 8 : tpc < 60 ? 1 + (tpc - 32) % 7 : tpc < 62 ? tpc - 54 : 8;
      mem[gp][cnt[gp]++] = b;
      P.map[b] = make_uchar4(255, 255, gp, 0);
    }
    const int bi[8] = {0, 0, 0, 1, 1, 2, 3, 2}, bj[8] = {0, 0, 1, 0, 1, 0, 0, 1};
    for (int gp = 1; gp < 8; gp++)
      for (int i = 0; i < 16; i++) P.map[mem[gp][i]].x = (4 * bi[gp] + (i & 3)) * 8 + 4 * bj[gp] + (i >> 2);
    for (int i = 0; i < 8; i++) P.map[mem[0][i]].x = (12 + (i & 3)) * 8 + 4 + (i >> 2);
    for (int i = 0; i < 2; i++) { P.map[mem[6][16 + i]].x = (12 + i) * 8 + 6; P.map[mem[7][16 + i]].x = (14 + i) * 8 + 6; }
    for (int i = 0; i < 4; i++) { P.map[mem[8][i]].x = (12 + i) * 8 + 7; P.map[mem[8][4 + i]].x = 128 + i; }
    const int ord[9] = {6, 1, 2, 0, 8, 7, 3, 4, 5};
    int n = 0;
    for (int q = 0; q < 9; q++)
      for (int i = 0; i < (ord[q] == 8 ? 6 : cnt[ord[q]]); i++, n++) { P.map[mem[ord[q]][i]].y = n / 5 * 8 + n % 5; P.map[mem[ord[q]][i]].w = ord[q] == 8 ? 6 : cnt[ord[q]]; }
  }
  h3_fused_kernel<<<NCTA, 512, SMEM_BYTES, cudaStreamPerThread>>>(P);
}
```

```cpp
#include <cuda_runtime.h>
#include <cuda_bf16.h>
#include <cuda.h>
#include <stdint.h>

#define INIT_SEQ S(1) S(2) S(3) K(0) K(1) T
#define AUX_PRE
#define AUX_SEQ AUX_PRE W(B_KVS) PUBA W(B_STATFREE) KC F(0) PF(1) G(0) X(0) PF(2) PF(3) PUBB X(1) F(1) FLB PF(4) PW PUBC A(B_KVC) F(2) FLC W(B_G1FREE) F(3) G(1) X(3) X(2) G(2) W(B_RD) X(4) F(4) Y(0) Y(1) Y(2) Y(3) R XE Y(4)
#define CH_W0 0xf2
#define CH_W1 0xf3
#define CH_W2 0xf410
#define CS_KB 5
#define CHK 3
#define MIM 1
#define KVCHK 1
#define FB 1
#define DFT_EARLY 3
#define GO_WG 4
#define EREL 0
#define PFW 0
#define SK2 2
#define YK 26
#define DFT_AT 16
#define USE_GO 1
#define GO_AT 2
#define HS_LAG 0
#define LOOKAHEAD 2
#define SPLIT9 0
#define GELU_BF16 4
#define R_G 160
#define R_P 32
#define DBG_TIME 0

namespace {

constexpr int GO_N = (GO_WG & 1) + ((GO_WG >> 1) & 1) + (GO_WG >> 2);
constexpr int S_ = 2048, D_ = 640, F_ = 1728;
constexpr int NCTA = 132;
typedef __nv_bfloat16 bf16;

__device__ __align__(1024) bf16 g_h[S_ * F_];
__device__ __align__(1024) bf16 g_kvZ[D_ * S_];
__device__ __align__(1024) bf16 g_yT[D_ * S_];
__device__ __align__(128) uint2 g_stats[S_];
constexpr int CSP = F_ / 2 + 32;
__device__ __align__(128) uint2 g_cs[2 * CSP];
constexpr int FL_EPOCH = 0, FL_START = 32, FL_KV = 64  , FL_Y = FL_KV + 3 * 32, FL_H = FL_Y + 32  , FL_G2 = FL_H + 96 * 32  , FL_COUNT = FL_G2 + 9 * 32;
__device__ __align__(128) unsigned g_flags[FL_COUNT];
__device__ __align__(128) const uint32_t g_tab[6144] = {
0x3f803f80,0x3f803f80,0x3f803f80,0x3f803f80,0x3f803f80,0x3f803f80,0x3f803f80,0x3f803f80,0x3f803f80,0x3f803f80,0x3f803f80,0x3f803f80,0x3f803f80,0x3f803f80,0x3f803f80,0x3f803f80,
0x0,0x0,0x0,0x0,0x0,0x0,0x0,0x0,0x0,0x0,0x0,0x0,0x0,0x0,0x0,0x0,
0x3f183f2c,0x3edb3f04,0x3e793eac,0x3d493e16,0x3f7d3f80,0x3f713f78,0x3f5c3f67,0x3f3e3f4e,0xbf4ebf3e,0xbf67bf5c,0xbf78bf71,0xbf80bf7d,0xbe16bd49,0xbeacbe79,0xbf04bedb,0xbf2cbf18,
0x3f4e3f3e,0x3f673f5c,0x3f783f71,0x3f803f7d,0x3e163d49,0x3eac3e79,0x3f043edb,0x3f2c3f18,0x3f183f2c,0x3edb3f04,0x3e793eac,0x3d493e16,0x3f7d3f80,0x3f713f78,0x3f5c3f67,0x3f3e3f4e,
0xbf75bf7f,0xbf46bf62,0xbef1bf22,0xbdc9be95,0x3e953dc9,0x3f223ef1,0x3f623f46,0x3f7f3f75,0x3f753f7f,0x3f463f62,0x3ef13f22,0x3dc93e95,0xbe95bdc9,0xbf22bef1,0xbf62bf46,0xbf7fbf75,
0xbe95bdc9,0xbf22bef1,0xbf62bf46,0xbf7fbf75,0xbf75bf7f,0xbf46bf62,0xbef1bf22,0xbdc9be95,0x3e953dc9,0x3f223ef1,0x3f623f46,0x3f7f3f75,0x3f753f7f,0x3f463f62,0x3ef13f22,0x3dc93e95,
0x3eac3f18,0xbe793d49,0xbf3ebf04,0xbf7dbf67,0x3edb3e16,0x3f5c3f2c,0x3f803f78,0x3f4e3f71,0xbf71bf4e,0xbf78bf80,0xbf2cbf5c,0xbe16bedb,0x3f673f7d,0x3f043f3e,0xbd493e79,0xbf18beac,
0x3f713f4e,0x3f783f80,0x3f2c3f5c,0x3e163edb,0xbf67bf7d,0xbf04bf3e,0x3d49be79,0x3f183eac,0x3eac3f18,0xbe793d49,0xbf3ebf04,0xbf7dbf67,0x3edb3e16,0x3f5c3f2c,0x3f803f78,0x3f4e3f71,
0x3f0e3e48,0x3f7b3f55,0x3f553f7b,0x3e483f0e,0xbf0ebe48,0xbf7bbf55,0xbf55bf7b,0xbe48bf0e,0x3f0e3e48,0x3f7b3f55,0x3f553f7b,0x3e483f0e,0xbf0ebe48,0xbf7bbf55,0xbf55bf7b,0xbe48bf0e,
0x3f553f7b,0x3e483f0e,0xbf0ebe48,0xbf7bbf55,0xbf55bf7b,0xbe48bf0e,0x3f0e3e48,0x3f7b3f55,0x3f553f7b,0x3e483f0e,0xbf0ebe48,0xbf7bbf55,0xbf55bf7b,0xbe48bf0e,0x3f0e3e48,0x3f7b3f55,
0xbf80bf5c,0xbf18bf67,0x3eacbe16,0x3f783f3e,0x3f2c3e79,0x3f7d3f71,0x3edb3f4e,0xbf04bd49,0xbd49bf04,0x3f4e3edb,0x3f713f7d,0x3e793f2c,0x3f3e3f78,0xbe163eac,0xbf67bf18,0xbf5cbf80,
0xbd49bf04,0x3f4e3edb,0x3f713f7d,0x3e793f2c,0x3f3e3f78,0xbe163eac,0xbf67bf18,0xbf5cbf80,0x3f803f5c,0x3f183f67,0xbeac3e16,0xbf78bf3e,0xbf2cbe79,0xbf7dbf71,0xbedbbf4e,0x3f043d49,
0xbf46be95,0xbf62bf7f,0x3dc9bef1,0x3f753f22,0x3f223f75,0xbef13dc9,0xbf7fbf62,0xbe95bf46,0x3f463e95,0x3f623f7f,0xbdc93ef1,0xbf75bf22,0xbf22bf75,0x3ef1bdc9,0x3f7f3f62,0x3e953f46,
0xbf22bf75,0x3ef1bdc9,0x3f7f3f62,0x3e953f46,0xbf46be95,0xbf62bf7f,0x3dc9bef1,0x3f753f22,0x3f223f75,0xbef13dc9,0xbf7fbf62,0xbe95bf46,0x3f463e95,0x3f623f7f,0xbdc93ef1,0xbf75bf22,
0xbf78bf67,0x3d49bf18,0x3f7d3f2c,0x3eac3f5c,0xbf04bf71,0x3f3e3e16,0x3f4e3f80,0xbedb3e79,0x3e79bedb,0x3f803f4e,0x3e163f3e,0xbf71bf04,0x3f5c3eac,0x3f2c3f7d,0xbf183d49,0xbf67bf78,
0x3e79bedb,0x3f803f4e,0x3e163f3e,0xbf71bf04,0x3f5c3eac,0x3f2c3f7d,0xbf183d49,0xbf67bf78,0x3f783f67,0xbd493f18,0xbf7dbf2c,0xbeacbf5c,0x3f043f71,0xbf3ebe16,0xbf4ebf80,0x3edbbe79,
0x3ec43f6d,0xbf6dbec4,0xbec4bf6d,0x3f6d3ec4,0x3ec43f6d,0xbf6dbec4,0xbec4bf6d,0x3f6d3ec4,0x3ec43f6d,0xbf6dbec4,0xbec4bf6d,0x3f6d3ec4,0x3ec43f6d,0xbf6dbec4,0xbec4bf6d,0x3f6d3ec4,
0x3f6d3ec4,0x3ec43f6d,0xbf6dbec4,0xbec4bf6d,0x3f6d3ec4,0x3ec43f6d,0xbf6dbec4,0xbec4bf6d,0x3f6d3ec4,0x3ec43f6d,0xbf6dbec4,0xbec4bf6d,0x3f6d3ec4,0x3ec43f6d,0xbf6dbec4,0xbec4bf6d,
0xbf043eac,0xbf3ebf7d,0x3f4e3d49,0x3edb3f78,0x3e793f67,0xbf80bf18,0x3e16bf2c,0x3f713f5c,0xbf5cbf71,0x3f2cbe16,0x3f183f80,0xbf67be79,0xbf78bedb,0xbd49bf4e,0x3f7d3f3e,0xbeac3f04,
0x3f5c3f71,0xbf2c3e16,0xbf18bf80,0x3f673e79,0x3f783edb,0x3d493f4e,0xbf7dbf3e,0x3eacbf04,0xbf043eac,0xbf3ebf7d,0x3f4e3d49,0x3edb3f78,0x3e793f67,0xbf80bf18,0x3e16bf2c,0x3f713f5c,
0xbdc9bf62,0x3f753f46,0xbf223e95,0xbef1bf7f,0x3f7f3ef1,0xbe953f22,0xbf46bf75,0x3f623dc9,0x3dc93f62,0xbf75bf46,0x3f22be95,0x3ef13f7f,0xbf7fbef1,0x3e95bf22,0x3f463f75,0xbf62bdc9,
0xbf7fbef1,0x3e95bf22,0x3f463f75,0xbf62bdc9,0xbdc9bf62,0x3f753f46,0xbf223e95,0xbef1bf7f,0x3f7f3ef1,0xbe953f22,0xbf46bf75,0x3f623dc9,0x3dc93f62,0xbf75bf46,0x3f22be95,0x3ef13f7f,
0xbf3e3e79,0xbe16bf71,0x3f673f4e,0xbf5c3d49,0x3f803f04,0xbf183edb,0xbeacbf7d,0x3f783f2c,0xbf2cbf78,0x3f7d3eac,0xbedb3f18,0xbf04bf80,0xbd493f5c,0xbf4ebf67,0x3f713e16,0xbe793f3e,
0x3f2c3f78,0xbf7dbeac,0x3edbbf18,0x3f043f80,0x3d49bf5c,0x3f4e3f67,0xbf71be16,0x3e79bf3e,0xbf3e3e79,0xbe16bf71,0x3f673f4e,0xbf5c3d49,0x3f803f04,0xbf183edb,0xbeacbf7d,0x3f783f2c,
0x3f7b3f0e,0xbf553e48,0x3e48bf55,0x3f0e3f7b,0xbf7bbf0e,0x3f55be48,0xbe483f55,0xbf0ebf7b,0x3f7b3f0e,0xbf553e48,0x3e48bf55,0x3f0e3f7b,0xbf7bbf0e,0x3f55be48,0xbe483f55,0xbf0ebf7b,
0xbe483f55,0xbf0ebf7b,0x3f7b3f0e,0xbf553e48,0x3e48bf55,0x3f0e3f7b,0xbf7bbf0e,0x3f55be48,0xbe483f55,0xbf0ebf7b,0x3f7b3f0e,0xbf553e48,0x3e48bf55,0x3f0e3f7b,0xbf7bbf0e,0x3f55be48,
0xbedbbf7d,0x3f5c3f3e,0xbf80be79,0x3f4ebeac,0x3f713f18,0xbf78bd49,0x3f2cbf04,0xbe163f67,0x3f67be16,0xbf043f2c,0xbd49bf78,0x3f183f71,0xbeac3f4e,0xbe79bf80,0x3f3e3f5c,0xbf7dbedb,
0x3f67be16,0xbf043f2c,0xbd49bf78,0x3f183f71,0xbeac3f4e,0xbe79bf80,0x3f3e3f5c,0xbf7dbedb,0x3edb3f7d,0xbf5cbf3e,0x3f803e79,0xbf4e3eac,0xbf71bf18,0x3f783d49,0xbf2c3f04,0x3e16bf67,
0xbf62bf22,0x3f7f3e95,0xbf753dc9,0x3f46bef1,0xbef13f46,0x3dc9bf75,0x3e953f7f,0xbf22bf62,0x3f623f22,0xbf7fbe95,0x3f75bdc9,0xbf463ef1,0x3ef1bf46,0xbdc93f75,0xbe95bf7f,0x3f223f62,
0x3ef1bf46,0xbdc93f75,0xbe95bf7f,0x3f223f62,0xbf62bf22,0x3f7f3e95,0xbf753dc9,0x3f46bef1,0xbef13f46,0x3dc9bf75,0x3e953f7f,0xbf22bf62,0x3f623f22,0xbf7fbe95,0x3f75bdc9,0xbf463ef1,
0xbe16bf80,0x3eac3f78,0xbf04bf67,0x3f2c3f4e,0x3f18bf3e,0xbedb3f5c,0x3e79bf71,0xbd493f7d,0x3f7dbd49,0xbf713e79,0x3f5cbedb,0xbf3e3f18,0x3f4e3f2c,0xbf67bf04,0x3f783eac,0xbf80be16,
0x3f7dbd49,0xbf713e79,0x3f5cbedb,0xbf3e3f18,0x3f4e3f2c,0xbf67bf04,0x3f783eac,0xbf80be16,0x3e163f80,0xbeacbf78,0x3f043f67,0xbf2cbf4e,0xbf183f3e,0x3edbbf5c,0xbe793f71,0x3d49bf7d,
0xbf353f35,0x3f35bf35,0xbf353f35,0x3f35bf35,0xbf353f35,0x3f35bf35,0xbf353f35,0x3f35bf35,0xbf353f35,0x3f35bf35,0xbf353f35,0x3f35bf35,0xbf353f35,0x3f35bf35,0xbf353f35,0x3f35bf35,
0x3f353f35,0xbf35bf35,0x3f353f35,0xbf35bf35,0x3f353f35,0xbf35bf35,0x3f353f35,0xbf35bf35,0x3f353f35,0xbf35bf35,0x3f353f35,0xbf35bf35,0x3f353f35,0xbf35bf35,0x3f353f35,0xbf35bf35,
0xbf7dbd49,0x3f713e79,0xbf5cbedb,0x3f3e3f18,0xbf4e3f2c,0x3f67bf04,0xbf783eac,0x3f80be16,0x3e16bf80,0xbeac3f78,0x3f04bf67,0xbf2c3f4e,0xbf18bf3e,0x3edb3f5c,0xbe79bf71,0x3d493f7d,
0xbe163f80,0x3eacbf78,0xbf043f67,0x3f2cbf4e,0x3f183f3e,0xbedbbf5c,0x3e793f71,0xbd49bf7d,0xbf7dbd49,0x3f713e79,0xbf5cbedb,0x3f3e3f18,0xbf4e3f2c,0x3f67bf04,0xbf783eac,0x3f80be16,
0x3f62bf22,0xbf7f3e95,0x3f753dc9,0xbf46bef1,0x3ef13f46,0xbdc9bf75,0xbe953f7f,0x3f22bf62,0xbf623f22,0x3f7fbe95,0xbf75bdc9,0x3f463ef1,0xbef1bf46,0x3dc93f75,0x3e95bf7f,0xbf223f62,
0xbef1bf46,0x3dc93f75,0x3e95bf7f,0xbf223f62,0x3f62bf22,0xbf7f3e95,0x3f753dc9,0xbf46bef1,0x3ef13f46,0xbdc9bf75,0xbe953f7f,0x3f22bf62,0xbf623f22,0x3f7fbe95,0xbf75bdc9,0x3f463ef1,
0xbf67be16,0x3f043f2c,0x3d49bf78,0xbf183f71,0x3eac3f4e,0x3e79bf80,0xbf3e3f5c,0x3f7dbedb,0x3edbbf7d,0xbf5c3f3e,0x3f80be79,0xbf4ebeac,0xbf713f18,0x3f78bd49,0xbf2cbf04,0x3e163f67,
0xbedb3f7d,0x3f5cbf3e,0xbf803e79,0x3f4e3eac,0x3f71bf18,0xbf783d49,0x3f2c3f04,0xbe16bf67,0xbf67be16,0x3f043f2c,0x3d49bf78,0xbf183f71,0x3eac3f4e,0x3e79bf80,0xbf3e3f5c,0x3f7dbedb,
0x3e483f55,0x3f0ebf7b,0xbf7b3f0e,0x3f553e48,0xbe48bf55,0xbf0e3f7b,0x3f7bbf0e,0xbf55be48,0x3e483f55,0x3f0ebf7b,0xbf7b3f0e,0x3f553e48,0xbe48bf55,0xbf0e3f7b,0x3f7bbf0e,0xbf55be48,
0xbf7b3f0e,0x3f553e48,0xbe48bf55,0xbf0e3f7b,0x3f7bbf0e,0xbf55be48,0x3e483f55,0x3f0ebf7b,0xbf7b3f0e,0x3f553e48,0xbe48bf55,0xbf0e3f7b,0x3f7bbf0e,0xbf55be48,0x3e483f55,0x3f0ebf7b,
0x3f2cbf78,0xbf7d3eac,0x3edb3f18,0x3f04bf80,0x3d493f5c,0x3f4ebf67,0xbf713e16,0x3e793f3e,0x3f3e3e79,0x3e16bf71,0xbf673f4e,0x3f5c3d49,0xbf803f04,0x3f183edb,0x3eacbf7d,0xbf783f2c,
0x3f3e3e79,0x3e16bf71,0xbf673f4e,0x3f5c3d49,0xbf803f04,0x3f183edb,0x3eacbf7d,0xbf783f2c,0xbf2c3f78,0x3f7dbeac,0xbedbbf18,0xbf043f80,0xbd49bf5c,0xbf4e3f67,0x3f71be16,0xbe79bf3e,
0x3dc9bf62,0xbf753f46,0x3f223e95,0x3ef1bf7f,0xbf7f3ef1,0x3e953f22,0x3f46bf75,0xbf623dc9,0xbdc93f62,0x3f75bf46,0xbf22be95,0xbef13f7f,0x3f7fbef1,0xbe95bf22,0xbf463f75,0x3f62bdc9,
0x3f7fbef1,0xbe95bf22,0xbf463f75,0x3f62bdc9,0x3dc9bf62,0xbf753f46,0x3f223e95,0x3ef1bf7f,0xbf7f3ef1,0x3e953f22,0x3f46bf75,0xbf623dc9,0xbdc93f62,0x3f75bf46,0xbf22be95,0xbef13f7f,
0x3f5cbf71,0xbf2cbe16,0xbf183f80,0x3f67be79,0x3f78bedb,0x3d49bf4e,0xbf7d3f3e,0x3eac3f04,0x3f043eac,0x3f3ebf7d,0xbf4e3d49,0xbedb3f78,0xbe793f67,0x3f80bf18,0xbe16bf2c,0xbf713f5c,
0x3f043eac,0x3f3ebf7d,0xbf4e3d49,0xbedb3f78,0xbe793f67,0x3f80bf18,0xbe16bf2c,0xbf713f5c,0xbf5c3f71,0x3f2c3e16,0x3f18bf80,0xbf673e79,0xbf783edb,0xbd493f4e,0x3f7dbf3e,0xbeacbf04,
0xbf6d3ec4,0xbec43f6d,0x3f6dbec4,0x3ec4bf6d,0xbf6d3ec4,0xbec43f6d,0x3f6dbec4,0x3ec4bf6d,0xbf6d3ec4,0xbec43f6d,0x3f6dbec4,0x3ec4bf6d,0xbf6d3ec4,0xbec43f6d,0x3f6dbec4,0x3ec4bf6d,
0xbec43f6d,0x3f6dbec4,0x3ec4bf6d,0xbf6d3ec4,0xbec43f6d,0x3f6dbec4,0x3ec4bf6d,0xbf6d3ec4,0xbec43f6d,0x3f6dbec4,0x3ec4bf6d,0xbf6d3ec4,0xbec43f6d,0x3f6dbec4,0x3ec4bf6d,0xbf6d3ec4,
0xbe79bedb,0xbf803f4e,0xbe163f3e,0x3f71bf04,0xbf5c3eac,0xbf2c3f7d,0x3f183d49,0x3f67bf78,0x3f78bf67,0xbd49bf18,0xbf7d3f2c,0xbeac3f5c,0x3f04bf71,0xbf3e3e16,0xbf4e3f80,0x3edb3e79,
0xbf783f67,0x3d493f18,0x3f7dbf2c,0x3eacbf5c,0xbf043f71,0x3f3ebe16,0x3f4ebf80,0xbedbbe79,0xbe79bedb,0xbf803f4e,0xbe163f3e,0x3f71bf04,0xbf5c3eac,0xbf2c3f7d,0x3f183d49,0x3f67bf78,
0x3f46be95,0x3f62bf7f,0xbdc9bef1,0xbf753f22,0xbf223f75,0x3ef13dc9,0x3f7fbf62,0x3e95bf46,0xbf463e95,0xbf623f7f,0x3dc93ef1,0x3f75bf22,0x3f22bf75,0xbef1bdc9,0xbf7f3f62,0xbe953f46,
0x3f22bf75,0xbef1bdc9,0xbf7f3f62,0xbe953f46,0x3f46be95,0x3f62bf7f,0xbdc9bef1,0xbf753f22,0xbf223f75,0x3ef13dc9,0x3f7fbf62,0x3e95bf46,0xbf463e95,0xbf623f7f,0x3dc93ef1,0x3f75bf22,
0x3d49bf04,0xbf4e3edb,0xbf713f7d,0xbe793f2c,0xbf3e3f78,0x3e163eac,0x3f67bf18,0x3f5cbf80,0x3f80bf5c,0x3f18bf67,0xbeacbe16,0xbf783f3e,0xbf2c3e79,0xbf7d3f71,0xbedb3f4e,0x3f04bd49,
0xbf803f5c,0xbf183f67,0x3eac3e16,0x3f78bf3e,0x3f2cbe79,0x3f7dbf71,0x3edbbf4e,0xbf043d49,0x3d49bf04,0xbf4e3edb,0xbf713f7d,0xbe793f2c,0xbf3e3f78,0x3e163eac,0x3f67bf18,0x3f5cbf80,
0xbf553f7b,0xbe483f0e,0x3f0ebe48,0x3f7bbf55,0x3f55bf7b,0x3e48bf0e,0xbf0e3e48,0xbf7b3f55,0xbf553f7b,0xbe483f0e,0x3f0ebe48,0x3f7bbf55,0x3f55bf7b,0x3e48bf0e,0xbf0e3e48,0xbf7b3f55,
0xbf0e3e48,0xbf7b3f55,0xbf553f7b,0xbe483f0e,0x3f0ebe48,0x3f7bbf55,0x3f55bf7b,0x3e48bf0e,0xbf0e3e48,0xbf7b3f55,0xbf553f7b,0xbe483f0e,0x3f0ebe48,0x3f7bbf55,0x3f55bf7b,0x3e48bf0e,
0x3f71bf4e,0x3f78bf80,0x3f2cbf5c,0x3e16bedb,0xbf673f7d,0xbf043f3e,0x3d493e79,0x3f18beac,0xbeac3f18,0x3e793d49,0x3f3ebf04,0x3f7dbf67,0xbedb3e16,0xbf5c3f2c,0xbf803f78,0xbf4e3f71,
0xbeac3f18,0x3e793d49,0x3f3ebf04,0x3f7dbf67,0xbedb3e16,0xbf5c3f2c,0xbf803f78,0xbf4e3f71,0xbf713f4e,0xbf783f80,0xbf2c3f5c,0xbe163edb,0x3f67bf7d,0x3f04bf3e,0xbd49be79,0xbf183eac,
0x3f75bf7f,0x3f46bf62,0x3ef1bf22,0x3dc9be95,0xbe953dc9,0xbf223ef1,0xbf623f46,0xbf7f3f75,0xbf753f7f,0xbf463f62,0xbef13f22,0xbdc93e95,0x3e95bdc9,0x3f22bef1,0x3f62bf46,0x3f7fbf75,
0x3e95bdc9,0x3f22bef1,0x3f62bf46,0x3f7fbf75,0x3f75bf7f,0x3f46bf62,0x3ef1bf22,0x3dc9be95,0xbe953dc9,0xbf223ef1,0xbf623f46,0xbf7f3f75,0xbf753f7f,0xbf463f62,0xbef13f22,0xbdc93e95,
0x3f4ebf3e,0x3f67bf5c,0x3f78bf71,0x3f80bf7d,0x3e16bd49,0x3eacbe79,0x3f04bedb,0x3f2cbf18,0xbf183f2c,0xbedb3f04,0xbe793eac,0xbd493e16,0xbf7d3f80,0xbf713f78,0xbf5c3f67,0xbf3e3f4e,
0xbf183f2c,0xbedb3f04,0xbe793eac,0xbd493e16,0xbf7d3f80,0xbf713f78,0xbf5c3f67,0xbf3e3f4e,0xbf4e3f3e,0xbf673f5c,0xbf783f71,0xbf803f7d,0xbe163d49,0xbeac3e79,0xbf043edb,0xbf2c3f18,
0xa554248d,0xa5f725b0,0xa731261f,0xa742a68d,0xa754a654,0xa765a60d,0xa777a58e,0xa784a137,0xa78d258d,0xa796260d,0xa79f280d,0x2731268d,0xa7b12816,0x270d26d4,0xa7c2281f,0x26d4270d,
0xbf803f80,0xbf803f80,0xbf803f80,0xbf803f80,0xbf803f80,0xbf803f80,0xbf803f80,0xbf803f80,0xbf803f80,0xbf803f80,0xbf803f80,0xbf803f80,0xbf803f80,0xbf803f80,0xbf803f80,0xbf803f80,
0x3f4ebf3e,0x3f67bf5c,0x3f78bf71,0x3f80bf7d,0x3e16bd49,0x3eacbe79,0x3f04bedb,0x3f2cbf18,0x3f18bf2c,0x3edbbf04,0x3e79beac,0x3d49be16,0x3f7dbf80,0x3f71bf78,0x3f5cbf67,0x3f3ebf4e,
0xbf183f2c,0xbedb3f04,0xbe793eac,0xbd493e16,0xbf7d3f80,0xbf713f78,0xbf5c3f67,0xbf3e3f4e,0x3f4ebf3e,0x3f67bf5c,0x3f78bf71,0x3f80bf7d,0x3e16bd49,0x3eacbe79,0x3f04bedb,0x3f2cbf18,
0xbe953dc9,0xbf223ef1,0xbf623f46,0xbf7f3f75,0xbf753f7f,0xbf463f62,0xbef13f22,0xbdc93e95,0x3e95bdc9,0x3f22bef1,0x3f62bf46,0x3f7fbf75,0x3f75bf7f,0x3f46bf62,0x3ef1bf22,0x3dc9be95,
0x3f75bf7f,0x3f46bf62,0x3ef1bf22,0x3dc9be95,0xbe953dc9,0xbf223ef1,0xbf623f46,0xbf7f3f75,0xbf753f7f,0xbf463f62,0xbef13f22,0xbdc93e95,0x3e95bdc9,0x3f22bef1,0x3f62bf46,0x3f7fbf75,
0x3f71bf4e,0x3f78bf80,0x3f2cbf5c,0x3e16bedb,0xbf673f7d,0xbf043f3e,0x3d493e79,0x3f18beac,0x3eacbf18,0xbe79bd49,0xbf3e3f04,0xbf7d3f67,0x3edbbe16,0x3f5cbf2c,0x3f80bf78,0x3f4ebf71,
0xbeac3f18,0x3e793d49,0x3f3ebf04,0x3f7dbf67,0xbedb3e16,0xbf5c3f2c,0xbf803f78,0xbf4e3f71,0x3f71bf4e,0x3f78bf80,0x3f2cbf5c,0x3e16bedb,0xbf673f7d,0xbf043f3e,0x3d493e79,0x3f18beac,
0xbf553f7b,0xbe483f0e,0x3f0ebe48,0x3f7bbf55,0x3f55bf7b,0x3e48bf0e,0xbf0e3e48,0xbf7b3f55,0xbf553f7b,0xbe483f0e,0x3f0ebe48,0x3f7bbf55,0x3f55bf7b,0x3e48bf0e,0xbf0e3e48,0xbf7b3f55,
0x3f0ebe48,0x3f7bbf55,0x3f55bf7b,0x3e48bf0e,0xbf0e3e48,0xbf7b3f55,0xbf553f7b,0xbe483f0e,0x3f0ebe48,0x3f7bbf55,0x3f55bf7b,0x3e48bf0e,0xbf0e3e48,0xbf7b3f55,0xbf553f7b,0xbe483f0e,
0x3d49bf04,0xbf4e3edb,0xbf713f7d,0xbe793f2c,0xbf3e3f78,0x3e163eac,0x3f67bf18,0x3f5cbf80,0xbf803f5c,0xbf183f67,0x3eac3e16,0x3f78bf3e,0x3f2cbe79,0x3f7dbf71,0x3edbbf4e,0xbf043d49,
0xbf803f5c,0xbf183f67,0x3eac3e16,0x3f78bf3e,0x3f2cbe79,0x3f7dbf71,0x3edbbf4e,0xbf043d49,0xbd493f04,0x3f4ebedb,0x3f71bf7d,0x3e79bf2c,0x3f3ebf78,0xbe16beac,0xbf673f18,0xbf5c3f80,
0x3f22bf75,0xbef1bdc9,0xbf7f3f62,0xbe953f46,0x3f46be95,0x3f62bf7f,0xbdc9bef1,0xbf753f22,0xbf223f75,0x3ef13dc9,0x3f7fbf62,0x3e95bf46,0xbf463e95,0xbf623f7f,0x3dc93ef1,0x3f75bf22,
0xbf463e95,0xbf623f7f,0x3dc93ef1,0x3f75bf22,0x3f22bf75,0xbef1bdc9,0xbf7f3f62,0xbe953f46,0x3f46be95,0x3f62bf7f,0xbdc9bef1,0xbf753f22,0xbf223f75,0x3ef13dc9,0x3f7fbf62,0x3e95bf46,
0xbe79bedb,0xbf803f4e,0xbe163f3e,0x3f71bf04,0xbf5c3eac,0xbf2c3f7d,0x3f183d49,0x3f67bf78,0xbf783f67,0x3d493f18,0x3f7dbf2c,0x3eacbf5c,0xbf043f71,0x3f3ebe16,0x3f4ebf80,0xbedbbe79,
0xbf783f67,0x3d493f18,0x3f7dbf2c,0x3eacbf5c,0xbf043f71,0x3f3ebe16,0x3f4ebf80,0xbedbbe79,0x3e793edb,0x3f80bf4e,0x3e16bf3e,0xbf713f04,0x3f5cbeac,0x3f2cbf7d,0xbf18bd49,0xbf673f78,
0x3f6dbec4,0x3ec4bf6d,0xbf6d3ec4,0xbec43f6d,0x3f6dbec4,0x3ec4bf6d,0xbf6d3ec4,0xbec43f6d,0x3f6dbec4,0x3ec4bf6d,0xbf6d3ec4,0xbec43f6d,0x3f6dbec4,0x3ec4bf6d,0xbf6d3ec4,0xbec43f6d,
0xbec43f6d,0x3f6dbec4,0x3ec4bf6d,0xbf6d3ec4,0xbec43f6d,0x3f6dbec4,0x3ec4bf6d,0xbf6d3ec4,0xbec43f6d,0x3f6dbec4,0x3ec4bf6d,0xbf6d3ec4,0xbec43f6d,0x3f6dbec4,0x3ec4bf6d,0xbf6d3ec4,
0x3f5cbf71,0xbf2cbe16,0xbf183f80,0x3f67be79,0x3f78bedb,0x3d49bf4e,0xbf7d3f3e,0x3eac3f04,0xbf04beac,0xbf3e3f7d,0x3f4ebd49,0x3edbbf78,0x3e79bf67,0xbf803f18,0x3e163f2c,0x3f71bf5c,
0x3f043eac,0x3f3ebf7d,0xbf4e3d49,0xbedb3f78,0xbe793f67,0x3f80bf18,0xbe16bf2c,0xbf713f5c,0x3f5cbf71,0xbf2cbe16,0xbf183f80,0x3f67be79,0x3f78bedb,0x3d49bf4e,0xbf7d3f3e,0x3eac3f04,
0xbf7f3ef1,0x3e953f22,0x3f46bf75,0xbf623dc9,0xbdc93f62,0x3f75bf46,0xbf22be95,0xbef13f7f,0x3f7fbef1,0xbe95bf22,0xbf463f75,0x3f62bdc9,0x3dc9bf62,0xbf753f46,0x3f223e95,0x3ef1bf7f,
0x3dc9bf62,0xbf753f46,0x3f223e95,0x3ef1bf7f,0xbf7f3ef1,0x3e953f22,0x3f46bf75,0xbf623dc9,0xbdc93f62,0x3f75bf46,0xbf22be95,0xbef13f7f,0x3f7fbef1,0xbe95bf22,0xbf463f75,0x3f62bdc9,
0x3f2cbf78,0xbf7d3eac,0x3edb3f18,0x3f04bf80,0x3d493f5c,0x3f4ebf67,0xbf713e16,0x3e793f3e,0xbf3ebe79,0xbe163f71,0x3f67bf4e,0xbf5cbd49,0x3f80bf04,0xbf18bedb,0xbeac3f7d,0x3f78bf2c,
0x3f3e3e79,0x3e16bf71,0xbf673f4e,0x3f5c3d49,0xbf803f04,0x3f183edb,0x3eacbf7d,0xbf783f2c,0x3f2cbf78,0xbf7d3eac,0x3edb3f18,0x3f04bf80,0x3d493f5c,0x3f4ebf67,0xbf713e16,0x3e793f3e,
0x3e483f55,0x3f0ebf7b,0xbf7b3f0e,0x3f553e48,0xbe48bf55,0xbf0e3f7b,0x3f7bbf0e,0xbf55be48,0x3e483f55,0x3f0ebf7b,0xbf7b3f0e,0x3f553e48,0xbe48bf55,0xbf0e3f7b,0x3f7bbf0e,0xbf55be48,
0x3f7bbf0e,0xbf55be48,0x3e483f55,0x3f0ebf7b,0xbf7b3f0e,0x3f553e48,0xbe48bf55,0xbf0e3f7b,0x3f7bbf0e,0xbf55be48,0x3e483f55,0x3f0ebf7b,0xbf7b3f0e,0x3f553e48,0xbe48bf55,0xbf0e3f7b,
0xbf67be16,0x3f043f2c,0x3d49bf78,0xbf183f71,0x3eac3f4e,0x3e79bf80,0xbf3e3f5c,0x3f7dbedb,0xbedb3f7d,0x3f5cbf3e,0xbf803e79,0x3f4e3eac,0x3f71bf18,0xbf783d49,0x3f2c3f04,0xbe16bf67,
0xbedb3f7d,0x3f5cbf3e,0xbf803e79,0x3f4e3eac,0x3f71bf18,0xbf783d49,0x3f2c3f04,0xbe16bf67,0x3f673e16,0xbf04bf2c,0xbd493f78,0x3f18bf71,0xbeacbf4e,0xbe793f80,0x3f3ebf5c,0xbf7d3edb,
0xbef1bf46,0x3dc93f75,0x3e95bf7f,0xbf223f62,0x3f62bf22,0xbf7f3e95,0x3f753dc9,0xbf46bef1,0x3ef13f46,0xbdc9bf75,0xbe953f7f,0x3f22bf62,0xbf623f22,0x3f7fbe95,0xbf75bdc9,0x3f463ef1,
0xbf623f22,0x3f7fbe95,0xbf75bdc9,0x3f463ef1,0xbef1bf46,0x3dc93f75,0x3e95bf7f,0xbf223f62,0x3f62bf22,0xbf7f3e95,0x3f753dc9,0xbf46bef1,0x3ef13f46,0xbdc9bf75,0xbe953f7f,0x3f22bf62,
0xbf7dbd49,0x3f713e79,0xbf5cbedb,0x3f3e3f18,0xbf4e3f2c,0x3f67bf04,0xbf783eac,0x3f80be16,0xbe163f80,0x3eacbf78,0xbf043f67,0x3f2cbf4e,0x3f183f3e,0xbedbbf5c,0x3e793f71,0xbd49bf7d,
0xbe163f80,0x3eacbf78,0xbf043f67,0x3f2cbf4e,0x3f183f3e,0xbedbbf5c,0x3e793f71,0xbd49bf7d,0x3f7d3d49,0xbf71be79,0x3f5c3edb,0xbf3ebf18,0x3f4ebf2c,0xbf673f04,0x3f78beac,0xbf803e16,
0x3f35bf35,0xbf353f35,0x3f35bf35,0xbf353f35,0x3f35bf35,0xbf353f35,0x3f35bf35,0xbf353f35,0x3f35bf35,0xbf353f35,0x3f35bf35,0xbf353f35,0x3f35bf35,0xbf353f35,0x3f35bf35,0xbf353f35,
0x3f353f35,0xbf35bf35,0x3f353f35,0xbf35bf35,0x3f353f35,0xbf35bf35,0x3f353f35,0xbf35bf35,0x3f353f35,0xbf35bf35,0x3f353f35,0xbf35bf35,0x3f353f35,0xbf35bf35,0x3f353f35,0xbf35bf35,
0xbe16bf80,0x3eac3f78,0xbf04bf67,0x3f2c3f4e,0x3f18bf3e,0xbedb3f5c,0x3e79bf71,0xbd493f7d,0xbf7d3d49,0x3f71be79,0xbf5c3edb,0x3f3ebf18,0xbf4ebf2c,0x3f673f04,0xbf78beac,0x3f803e16,
0x3f7dbd49,0xbf713e79,0x3f5cbedb,0xbf3e3f18,0x3f4e3f2c,0xbf67bf04,0x3f783eac,0xbf80be16,0xbe16bf80,0x3eac3f78,0xbf04bf67,0x3f2c3f4e,0x3f18bf3e,0xbedb3f5c,0x3e79bf71,0xbd493f7d,
0xbef13f46,0x3dc9bf75,0x3e953f7f,0xbf22bf62,0x3f623f22,0xbf7fbe95,0x3f75bdc9,0xbf463ef1,0x3ef1bf46,0xbdc93f75,0xbe95bf7f,0x3f223f62,0xbf62bf22,0x3f7f3e95,0xbf753dc9,0x3f46bef1,
0xbf62bf22,0x3f7f3e95,0xbf753dc9,0x3f46bef1,0xbef13f46,0x3dc9bf75,0x3e953f7f,0xbf22bf62,0x3f623f22,0xbf7fbe95,0x3f75bdc9,0xbf463ef1,0x3ef1bf46,0xbdc93f75,0xbe95bf7f,0x3f223f62,
0xbedbbf7d,0x3f5c3f3e,0xbf80be79,0x3f4ebeac,0x3f713f18,0xbf78bd49,0x3f2cbf04,0xbe163f67,0xbf673e16,0x3f04bf2c,0x3d493f78,0xbf18bf71,0x3eacbf4e,0x3e793f80,0xbf3ebf5c,0x3f7d3edb,
0x3f67be16,0xbf043f2c,0xbd49bf78,0x3f183f71,0xbeac3f4e,0xbe79bf80,0x3f3e3f5c,0xbf7dbedb,0xbedbbf7d,0x3f5c3f3e,0xbf80be79,0x3f4ebeac,0x3f713f18,0xbf78bd49,0x3f2cbf04,0xbe163f67,
0x3f7b3f0e,0xbf553e48,0x3e48bf55,0x3f0e3f7b,0xbf7bbf0e,0x3f55be48,0xbe483f55,0xbf0ebf7b,0x3f7b3f0e,0xbf553e48,0x3e48bf55,0x3f0e3f7b,0xbf7bbf0e,0x3f55be48,0xbe483f55,0xbf0ebf7b,
0x3e48bf55,0x3f0e3f7b,0xbf7bbf0e,0x3f55be48,0xbe483f55,0xbf0ebf7b,0x3f7b3f0e,0xbf553e48,0x3e48bf55,0x3f0e3f7b,0xbf7bbf0e,0x3f55be48,0xbe483f55,0xbf0ebf7b,0x3f7b3f0e,0xbf553e48,
0xbf3e3e79,0xbe16bf71,0x3f673f4e,0xbf5c3d49,0x3f803f04,0xbf183edb,0xbeacbf7d,0x3f783f2c,0x3f2c3f78,0xbf7dbeac,0x3edbbf18,0x3f043f80,0x3d49bf5c,0x3f4e3f67,0xbf71be16,0x3e79bf3e,
0x3f2c3f78,0xbf7dbeac,0x3edbbf18,0x3f043f80,0x3d49bf5c,0x3f4e3f67,0xbf71be16,0x3e79bf3e,0x3f3ebe79,0x3e163f71,0xbf67bf4e,0x3f5cbd49,0xbf80bf04,0x3f18bedb,0x3eac3f7d,0xbf78bf2c,
0xbf7fbef1,0x3e95bf22,0x3f463f75,0xbf62bdc9,0xbdc9bf62,0x3f753f46,0xbf223e95,0xbef1bf7f,0x3f7f3ef1,0xbe953f22,0xbf46bf75,0x3f623dc9,0x3dc93f62,0xbf75bf46,0x3f22be95,0x3ef13f7f,
0x3dc93f62,0xbf75bf46,0x3f22be95,0x3ef13f7f,0xbf7fbef1,0x3e95bf22,0x3f463f75,0xbf62bdc9,0xbdc9bf62,0x3f753f46,0xbf223e95,0xbef1bf7f,0x3f7f3ef1,0xbe953f22,0xbf46bf75,0x3f623dc9,
0xbf043eac,0xbf3ebf7d,0x3f4e3d49,0x3edb3f78,0x3e793f67,0xbf80bf18,0x3e16bf2c,0x3f713f5c,0x3f5c3f71,0xbf2c3e16,0xbf18bf80,0x3f673e79,0x3f783edb,0x3d493f4e,0xbf7dbf3e,0x3eacbf04,
0x3f5c3f71,0xbf2c3e16,0xbf18bf80,0x3f673e79,0x3f783edb,0x3d493f4e,0xbf7dbf3e,0x3eacbf04,0x3f04beac,0x3f3e3f7d,0xbf4ebd49,0xbedbbf78,0xbe79bf67,0x3f803f18,0xbe163f2c,0xbf71bf5c,
0xbec4bf6d,0x3f6d3ec4,0x3ec43f6d,0xbf6dbec4,0xbec4bf6d,0x3f6d3ec4,0x3ec43f6d,0xbf6dbec4,0xbec4bf6d,0x3f6d3ec4,0x3ec43f6d,0xbf6dbec4,0xbec4bf6d,0x3f6d3ec4,0x3ec43f6d,0xbf6dbec4,
0x3f6d3ec4,0x3ec43f6d,0xbf6dbec4,0xbec4bf6d,0x3f6d3ec4,0x3ec43f6d,0xbf6dbec4,0xbec4bf6d,0x3f6d3ec4,0x3ec43f6d,0xbf6dbec4,0xbec4bf6d,0x3f6d3ec4,0x3ec43f6d,0xbf6dbec4,0xbec4bf6d,
0xbf78bf67,0x3d49bf18,0x3f7d3f2c,0x3eac3f5c,0xbf04bf71,0x3f3e3e16,0x3f4e3f80,0xbedb3e79,0xbe793edb,0xbf80bf4e,0xbe16bf3e,0x3f713f04,0xbf5cbeac,0xbf2cbf7d,0x3f18bd49,0x3f673f78,
0x3e79bedb,0x3f803f4e,0x3e163f3e,0xbf71bf04,0x3f5c3eac,0x3f2c3f7d,0xbf183d49,0xbf67bf78,0xbf78bf67,0x3d49bf18,0x3f7d3f2c,0x3eac3f5c,0xbf04bf71,0x3f3e3e16,0x3f4e3f80,0xbedb3e79,
0x3f223f75,0xbef13dc9,0xbf7fbf62,0xbe95bf46,0x3f463e95,0x3f623f7f,0xbdc93ef1,0xbf75bf22,0xbf22bf75,0x3ef1bdc9,0x3f7f3f62,0x3e953f46,0xbf46be95,0xbf62bf7f,0x3dc9bef1,0x3f753f22,
0xbf46be95,0xbf62bf7f,0x3dc9bef1,0x3f753f22,0x3f223f75,0xbef13dc9,0xbf7fbf62,0xbe95bf46,0x3f463e95,0x3f623f7f,0xbdc93ef1,0xbf75bf22,0xbf22bf75,0x3ef1bdc9,0x3f7f3f62,0x3e953f46,
0xbf80bf5c,0xbf18bf67,0x3eacbe16,0x3f783f3e,0x3f2c3e79,0x3f7d3f71,0x3edb3f4e,0xbf04bd49,0x3d493f04,0xbf4ebedb,0xbf71bf7d,0xbe79bf2c,0xbf3ebf78,0x3e16beac,0x3f673f18,0x3f5c3f80,
0xbd49bf04,0x3f4e3edb,0x3f713f7d,0x3e793f2c,0x3f3e3f78,0xbe163eac,0xbf67bf18,0xbf5cbf80,0xbf80bf5c,0xbf18bf67,0x3eacbe16,0x3f783f3e,0x3f2c3e79,0x3f7d3f71,0x3edb3f4e,0xbf04bd49,
0x3f0e3e48,0x3f7b3f55,0x3f553f7b,0x3e483f0e,0xbf0ebe48,0xbf7bbf55,0xbf55bf7b,0xbe48bf0e,0x3f0e3e48,0x3f7b3f55,0x3f553f7b,0x3e483f0e,0xbf0ebe48,0xbf7bbf55,0xbf55bf7b,0xbe48bf0e,
0xbf55bf7b,0xbe48bf0e,0x3f0e3e48,0x3f7b3f55,0x3f553f7b,0x3e483f0e,0xbf0ebe48,0xbf7bbf55,0xbf55bf7b,0xbe48bf0e,0x3f0e3e48,0x3f7b3f55,0x3f553f7b,0x3e483f0e,0xbf0ebe48,0xbf7bbf55,
0x3eac3f18,0xbe793d49,0xbf3ebf04,0xbf7dbf67,0x3edb3e16,0x3f5c3f2c,0x3f803f78,0x3f4e3f71,0x3f713f4e,0x3f783f80,0x3f2c3f5c,0x3e163edb,0xbf67bf7d,0xbf04bf3e,0x3d49be79,0x3f183eac,
0x3f713f4e,0x3f783f80,0x3f2c3f5c,0x3e163edb,0xbf67bf7d,0xbf04bf3e,0x3d49be79,0x3f183eac,0xbeacbf18,0x3e79bd49,0x3f3e3f04,0x3f7d3f67,0xbedbbe16,0xbf5cbf2c,0xbf80bf78,0xbf4ebf71,
0xbe95bdc9,0xbf22bef1,0xbf62bf46,0xbf7fbf75,0xbf75bf7f,0xbf46bf62,0xbef1bf22,0xbdc9be95,0x3e953dc9,0x3f223ef1,0x3f623f46,0x3f7f3f75,0x3f753f7f,0x3f463f62,0x3ef13f22,0x3dc93e95,
0x3f753f7f,0x3f463f62,0x3ef13f22,0x3dc93e95,0xbe95bdc9,0xbf22bef1,0xbf62bf46,0xbf7fbf75,0xbf75bf7f,0xbf46bf62,0xbef1bf22,0xbdc9be95,0x3e953dc9,0x3f223ef1,0x3f623f46,0x3f7f3f75,
0x3f183f2c,0x3edb3f04,0x3e793eac,0x3d493e16,0x3f7d3f80,0x3f713f78,0x3f5c3f67,0x3f3e3f4e,0x3f4e3f3e,0x3f673f5c,0x3f783f71,0x3f803f7d,0x3e163d49,0x3eac3e79,0x3f043edb,0x3f2c3f18,
0x3f4e3f3e,0x3f673f5c,0x3f783f71,0x3f803f7d,0x3e163d49,0x3eac3e79,0x3f043edb,0x3f2c3f18,0xbf18bf2c,0xbedbbf04,0xbe79beac,0xbd49be16,0xbf7dbf80,0xbf71bf78,0xbf5cbf67,0xbf3ebf4e,
0x38fb37c9,0x39a13960,0x39fc39cf,0x3a273a13,0xba7eba80,0xba73ba7a,0xba5fba6a,0xba42ba51,0x3a4a3a39,0x3a653a58,0x3a773a6f,0x3a7f3a7c,0xba1dba31,0xb9e6ba09,0xb989b9b8,0xb897b92f,
0x3a7e3a80,0x3a733a7a,0x3a5f3a6a,0x3a423a51,0x38fb37c9,0x39a13960,0x39fc39cf,0x3a273a13,0x3a1d3a31,0x39e63a09,0x398939b8,0x3897392f,0x3a4a3a39,0x3a653a58,0x3a773a6f,0x3a7f3a7c,
0xba6fba7f,0xba13ba4a,0xb7c9b9a1,0x3a093989,0x39b83897,0x3a513a1d,0x3a803a73,0x3a583a77,0x3a6a3a42,0x3a7c3a7e,0x3a393a65,0x396039fc,0x39cf3a27,0xb92f38fb,0xba31b9e6,0xba7aba5f,
0xb9b8b897,0xba51ba1d,0xba80ba73,0xba58ba77,0xba6fba7f,0xba13ba4a,0xb7c9b9a1,0x3a093989,0xb9cfba27,0x392fb8fb,0x3a3139e6,0x3a7a3a5f,0x3a6a3a42,0x3a7c3a7e,0x3a393a65,0x396039fc,
0xba7cba4a,0xba31ba73,0x3960b989,0x3a6f3a27,0x392f3a1d,0xba39b9a1,0xba7aba77,0xb9b8ba42,0x3a1338fb,0x3a803a65,0x3a093a5f,0xb9cf3897,0xba51ba7e,0x37c9b9e6,0x3a5839fc,0x3a6a3a7f,
0xb92fba1d,0x3a3939a1,0x3a7a3a77,0x39b83a42,0xba7cba4a,0xba31ba73,0x3960b989,0x3a6f3a27,0x3a513a7e,0xb7c939e6,0xba58b9fc,0xba6aba7f,0x3a1338fb,0x3a803a65,0x3a093a5f,0xb9cf3897,
0xba7fba51,0xb8fbba39,0x3a733a09,0x39fc3a6f,0x3897ba13,0x3a7e3a31,0x39a13a58,0xba5fb9b8,0xba27ba7c,0x3a1db7c9,0x3a653a7a,0xb98939cf,0x3a42392f,0x3a4a3a80,0xb9e63960,0xba77ba6a,
0xb8973a13,0xba7eba31,0xb9a1ba58,0x3a5f39b8,0xba7fba51,0xb8fbba39,0x3a733a09,0x39fc3a6f,0xba42b92f,0xba4aba80,0x39e6b960,0x3a773a6a,0xba27ba7c,0x3a1db7c9,0x3a653a7a,0xb98939cf,
0x39e63a7a,0xba77b9cf,0xb897ba51,0x3a7e3a39,0x3a653960,0x39893a6a,0xba7fba13,0x38fbba31,0xb9a13a09,0xba5fba6f,0x3a27b92f,0x3a1d3a80,0x3a733a58,0xb9fc39b8,0xba42ba7c,0x3a4a37c9,
0x3a653960,0x39893a6a,0xba7fba13,0x38fbba31,0xb9e6ba7a,0x3a7739cf,0x38973a51,0xba7eba39,0x3a733a58,0xb9fc39b8,0xba42ba7c,0x3a4a37c9,0x39a1ba09,0x3a5f3a6f,0xba27392f,0xba1dba80,
0xba7ab989,0x39b8ba27,0x3a133a7e,0xba80b9e6,0xb960ba77,0x3a6f3a42,0xba5138fb,0xb7c9ba65,0x3a09b9fc,0x39cf3a7f,0xba7cba1d,0x3a31b9a1,0x3a583a5f,0xba6ab897,0x392fba4a,0x3a393a73,
0xb960ba77,0x3a6f3a42,0xba5138fb,0xb7c9ba65,0x3a7a3989,0xb9b83a27,0xba13ba7e,0x3a8039e6,0x3a583a5f,0xba6ab897,0x392fba4a,0x3a393a73,0xba0939fc,0xb9cfba7f,0x3a7c3a1d,0xba3139a1,
0x3a39b9e6,0xb9603a5f,0xb9b8ba7f,0x3a513a4a,0xba31ba65,0x3a7a39fc,0xba6f3897,0x3a13ba1d,0xb7c93a73,0xba09ba77,0x3a6a3a27,0xba7cb8fb,0x3a8039a1,0xba583989,0x39cfba42,0x392f3a7e,
0xba31ba65,0x3a7a39fc,0xba6f3897,0x3a13ba1d,0xba3939e6,0x3960ba5f,0x39b83a7f,0xba51ba4a,0x3a8039a1,0xba583989,0x39cfba42,0x392f3a7e,0x37c9ba73,0x3a093a77,0xba6aba27,0x3a7c38fb,
0xba5f39cf,0x3a42ba13,0xba1d3a39,0x39e6ba58,0xb9fcba6a,0x3a273a51,0xba4aba31,0x3a653a09,0xba77b9b8,0x3a7f392f,0xba7e37c9,0x3a73b960,0x3989ba6f,0xb8973a7c,0xb8fbba80,0x39a13a7a,
0xb9fcba6a,0x3a273a51,0xba4aba31,0x3a653a09,0x3a5fb9cf,0xba423a13,0x3a1dba39,0xb9e63a58,0x3989ba6f,0xb8973a7c,0xb8fbba80,0x39a13a7a,0x3a7739b8,0xba7fb92f,0x3a7eb7c9,0xba733960,
0x3a5f39cf,0xba42ba13,0x3a1d3a39,0xb9e6ba58,0x39fcba6a,0xba273a51,0x3a4aba31,0xba653a09,0x39893a6f,0xb897ba7c,0xb8fb3a80,0x39a1ba7a,0x3a77b9b8,0xba7f392f,0x3a7e37c9,0xba73b960,
0xb9fc3a6a,0x3a27ba51,0xba4a3a31,0x3a65ba09,0x3a5f39cf,0xba42ba13,0x3a1d3a39,0xb9e6ba58,0xba7739b8,0x3a7fb92f,0xba7eb7c9,0x3a733960,0x39893a6f,0xb897ba7c,0xb8fb3a80,0x39a1ba7a,
0x3a31ba65,0xba7a39fc,0x3a6f3897,0xba13ba1d,0x3a3939e6,0xb960ba5f,0xb9b83a7f,0x3a51ba4a,0x37c93a73,0x3a09ba77,0xba6a3a27,0x3a7cb8fb,0xba8039a1,0x3a583989,0xb9cfba42,0xb92f3a7e,
0xba39b9e6,0x39603a5f,0x39b8ba7f,0xba513a4a,0x3a31ba65,0xba7a39fc,0x3a6f3897,0xba13ba1d,0x3a80b9a1,0xba58b989,0x39cf3a42,0x392fba7e,0x37c93a73,0x3a09ba77,0xba6a3a27,0x3a7cb8fb,
0x3960ba77,0xba6f3a42,0x3a5138fb,0x37c9ba65,0xba7a3989,0x39b83a27,0x3a13ba7e,0xba8039e6,0x3a0939fc,0x39cfba7f,0xba7c3a1d,0x3a3139a1,0x3a58ba5f,0xba6a3897,0x392f3a4a,0x3a39ba73,
0x3a7ab989,0xb9b8ba27,0xba133a7e,0x3a80b9e6,0x3960ba77,0xba6f3a42,0x3a5138fb,0x37c9ba65,0xba583a5f,0x3a6ab897,0xb92fba4a,0xba393a73,0x3a0939fc,0x39cfba7f,0xba7c3a1d,0x3a3139a1,
0x39e6ba7a,0xba7739cf,0xb8973a51,0x3a7eba39,0x3a65b960,0x3989ba6a,0xba7f3a13,0x38fb3a31,0x3a73ba58,0xb9fcb9b8,0xba423a7c,0x3a4ab7c9,0x39a13a09,0x3a5fba6f,0xba27b92f,0xba1d3a80,
0xba653960,0xb9893a6a,0x3a7fba13,0xb8fbba31,0x39e6ba7a,0xba7739cf,0xb8973a51,0x3a7eba39,0xb9a1ba09,0xba5f3a6f,0x3a27392f,0x3a1dba80,0x3a73ba58,0xb9fcb9b8,0xba423a7c,0x3a4ab7c9,
0xba7f3a51,0xb8fb3a39,0x3a73ba09,0x39fcba6f,0x38973a13,0x3a7eba31,0x39a1ba58,0xba5f39b8,0xba42392f,0xba4a3a80,0x39e63960,0x3a77ba6a,0xba273a7c,0x3a1d37c9,0x3a65ba7a,0xb989b9cf,
0x38973a13,0x3a7eba31,0x39a1ba58,0xba5f39b8,0x3a7fba51,0x38fbba39,0xba733a09,0xb9fc3a6f,0xba273a7c,0x3a1d37c9,0x3a65ba7a,0xb989b9cf,0x3a42b92f,0x3a4aba80,0xb9e6b960,0xba773a6a,
0x392fba1d,0xba3939a1,0xba7a3a77,0xb9b83a42,0x3a7cba4a,0x3a31ba73,0xb960b989,0xba6f3a27,0x3a13b8fb,0x3a80ba65,0x3a09ba5f,0xb9cfb897,0xba513a7e,0x37c939e6,0x3a58b9fc,0x3a6aba7f,
0x3a7cba4a,0x3a31ba73,0xb960b989,0xba6f3a27,0xb92f3a1d,0x3a39b9a1,0x3a7aba77,0x39b8ba42,0xba513a7e,0x37c939e6,0x3a58b9fc,0x3a6aba7f,0xba1338fb,0xba803a65,0xba093a5f,0x39cf3897,
0x39b8b897,0x3a51ba1d,0x3a80ba73,0x3a58ba77,0x3a6fba7f,0x3a13ba4a,0x37c9b9a1,0xba093989,0xba6a3a42,0xba7c3a7e,0xba393a65,0xb96039fc,0xb9cf3a27,0x392f38fb,0x3a31b9e6,0x3a7aba5f,
0x3a6fba7f,0x3a13ba4a,0x37c9b9a1,0xba093989,0xb9b83897,0xba513a1d,0xba803a73,0xba583a77,0xb9cf3a27,0x392f38fb,0x3a31b9e6,0x3a7aba5f,0x3a6aba42,0x3a7cba7e,0x3a39ba65,0x3960b9fc,
0xb8fb37c9,0xb9a13960,0xb9fc39cf,0xba273a13,0x3a7eba80,0x3a73ba7a,0x3a5fba6a,0x3a42ba51,0x3a1dba31,0x39e6ba09,0x3989b9b8,0x3897b92f,0x3a4aba39,0x3a65ba58,0x3a77ba6f,0x3a7fba7c,
0x3a7eba80,0x3a73ba7a,0x3a5fba6a,0x3a42ba51,0x38fbb7c9,0x39a1b960,0x39fcb9cf,0x3a27ba13,0x3a4aba39,0x3a65ba58,0x3a77ba6f,0x3a7fba7c,0xba1d3a31,0xb9e63a09,0xb98939b8,0xb897392f,
0xba4a3a39,0xba653a58,0xba773a6f,0xba7f3a7c,0x3a1dba31,0x39e6ba09,0x3989b9b8,0x3897b92f,0xba7e3a80,0xba733a7a,0xba5f3a6a,0xba423a51,0xb8fb37c9,0xb9a13960,0xb9fc39cf,0xba273a13,
0xba1d3a31,0xb9e63a09,0xb98939b8,0xb897392f,0xba4a3a39,0xba653a58,0xba773a6f,0xba7f3a7c,0x38fbb7c9,0x39a1b960,0x39fcb9cf,0x3a27ba13,0xba7e3a80,0xba733a7a,0xba5f3a6a,0xba423a51,
0x39cfba27,0xb92fb8fb,0xba3139e6,0xba7a3a5f,0xba6a3a42,0xba7c3a7e,0xba393a65,0xb96039fc,0xba6f3a7f,0xba133a4a,0xb7c939a1,0x3a09b989,0x39b8b897,0x3a51ba1d,0x3a80ba73,0x3a58ba77,
0x3a6aba42,0x3a7cba7e,0x3a39ba65,0x3960b9fc,0x39cfba27,0xb92fb8fb,0xba3139e6,0xba7a3a5f,0xb9b83897,0xba513a1d,0xba803a73,0xba583a77,0xba6f3a7f,0xba133a4a,0xb7c939a1,0x3a09b989,
0x3a51ba7e,0xb7c9b9e6,0xba5839fc,0xba6a3a7f,0x3a13b8fb,0x3a80ba65,0x3a09ba5f,0xb9cfb897,0xba7c3a4a,0xba313a73,0x39603989,0x3a6fba27,0x392fba1d,0xba3939a1,0xba7a3a77,0xb9b83a42,
0xba1338fb,0xba803a65,0xba093a5f,0x39cf3897,0x3a51ba7e,0xb7c9b9e6,0xba5839fc,0xba6a3a7f,0xb92f3a1d,0x3a39b9a1,0x3a7aba77,0x39b8ba42,0xba7c3a4a,0xba313a73,0x39603989,0x3a6fba27,
0x3a27ba7c,0xba1db7c9,0xba653a7a,0x398939cf,0xba42392f,0xba4a3a80,0x39e63960,0x3a77ba6a,0xb897ba13,0xba7e3a31,0xb9a13a58,0x3a5fb9b8,0xba7f3a51,0xb8fb3a39,0x3a73ba09,0x39fcba6f,
0x3a42b92f,0x3a4aba80,0xb9e6b960,0xba773a6a,0x3a27ba7c,0xba1db7c9,0xba653a7a,0x398939cf,0x3a7fba51,0x38fbba39,0xba733a09,0xb9fc3a6f,0xb897ba13,0xba7e3a31,0xb9a13a58,0x3a5fb9b8,
0x39a13a09,0x3a5fba6f,0xba27b92f,0xba1d3a80,0xba733a58,0x39fc39b8,0x3a42ba7c,0xba4a37c9,0x3a65b960,0x3989ba6a,0xba7f3a13,0x38fb3a31,0xb9e63a7a,0x3a77b9cf,0x3897ba51,0xba7e3a39,
0xba733a58,0x39fc39b8,0x3a42ba7c,0xba4a37c9,0xb9a1ba09,0xba5f3a6f,0x3a27392f,0x3a1dba80,0xb9e63a7a,0x3a77b9cf,0x3897ba51,0xba7e3a39,0xba653960,0xb9893a6a,0x3a7fba13,0xb8fbba31,
0x3a58ba5f,0xba6a3897,0x392f3a4a,0x3a39ba73,0xba09b9fc,0xb9cf3a7f,0x3a7cba1d,0xba31b9a1,0xba7a3989,0x39b83a27,0x3a13ba7e,0xba8039e6,0xb9603a77,0x3a6fba42,0xba51b8fb,0xb7c93a65,
0xba09b9fc,0xb9cf3a7f,0x3a7cba1d,0xba31b9a1,0xba583a5f,0x3a6ab897,0xb92fba4a,0xba393a73,0xb9603a77,0x3a6fba42,0xba51b8fb,0xb7c93a65,0x3a7ab989,0xb9b8ba27,0xba133a7e,0x3a80b9e6,
0xba8039a1,0x3a583989,0xb9cfba42,0xb92f3a7e,0xb7c9ba73,0xba093a77,0x3a6aba27,0xba7c38fb,0x3a3939e6,0xb960ba5f,0xb9b83a7f,0x3a51ba4a,0xba313a65,0x3a7ab9fc,0xba6fb897,0x3a133a1d,
0xb7c9ba73,0xba093a77,0x3a6aba27,0xba7c38fb,0x3a80b9a1,0xba58b989,0x39cf3a42,0x392fba7e,0xba313a65,0x3a7ab9fc,0xba6fb897,0x3a133a1d,0xba39b9e6,0x39603a5f,0x39b8ba7f,0xba513a4a,
0x3a77b9b8,0xba7f392f,0x3a7e37c9,0xba73b960,0xb989ba6f,0x38973a7c,0x38fbba80,0xb9a13a7a,0x39fcba6a,0xba273a51,0x3a4aba31,0xba653a09,0xba5fb9cf,0x3a423a13,0xba1dba39,0x39e63a58,
0xb989ba6f,0x38973a7c,0x38fbba80,0xb9a13a7a,0xba7739b8,0x3a7fb92f,0xba7eb7c9,0x3a733960,0xba5fb9cf,0x3a423a13,0xba1dba39,0x39e63a58,0xb9fc3a6a,0x3a27ba51,0xba4a3a31,0x3a65ba09,
0xb9893a6f,0x3897ba7c,0x38fb3a80,0xb9a1ba7a,0xba77b9b8,0x3a7f392f,0xba7e37c9,0x3a73b960,0x39fc3a6a,0xba27ba51,0x3a4a3a31,0xba65ba09,0xba5f39cf,0x3a42ba13,0xba1d3a39,0x39e6ba58,
0x3a7739b8,0xba7fb92f,0x3a7eb7c9,0xba733960,0xb9893a6f,0x3897ba7c,0x38fb3a80,0xb9a1ba7a,0x3a5fb9cf,0xba423a13,0x3a1dba39,0xb9e63a58,0x39fc3a6a,0xba27ba51,0x3a4a3a31,0xba65ba09,
0xba80b9a1,0x3a58b989,0xb9cf3a42,0xb92fba7e,0xb7c93a73,0xba09ba77,0x3a6a3a27,0xba7cb8fb,0x3a313a65,0xba7ab9fc,0x3a6fb897,0xba133a1d,0x3a39b9e6,0xb9603a5f,0xb9b8ba7f,0x3a513a4a,
0x37c9ba73,0x3a093a77,0xba6aba27,0x3a7c38fb,0xba80b9a1,0x3a58b989,0xb9cf3a42,0xb92fba7e,0xba3939e6,0x3960ba5f,0x39b83a7f,0xba51ba4a,0x3a313a65,0xba7ab9fc,0x3a6fb897,0xba133a1d,
0xba58ba5f,0x3a6a3897,0xb92f3a4a,0xba39ba73,0x3a09b9fc,0x39cf3a7f,0xba7cba1d,0x3a31b9a1,0x39603a77,0xba6fba42,0x3a51b8fb,0x37c93a65,0xba7ab989,0x39b8ba27,0x3a133a7e,0xba80b9e6,
0xba0939fc,0xb9cfba7f,0x3a7c3a1d,0xba3139a1,0xba58ba5f,0x3a6a3897,0xb92f3a4a,0xba39ba73,0x3a7a3989,0xb9b83a27,0xba13ba7e,0x3a8039e6,0x39603a77,0xba6fba42,0x3a51b8fb,0x37c93a65,
0xba73ba58,0x39fcb9b8,0x3a423a7c,0xba4ab7c9,0xb9a13a09,0xba5fba6f,0x3a27b92f,0x3a1d3a80,0xba65b960,0xb989ba6a,0x3a7f3a13,0xb8fb3a31,0x39e63a7a,0xba77b9cf,0xb897ba51,0x3a7e3a39,
0x39a1ba09,0x3a5f3a6f,0xba27392f,0xba1dba80,0xba73ba58,0x39fcb9b8,0x3a423a7c,0xba4ab7c9,0xb9e6ba7a,0x3a7739cf,0x38973a51,0xba7eba39,0xba65b960,0xb989ba6a,0x3a7f3a13,0xb8fb3a31,
0x3a42392f,0x3a4a3a80,0xb9e63960,0xba77ba6a,0x3a273a7c,0xba1d37c9,0xba65ba7a,0x3989b9cf,0x3897ba13,0x3a7e3a31,0x39a13a58,0xba5fb9b8,0x3a7f3a51,0x38fb3a39,0xba73ba09,0xb9fcba6f,
0x3a273a7c,0xba1d37c9,0xba65ba7a,0x3989b9cf,0xba42b92f,0xba4aba80,0x39e6b960,0x3a773a6a,0x3a7f3a51,0x38fb3a39,0xba73ba09,0xb9fcba6f,0xb8973a13,0xba7eba31,0xb9a1ba58,0x3a5f39b8,
0xba51ba7e,0x37c9b9e6,0x3a5839fc,0x3a6a3a7f,0xba13b8fb,0xba80ba65,0xba09ba5f,0x39cfb897,0x392f3a1d,0xba39b9a1,0xba7aba77,0xb9b8ba42,0x3a7c3a4a,0x3a313a73,0xb9603989,0xba6fba27,
0xba13b8fb,0xba80ba65,0xba09ba5f,0x39cfb897,0x3a513a7e,0xb7c939e6,0xba58b9fc,0xba6aba7f,0x3a7c3a4a,0x3a313a73,0xb9603989,0xba6fba27,0xb92fba1d,0x3a3939a1,0x3a7a3a77,0x39b83a42,
0x39cf3a27,0xb92f38fb,0xba31b9e6,0xba7aba5f,0xba6aba42,0xba7cba7e,0xba39ba65,0xb960b9fc,0x39b83897,0x3a513a1d,0x3a803a73,0x3a583a77,0x3a6f3a7f,0x3a133a4a,0x37c939a1,0xba09b989,
0xba6aba42,0xba7cba7e,0xba39ba65,0xb960b9fc,0xb9cfba27,0x392fb8fb,0x3a3139e6,0x3a7a3a5f,0x3a6f3a7f,0x3a133a4a,0x37c939a1,0xba09b989,0xb9b8b897,0xba51ba1d,0xba80ba73,0xba58ba77,
0xba1dba31,0xb9e6ba09,0xb989b9b8,0xb897b92f,0xba4aba39,0xba65ba58,0xba77ba6f,0xba7fba7c,0xba7eba80,0xba73ba7a,0xba5fba6a,0xba42ba51,0xb8fbb7c9,0xb9a1b960,0xb9fcb9cf,0xba27ba13,
0xba4aba39,0xba65ba58,0xba77ba6f,0xba7fba7c,0x3a1d3a31,0x39e63a09,0x398939b8,0x3897392f,0xb8fbb7c9,0xb9a1b960,0xb9fcb9cf,0xba27ba13,0x3a7e3a80,0x3a733a7a,0x3a5f3a6a,0x3a423a51,
0x3d973cc9,0xbf7fbf80,0x3ee63ecf,0xbf65bf6a,0x3e2f3dfb,0xbf7cbf7e,0x3f093efc,0xbf58bf5f,0x3e893e60,0xbf77bf7a,0x3f1d3f13,0xbf4abf51,0x3eb83ea1,0xbf6fbf73,0x3f313f27,0xbf39bf42,
0x3eb83dfb,0xbf6fbf7e,0x3f393f5f,0x3f313efc,0x3f423f13,0xbf27bf51,0x3ea13f09,0x3f733f58,0x3f7a3f65,0xbe60bee6,0xbe2f3d97,0x3f7c3f7f,0x3f773f80,0x3e893cc9,0xbf1dbecf,0x3f4a3f6a,
0x3f1d3e60,0xbf4abf7a,0xbf5fbf13,0x3efc3f51,0x3f803f65,0xbcc9bee6,0xbf6fbf7f,0xbeb83d97,0x3f273f6a,0x3f423ecf,0xbea1bf31,0xbf73bf39,0xbe2f3e89,0x3f7c3f77,0x3f093dfb,0xbf58bf7e,
0x3f513ea1,0xbf13bf73,0xbe60bf42,0xbf7abf27,0x3f4a3f80,0x3f1d3cc9,0x3f5f3ecf,0xbefcbf6a,0xbeb83e89,0x3f6f3f77,0x3f393f7e,0x3f313dfb,0xbf7fbf58,0xbd973f09,0xbee63e2f,0x3f653f7c,
0x3f733ecf,0xbea1bf6a,0x3f7f3f39,0x3d97bf31,0x3e603f5f,0x3f7a3efc,0xbe2f3f1d,0x3f7c3f4a,0xbf7ebf13,0x3dfb3f51,0xbf77bf58,0xbe893f09,0xbcc9bf42,0xbf80bf27,0x3eb8bee6,0xbf6fbf65,
0x3f803efc,0xbcc9bf5f,0xbeb83f1d,0x3f6f3f4a,0xbee63f09,0x3f653f58,0xbf27bf7c,0xbf423e2f,0xbf13bf7f,0xbf513d97,0x3f7a3ea1,0xbe60bf73,0x3f7e3ecf,0xbdfbbf6a,0xbe893f31,0x3f773f39,
0x3f773f13,0x3e89bf51,0xbf4abf58,0xbf1d3f09,0xbf6a3d97,0x3ecf3f7f,0x3f803ea1,0xbcc9bf73,0x3ee6bf31,0xbf65bf39,0xbf423eb8,0x3f273f6f,0x3e603f7e,0x3f7a3dfb,0x3e2fbf5f,0xbf7cbefc,
0x3f583f27,0x3f09bf42,0x3f51bee6,0xbf13bf65,0xbf77becf,0xbe893f6a,0xbf1d3f31,0x3f4a3f39,0x3f803dfb,0xbcc9bf7e,0x3eb8bf5f,0xbf6fbefc,0xbf733e2f,0x3ea13f7c,0xbd973f7a,0x3f7f3e60,
0x3f273f39,0x3f42bf31,0x3ea13f6f,0x3f73beb8,0xbf13bf4a,0xbf513f1d,0xbe60bf77,0xbf7a3e89,0x3efc3f58,0x3f5fbf09,0x3dfb3f7c,0x3f7ebe2f,0xbecfbf65,0xbf6a3ee6,0xbcc9bf7f,0xbf803d97,
0x3ecf3f4a,0x3f6abf1d,0xbf803e89,0x3cc93f77,0x3d97bf7c,0xbf7f3e2f,0x3f653e60,0x3ee6bf7a,0xbf093f73,0x3f583ea1,0xbf13bf27,0xbf513f42,0x3f5fbf31,0xbefcbf39,0x3dfb3f6f,0x3f7ebeb8,
0x3dfb3f58,0x3f7ebf09,0x3e89bf7c,0xbf773e2f,0x3f31bf73,0xbf39bea1,0xbf6a3f42,0x3ecf3f27,0xbf7f3eb8,0xbd973f6f,0x3f653cc9,0x3ee6bf80,0x3f133efc,0x3f51bf5f,0xbe60bf4a,0xbf7a3f1d,
0xbe2f3f65,0x3f7cbee6,0x3f58bd97,0x3f09bf7f,0x3f7ebf31,0xbdfbbf39,0x3e89bf6f,0xbf773eb8,0xbecfbefc,0xbf6a3f5f,0xbf803f1d,0x3cc93f4a,0xbf423f7a,0x3f273e60,0x3ea13f13,0x3f73bf51,
0xbee63f6f,0x3f65beb8,0xbf423f80,0x3f273cc9,0x3f58be89,0x3f09bf77,0x3f133dfb,0x3f51bf7e,0x3f1dbf7c,0xbf4a3e2f,0x3f5fbf7a,0xbefcbe60,0xbf393d97,0xbf313f7f,0xbecfbea1,0xbf6a3f73,
0xbf313f77,0x3f39be89,0xbecfbdfb,0xbf6a3f7e,0x3ea13e60,0x3f73bf7a,0xbf7f3f51,0xbd973f13,0x3f7cbf42,0x3e2fbf27,0xbf093f65,0x3f58bee6,0x3f1dbf6f,0xbf4a3eb8,0x3efc3cc9,0x3f5fbf80,
0xbf5f3f7c,0x3efcbe2f,0x3f7ebf7a,0xbdfbbe60,0xbeb83f27,0x3f6fbf42,0x3f31bf65,0xbf393ee6,0x3ea13cc9,0x3f73bf80,0x3d97becf,0xbf7f3f6a,0x3f58bf1d,0x3f09bf4a,0xbf133e89,0xbf513f77,
0xbf7a3f7f,0x3e60bd97,0xbe2f3ea1,0x3f7cbf73,0xbf5f3f6f,0x3efcbeb8,0x3dfb3cc9,0x3f7ebf80,0xbf313f4a,0x3f39bf1d,0x3ecfbe89,0x3f6abf77,0xbee63f13,0x3f65bf51,0x3f27bf09,0x3f42bf58,
0xbf7f3f80,0xbd973cc9,0xbf653f6a,0xbee63ecf,0xbf7c3f7e,0xbe2f3dfb,0xbf583f5f,0xbf093efc,0xbf773f7a,0xbe893e60,0xbf4a3f51,0xbf1d3f13,0xbf6f3f73,0xbeb83ea1,0xbf393f42,0xbf313f27,
0xbf6f3f7e,0xbeb83dfb,0x3f31befc,0xbf393f5f,0xbf273f51,0xbf423f13,0x3f73bf58,0xbea13f09,0xbe603ee6,0xbf7a3f65,0x3f7cbf7f,0x3e2f3d97,0x3e89bcc9,0xbf773f80,0x3f4abf6a,0x3f1dbecf,
0xbf4a3f7a,0xbf1d3e60,0x3efcbf51,0x3f5fbf13,0xbcc93ee6,0xbf803f65,0xbeb8bd97,0x3f6fbf7f,0x3f42becf,0xbf273f6a,0xbf733f39,0x3ea1bf31,0x3f7cbf77,0x3e2f3e89,0xbf583f7e,0xbf093dfb,
0xbf133f73,0xbf513ea1,0xbf7a3f27,0x3e60bf42,0x3f1dbcc9,0xbf4a3f80,0xbefc3f6a,0xbf5f3ecf,0x3f6fbf77,0x3eb83e89,0x3f31bdfb,0xbf393f7e,0xbd97bf09,0x3f7fbf58,0x3f65bf7c,0x3ee63e2f,
0xbea13f6a,0xbf733ecf,0x3d973f31,0xbf7f3f39,0x3f7abefc,0xbe603f5f,0x3f7cbf4a,0x3e2f3f1d,0x3dfbbf51,0x3f7ebf13,0xbe89bf09,0x3f77bf58,0xbf803f27,0x3cc9bf42,0xbf6f3f65,0xbeb8bee6,
0xbcc93f5f,0xbf803efc,0x3f6fbf4a,0x3eb83f1d,0x3f65bf58,0x3ee63f09,0xbf42be2f,0x3f27bf7c,0xbf51bd97,0x3f13bf7f,0xbe603f73,0xbf7a3ea1,0xbdfb3f6a,0xbf7e3ecf,0x3f77bf39,0x3e893f31,
0x3e893f51,0xbf773f13,0xbf1dbf09,0x3f4abf58,0x3ecfbf7f,0x3f6a3d97,0xbcc93f73,0xbf803ea1,0xbf653f39,0xbee6bf31,0x3f27bf6f,0x3f423eb8,0x3f7abdfb,0xbe603f7e,0xbf7c3efc,0xbe2fbf5f,
0x3f093f42,0xbf583f27,0xbf133f65,0xbf51bee6,0xbe89bf6a,0x3f77becf,0x3f4abf39,0x3f1d3f31,0xbcc93f7e,0xbf803dfb,0xbf6f3efc,0xbeb8bf5f,0x3ea1bf7c,0x3f733e2f,0x3f7fbe60,0x3d973f7a,
0x3f423f31,0xbf273f39,0x3f733eb8,0xbea13f6f,0xbf51bf1d,0x3f13bf4a,0xbf7abe89,0x3e60bf77,0x3f5f3f09,0xbefc3f58,0x3f7e3e2f,0xbdfb3f7c,0xbf6abee6,0x3ecfbf65,0xbf80bd97,0x3cc9bf7f,
0x3f6a3f1d,0xbecf3f4a,0x3cc9bf77,0x3f803e89,0xbf7fbe2f,0xbd97bf7c,0x3ee63f7a,0xbf653e60,0x3f58bea1,0x3f093f73,0xbf51bf42,0x3f13bf27,0xbefc3f39,0xbf5fbf31,0x3f7e3eb8,0xbdfb3f6f,
0x3f7e3f09,0xbdfb3f58,0xbf77be2f,0xbe89bf7c,0xbf393ea1,0xbf31bf73,0x3ecfbf27,0x3f6a3f42,0xbd97bf6f,0x3f7f3eb8,0x3ee63f80,0xbf653cc9,0x3f513f5f,0xbf133efc,0xbf7abf1d,0x3e60bf4a,
0x3f7c3ee6,0x3e2f3f65,0x3f093f7f,0xbf58bd97,0xbdfb3f39,0xbf7ebf31,0xbf77beb8,0xbe89bf6f,0xbf6abf5f,0x3ecfbefc,0x3cc9bf4a,0x3f803f1d,0x3f27be60,0x3f423f7a,0x3f733f51,0xbea13f13,
0x3f653eb8,0x3ee63f6f,0x3f27bcc9,0x3f423f80,0x3f093f77,0xbf58be89,0x3f513f7e,0xbf133dfb,0xbf4abe2f,0xbf1dbf7c,0xbefc3e60,0xbf5fbf7a,0xbf31bf7f,0x3f393d97,0xbf6abf73,0x3ecfbea1,
0x3f393e89,0x3f313f77,0xbf6abf7e,0x3ecfbdfb,0x3f733f7a,0xbea13e60,0xbd97bf13,0x3f7f3f51,0x3e2f3f27,0xbf7cbf42,0x3f583ee6,0x3f093f65,0xbf4abeb8,0xbf1dbf6f,0x3f5f3f80,0xbefc3cc9,
0x3efc3e2f,0x3f5f3f7c,0xbdfb3e60,0xbf7ebf7a,0x3f6f3f42,0x3eb83f27,0xbf39bee6,0xbf31bf65,0x3f733f80,0xbea13cc9,0xbf7fbf6a,0xbd97becf,0x3f093f4a,0xbf58bf1d,0xbf51bf77,0x3f133e89,
0x3e603d97,0x3f7a3f7f,0x3f7c3f73,0x3e2f3ea1,0x3efc3eb8,0x3f5f3f6f,0x3f7e3f80,0xbdfb3cc9,0x3f393f1d,0x3f313f4a,0x3f6a3f77,0xbecfbe89,0x3f653f51,0x3ee63f13,0x3f423f58,0xbf27bf09,
0x3f423f39,0xbf27bf31,0x3f733f6f,0xbea1beb8,0x3f513f4a,0xbf13bf1d,0x3f7a3f77,0xbe60be89,0x3f5f3f58,0xbefcbf09,0x3f7e3f7c,0xbdfbbe2f,0x3f6a3f65,0xbecfbee6,0x3f803f7f,0xbcc9bd97,
0xbf6abf4a,0x3ecf3f1d,0xbcc9be89,0xbf80bf77,0xbf7fbf7c,0xbd973e2f,0x3ee63e60,0xbf65bf7a,0xbf58bf73,0xbf09bea1,0x3f513f27,0xbf13bf42,0xbefcbf31,0xbf5fbf39,0x3f7e3f6f,0xbdfbbeb8,
0x3f7e3f58,0xbdfbbf09,0xbf77bf7c,0xbe893e2f,0x3f393f73,0x3f313ea1,0xbecfbf42,0xbf6abf27,0xbd973eb8,0x3f7f3f6f,0x3ee63cc9,0xbf65bf80,0xbf51befc,0x3f133f5f,0x3f7a3f4a,0xbe60bf1d,
0xbf7cbf65,0xbe2f3ee6,0xbf093d97,0x3f583f7f,0xbdfbbf31,0xbf7ebf39,0xbf77bf6f,0xbe893eb8,0x3f6a3efc,0xbecfbf5f,0xbcc9bf1d,0xbf80bf4a,0x3f273f7a,0x3f423e60,0x3f733f13,0xbea1bf51,
0x3f653f6f,0x3ee6beb8,0x3f273f80,0x3f423cc9,0xbf093e89,0x3f583f77,0xbf51bdfb,0x3f133f7e,0xbf4abf7c,0xbf1d3e2f,0xbefcbf7a,0xbf5fbe60,0x3f31bd97,0xbf39bf7f,0x3f6a3ea1,0xbecfbf73,
0xbf39bf77,0xbf313e89,0x3f6a3dfb,0xbecfbf7e,0x3f733e60,0xbea1bf7a,0xbd973f51,0x3f7f3f13,0xbe2f3f42,0x3f7c3f27,0xbf58bf65,0xbf093ee6,0xbf4abf6f,0xbf1d3eb8,0x3f5f3cc9,0xbefcbf80,
0x3efc3f7c,0x3f5fbe2f,0xbdfbbf7a,0xbf7ebe60,0xbf6fbf27,0xbeb83f42,0x3f393f65,0x3f31bee6,0x3f733cc9,0xbea1bf80,0xbf7fbecf,0xbd973f6a,0xbf093f1d,0x3f583f4a,0x3f51be89,0xbf13bf77,
0xbe60bf7f,0xbf7a3d97,0xbf7cbea1,0xbe2f3f73,0x3efc3f6f,0x3f5fbeb8,0x3f7e3cc9,0xbdfbbf80,0xbf39bf4a,0xbf313f1d,0xbf6a3e89,0x3ecf3f77,0x3f653f13,0x3ee6bf51,0x3f42bf09,0xbf27bf58,
0xbd973f80,0x3f7f3cc9,0xbee63f6a,0x3f653ecf,0x3e2fbf7e,0xbf7cbdfb,0x3f09bf5f,0xbf58befc,0xbe893f7a,0x3f773e60,0xbf1d3f51,0x3f4a3f13,0x3eb8bf73,0xbf6fbea1,0x3f31bf42,0xbf39bf27,
0x3eb8bf7e,0xbf6fbdfb,0x3f393efc,0x3f31bf5f,0xbf423f51,0x3f273f13,0xbea1bf58,0xbf733f09,0x3f7abee6,0xbe60bf65,0xbe2f3f7f,0x3f7cbd97,0xbf77bcc9,0xbe893f80,0x3f1dbf6a,0xbf4abecf,
0xbf1d3f7a,0x3f4a3e60,0x3f5fbf51,0xbefcbf13,0x3f80bee6,0xbcc9bf65,0xbf6f3d97,0xbeb83f7f,0xbf27becf,0xbf423f6a,0x3ea13f39,0x3f73bf31,0xbe2f3f77,0x3f7cbe89,0x3f09bf7e,0xbf58bdfb,
0x3f51bf73,0xbf13bea1,0xbe60bf27,0xbf7a3f42,0xbf4abcc9,0xbf1d3f80,0xbf5f3f6a,0x3efc3ecf,0xbeb83f77,0x3f6fbe89,0x3f393dfb,0x3f31bf7e,0x3f7fbf09,0x3d97bf58,0x3ee6bf7c,0xbf653e2f,
0xbf733f6a,0x3ea13ecf,0xbf7f3f31,0xbd973f39,0x3e603efc,0x3f7abf5f,0xbe2f3f4a,0x3f7cbf1d,0x3f7ebf51,0xbdfbbf13,0x3f77bf09,0x3e89bf58,0xbcc9bf27,0xbf803f42,0x3eb8bf65,0xbf6f3ee6,
0x3f80bf5f,0xbcc9befc,0xbeb83f4a,0x3f6fbf1d,0x3ee6bf58,0xbf653f09,0x3f27be2f,0x3f42bf7c,0xbf133d97,0xbf513f7f,0x3f7abf73,0xbe60bea1,0xbf7e3f6a,0x3dfb3ecf,0x3e89bf39,0xbf773f31,
0xbf773f51,0xbe893f13,0x3f4abf09,0x3f1dbf58,0xbf6a3f7f,0x3ecfbd97,0x3f80bf73,0xbcc9bea1,0xbee63f39,0x3f65bf31,0x3f42bf6f,0xbf273eb8,0x3e603dfb,0x3f7abf7e,0x3e2fbefc,0xbf7c3f5f,
0x3f58bf42,0x3f09bf27,0x3f51bf65,0xbf133ee6,0x3f77bf6a,0x3e89becf,0x3f1dbf39,0xbf4a3f31,0x3f80bf7e,0xbcc9bdfb,0x3eb8befc,0xbf6f3f5f,0x3f73bf7c,0xbea13e2f,0x3d97be60,0xbf7f3f7a,
0xbf273f31,0xbf423f39,0xbea13eb8,0xbf733f6f,0xbf133f1d,0xbf513f4a,0xbe603e89,0xbf7a3f77,0xbefc3f09,0xbf5f3f58,0xbdfb3e2f,0xbf7e3f7c,0xbecf3ee6,0xbf6a3f65,0xbcc93d97,0xbf803f7f,
0x3ecfbf1d,0x3f6abf4a,0xbf803f77,0x3cc9be89,0xbd97be2f,0x3f7fbf7c,0xbf653f7a,0xbee63e60,0xbf093ea1,0x3f58bf73,0xbf133f42,0xbf513f27,0xbf5f3f39,0x3efcbf31,0xbdfb3eb8,0xbf7e3f6f,
0xbdfb3f09,0xbf7e3f58,0xbe89be2f,0x3f77bf7c,0x3f31bea1,0xbf393f73,0xbf6a3f27,0x3ecfbf42,0x3f7fbf6f,0x3d973eb8,0xbf653f80,0xbee63cc9,0x3f13bf5f,0x3f51befc,0xbe603f1d,0xbf7a3f4a,
0xbe2fbee6,0x3f7cbf65,0x3f58bf7f,0x3f093d97,0xbf7e3f39,0x3dfbbf31,0xbe89beb8,0x3f77bf6f,0xbecf3f5f,0xbf6a3efc,0xbf803f4a,0x3cc9bf1d,0x3f42be60,0xbf273f7a,0xbea13f51,0xbf733f13,
0x3ee63eb8,0xbf653f6f,0x3f42bcc9,0xbf273f80,0x3f58bf77,0x3f093e89,0x3f13bf7e,0x3f51bdfb,0xbf1dbe2f,0x3f4abf7c,0xbf5f3e60,0x3efcbf7a,0xbf393f7f,0xbf31bd97,0xbecf3f73,0xbf6a3ea1,
0xbf31be89,0x3f39bf77,0xbecf3f7e,0xbf6a3dfb,0xbea13f7a,0xbf733e60,0x3f7fbf13,0x3d973f51,0x3f7cbf27,0x3e2f3f42,0xbf09bee6,0x3f58bf65,0xbf1dbeb8,0x3f4abf6f,0xbefc3f80,0xbf5f3cc9,
0x3f5f3e2f,0xbefc3f7c,0xbf7e3e60,0x3dfbbf7a,0xbeb8bf42,0x3f6fbf27,0x3f313ee6,0xbf393f65,0xbea13f80,0xbf733cc9,0xbd97bf6a,0x3f7fbecf,0x3f58bf4a,0x3f093f1d,0xbf133f77,0xbf51be89,
0xbf7abd97,0x3e60bf7f,0xbe2fbf73,0x3f7cbea1,0x3f5f3eb8,0xbefc3f6f,0xbdfb3f80,0xbf7e3cc9,0xbf31bf1d,0x3f39bf4a,0x3ecfbf77,0x3f6a3e89,0x3ee63f51,0xbf653f13,0xbf273f58,0xbf42bf09,
0x3f7fbcc9,0x3d973f80,0x3f65becf,0x3ee63f6a,0xbf7c3dfb,0xbe2fbf7e,0xbf583efc,0xbf09bf5f,0x3f77be60,0x3e893f7a,0x3f4abf13,0x3f1d3f51,0xbf6f3ea1,0xbeb8bf73,0xbf393f27,0xbf31bf42,
0xbf6f3dfb,0xbeb8bf7e,0x3f313f5f,0xbf393efc,0x3f27bf13,0x3f423f51,0xbf73bf09,0x3ea1bf58,0xbe603f65,0xbf7abee6,0x3f7c3d97,0x3e2f3f7f,0xbe89bf80,0x3f77bcc9,0xbf4a3ecf,0xbf1dbf6a,
0x3f4abe60,0x3f1d3f7a,0xbefc3f13,0xbf5fbf51,0xbcc93f65,0xbf80bee6,0xbeb8bf7f,0x3f6f3d97,0xbf42bf6a,0x3f27becf,0x3f733f31,0xbea13f39,0x3f7c3e89,0x3e2f3f77,0xbf583dfb,0xbf09bf7e,
0xbf133ea1,0xbf51bf73,0xbf7abf42,0x3e60bf27,0xbf1dbf80,0x3f4abcc9,0x3efcbecf,0x3f5f3f6a,0x3f6f3e89,0x3eb83f77,0x3f313f7e,0xbf393dfb,0x3d973f58,0xbf7fbf09,0xbf65be2f,0xbee6bf7c,
0x3ea1becf,0x3f733f6a,0xbd97bf39,0x3f7f3f31,0x3f7a3f5f,0xbe603efc,0x3f7c3f1d,0x3e2f3f4a,0xbdfb3f13,0xbf7ebf51,0x3e893f58,0xbf77bf09,0xbf80bf42,0x3cc9bf27,0xbf6fbee6,0xbeb8bf65,
0xbcc93efc,0xbf80bf5f,0x3f6f3f1d,0x3eb83f4a,0xbf65bf09,0xbee6bf58,0x3f423f7c,0xbf27be2f,0xbf51bf7f,0x3f133d97,0xbe603ea1,0xbf7abf73,0x3dfbbecf,0x3f7e3f6a,0xbf77bf31,0xbe89bf39,
0xbe89bf13,0x3f773f51,0x3f1d3f58,0xbf4abf09,0x3ecf3d97,0x3f6a3f7f,0xbcc93ea1,0xbf80bf73,0x3f653f31,0x3ee63f39,0xbf27beb8,0xbf42bf6f,0x3f7a3f7e,0xbe603dfb,0xbf7cbf5f,0xbe2fbefc,
0x3f093f27,0xbf58bf42,0xbf13bee6,0xbf51bf65,0x3e893ecf,0xbf77bf6a,0xbf4abf31,0xbf1dbf39,0xbcc93dfb,0xbf80bf7e,0xbf6fbf5f,0xbeb8befc,0xbea1be2f,0xbf73bf7c,0xbf7fbf7a,0xbd97be60,
0x3f6e3f7a,0x3f1f3f28,0x3ec23ed0,0x3e2f3e48,0x3f583f63,0x3f0e3f17,0x3ea63eb4,0x3df93e15,0x3f443f4e,0x3efd3f06,0x3e8b3e99,0x3d953dc7,0x3f313f3a,0x3edf3eee,0x3e623e7c,0x3cc63d46,
0x3f583f62,0x3f133f1b,0x3eb53ec2,0x3e243e3b,0x3f453f4f,0x3f043f0b,0x3e9b3ea8,0x3de93e0c,0x3f333f3c,0x3eeb3ef9,0x3e823e8f,0x3d8b3dba,0x3f233f2b,0x3ecf3edd,0x3e533e6c,0x3cb93d39,
0x3f443f4d,0x3f073f0e,0x3ea83eb4,0x3e183e2e,0x3f343f3c,0x3ef33f00,0x3e903e9c,0x3dd93e02,0x3f243f2c,0x3ed93ee6,0x3e723e84,0x3d823dad,0x3f153f1c,0x3ec03ecc,0x3e453e5b,0x3cad3d2d,
0x3f323f39,0x3ef73f02,0x3e9b3ea6,0x3e0d3e22,0x3f233f2a,0x3edf3eeb,0x3e853e90,0x3dc93df1,0x3f153f1c,0x3ec83ed3,0x3e603e75,0x3d713da1,0x3f083f0f,0x3eb13ebc,0x3e363e4b,0x3ca03d20,
0x3f203f27,0x3ee13eec,0x3e8e3e98,0x3e023e15,0x3f133f1a,0x3ecc3ed6,0x3e743e84,0x3db93dde,0x3f073f0d,0x3eb73ec1,0x3e4e3e61,0x3d5e3d94,0x3ef83f02,0x3ea23eac,0x3e283e3b,0x3c943d14,
0x3f103f15,0x3ecc3ed6,0x3e813e8a,0x3ded3e08,0x3f053f0a,0x3eb93ec2,0x3e5f3e71,0x3da93dcb,0x3ef43eff,0x3ea63eaf,0x3e3c3e4d,0x3d4b3d87,0x3ee03eea,0x3e933e9d,0x3e193e2a,0x3c873d07,
0x3f003f05,0x3eb73ec0,0x3e6a3e7a,0x3dd73df6,0x3eed3ef6,0x3ea63eaf,0x3e4a3e5a,0x3d993db8,0x3edb3ee4,0x3e963e9e,0x3e2a3e3a,0x3d383d75,0x3ec93ed2,0x3e853e8d,0x3e0b3e1a,0x3c753cf5,
0x3ee23eeb,0x3ea33eab,0x3e513e5f,0x3dc13ddd,0x3ed23eda,0x3e943e9c,0x3e353e43,0x3d8a3da5,0x3ec23eca,0x3e853e8d,0x3e183e26,0x3d253d5c,0x3eb33eba,0x3e6e3e7c,0x3df93e0a,0x3c5c3cdc,
0x3ec63ecd,0x3e903e96,0x3e393e45,0x3dab3dc3,0x3eb83ebf,0x3e833e89,0x3e203e2c,0x3d743d92,0x3eaa3eb1,0x3e6b3e78,0x3e073e13,0x3d123d43,0x3e9d3ea3,0x3e523e5f,0x3ddc3df5,0x3c433cc3,
0x3eaa3eb0,0x3e793e82,0x3e203e2b,0x3d953daa,0x3e9f3ea4,0x3e623e6d,0x3e0b3e15,0x3d543d7f,0x3e933e99,0x3e4c3e57,0x3dea3e00,0x3cff3d2a,0x3e883e8d,0x3e363e41,0x3dbf3dd5,0x3c2a3caa,
0x3e903e94,0x3e533e5c,0x3e083e11,0x3d7d3d91,0x3e863e8b,0x3e403e49,0x3dec3dfe,0x3d353d59,0x3e793e81,0x3e2d3e37,0x3dc73dda,0x3cd93d11,0x3e663e6f,0x3e1b3e24,0x3da33db5,0x3c113c91,
0x3e6b3e73,0x3e2d3e35,0x3de13df0,0x3d513d6f,0x3e5c3e63,0x3e1e3e26,0x3dc33dd2,0x3d153d33,0x3e4c3e54,0x3e0f3e16,0x3da53db4,0x3cb33cef,0x3e3d3e44,0x3dff3e07,0x3d863d95,0x3bef3c6f,
0x3e393e3f,0x3e083e0e,0x3db13dbd,0x3d253d3d,0x3e2c3e32,0x3df93e02,0x3d993da5,0x3cec3d0d,0x3e203e26,0x3de13ded,0x3d823d8e,0x3c8d3cbd,0x3e143e1a,0x3dc93dd5,0x3d543d6c,0x3bbc3c3d,
0x3e073e0b,0x3dc73dd0,0x3d823d8a,0x3cf23d0a,0x3dfc3e02,0x3db63dbf,0x3d613d72,0x3cad3ccf,0x3dea3df3,0x3da53dad,0x3d3e3d50,0x3c4f3c8a,0x3dd93de2,0x3d933d9c,0x3d1c3d2d,0x3b8a3c0a,
0x3dab3db0,0x3d7d3d84,0x3d253d30,0x3c9a3cb0,0x3da03da5,0x3d673d72,0x3d0f3d1a,0x3c5c3c84,0x3d953d9a,0x3d513d5c,0x3cf23d04,0x3c043c30,0x3d8a3d8f,0x3d3b3d46,0x3cc63cdc,0x3b303bb0,
0x3d123d17,0x3cd93ce2,0x3c8d3c97,0x3c043c17,0x3d093d0d,0x3cc63ccf,0x3c753c84,0x3bbc3be2,0x3cff3d04,0x3cb33cbd,0x3c4f3c62,0x3b623b97,0x3cec3cf5,0x3ca03caa,0x3c2a3c3d,0x3a973b17,
0xbc43bc49,0xbc11bc17,0xbbbcbbc9,0xbb30bb49,0xbc36bc3d,0xbc04bc0a,0xbba3bbb0,0xbafbbb17,0xbc2abc30,0xbbefbbfb,0xbb8abb97,0xba97bac9,0xbc1dbc23,0xbbd6bbe2,0xbb62bb7b,0xb9c9ba49,
0xbd74bd7c,0xbd35bd3d,0xbcecbcfb,0xbc5cbc7b,0xbd64bd6c,0xbd25bd2d,0xbcccbcdc,0xbc1dbc3d,0xbd54bd5c,0xbd15bd1d,0xbcadbcbd,0xbbbcbbfb,0xbd45bd4c,0xbd06bd0d,0xbc8dbc9d,0xbafbbb7b,
0xbddcbde3,0xbda3bdaa,0xbd54bd62,0xbcc6bce2,0xbdcebdd5,0xbd95bd9c,0xbd38bd46,0xbc8dbcaa,0xbdbfbdc7,0xbd86bd8e,0xbd1cbd2a,0xbc2abc62,0xbdb1bdb8,0xbd71bd7f,0xbcffbd0d,0xbb62bbe2,
0xbe20be25,0xbdecbdf6,0xbd99bda4,0xbd0fbd23,0xbe15be1a,0xbdd7bde2,0xbd85bd8f,0xbcccbcf5,0xbe0bbe10,0xbdc3bdcd,0xbd61bd75,0xbc75bca3,0xbe00be05,0xbdaebdb8,0xbd38bd4c,0xbba3bc23,
0xbe52be59,0xbe1bbe22,0xbdc9bdd6,0xbd3bbd56,0xbe44be4b,0xbe0dbe14,0xbdaebdbb,0xbd06bd20,0xbe36be3d,0xbdffbe06,0xbd93bda1,0xbca0bcd6,0xbe28be2f,0xbde4bdf1,0xbd71bd86,0xbbd6bc56,
0xbe83be87,0xbe40be48,0xbdf9be05,0xbd67bd84,0xbe74be7c,0xbe2fbe37,0xbdd7bde8,0xbd25bd46,0xbe62be6b,0xbe1ebe26,0xbdb6bdc7,0xbcc6bd04,0xbe51be5a,0xbe0dbe15,0xbd95bda5,0xbc04bc84,
0xbe9dbea2,0xbe66be70,0xbe14be1e,0xbd8abd9d,0xbe92be97,0xbe51be5b,0xbe00be0a,0xbd45bd6c,0xbe88be8d,0xbe3dbe47,0xbdd9bded,0xbcecbd1d,0xbe7abe82,0xbe28be32,0xbdb1bdc5,0xbc1dbc9d,
0xbeb8bebe,0xbe86be8c,0xbe2cbe38,0xbda0bdb7,0xbeabbeb1,0xbe74be80,0xbe15be21,0xbd64bd89,0xbe9fbea5,0xbe5cbe68,0xbdfcbe09,0xbd09bd36,0xbe92be98,0xbe44be50,0xbdcebde5,0xbc36bcb6,
0xbed4bedb,0xbe99bea0,0xbe45be52,0xbdb6bdd0,0xbec5becc,0xbe8bbe92,0xbe2abe37,0xbd82bd9c,0xbeb6bebd,0xbe7bbe84,0xbe0fbe1d,0xbd1cbd50,0xbea8beaf,0xbe60be6d,0xbdeabe02,0xbc4fbccf,
0xbef1befa,0xbeadbeb5,0xbe5dbe6d,0xbdccbde9,0xbedfbee8,0xbe9dbea5,0xbe3fbe4e,0xbd92bdaf,0xbecebed7,0xbe8dbe95,0xbe21be30,0xbd2ebd69,0xbebebec6,0xbe7cbe86,0xbe03be12,0xbc68bce9,
0xbf08bf0d,0xbec2becb,0xbe76be84,0xbde2be01,0xbefbbf03,0xbeafbeb9,0xbe54be65,0xbda1bdc2,0xbee7bef1,0xbe9ebea7,0xbe33be44,0xbd41bd81,0xbed4bede,0xbe8cbe95,0xbe12be22,0xbc81bd01,
0xbf18bf1e,0xbed7bee1,0xbe88be91,0xbdf9be0e,0xbf0cbf12,0xbec2becc,0xbe6abe7c,0xbdb1bdd5,0xbf01bf06,0xbeaebeb8,0xbe45be57,0xbd54bd8e,0xbeecbef6,0xbe9bbea4,0xbe20be32,0xbc8dbd0d,
0xbf29bf30,0xbeecbef8,0xbe94be9f,0xbe07be1b,0xbf1bbf22,0xbed5bee1,0xbe7fbe8a,0xbdc1bde8,0xbf0ebf15,0xbebfbeca,0xbe57be6b,0xbd67bd9a,0xbf02bf08,0xbea9beb4,0xbe2fbe43,0xbc9abd1a,
0xbf3bbf43,0xbf01bf08,0xbea1bead,0xbe13be28,0xbf2bbf33,0xbee9bef6,0xbe8bbe96,0xbdd1bdfb,0xbf1dbf24,0xbed0bedc,0xbe69be7f,0xbd7abda7,0xbf0fbf15,0xbeb8bec4,0xbe3dbe53,0xbca7bd27,
0xbf4ebf57,0xbf0dbf14,0xbeaebebb,0xbe1ebe35,0xbf3cbf45,0xbefdbf06,0xbe96bea2,0xbde1be07,0xbf2bbf34,0xbee2beef,0xbe7bbe89,0xbd86bdb4,0xbf1cbf23,0xbec8bed5,0xbe4cbe63,0xbcb3bd33,
0xbf63bf6e,0xbf19bf21,0xbebbbec9,0xbe29be42,0xbf4ebf58,0xbf09bf11,0xbea1beae,0xbdf1be11,0xbf3bbf45,0xbef4bf01,0xbe87be94,0xbd90bdc0,0xbf29bf32,0xbed7bee5,0xbe5bbe74,0xbcc0bd40,
0xbcc68000,0xbe62be48,0xbedfbed0,0xbf31bf28,0xbd95bd46,0xbe8bbe7c,0xbefdbeee,0xbf44bf3a,0xbdf9bdc7,0xbea6be99,0xbf0ebf06,0xbf58bf4e,0xbe2fbe15,0xbec2beb4,0xbf1fbf17,0xbf6ebf63,
0xbcb98000,0xbe53be3b,0xbecfbec2,0xbf23bf1b,0xbd8bbd39,0xbe82be6c,0xbeebbedd,0xbf33bf2b,0xbde9bdba,0xbe9bbe8f,0xbf04bef9,0xbf45bf3c,0xbe24be0c,0xbeb5bea8,0xbf13bf0b,0xbf58bf4f,
0xbcad8000,0xbe45be2e,0xbec0beb4,0xbf15bf0e,0xbd82bd2d,0xbe72be5b,0xbed9becc,0xbf24bf1c,0xbdd9bdad,0xbe90be84,0xbef3bee6,0xbf34bf2c,0xbe18be02,0xbea8be9c,0xbf07bf00,0xbf44bf3c,
0xbca08000,0xbe36be22,0xbeb1bea6,0xbf08bf02,0xbd71bd20,0xbe60be4b,0xbec8bebc,0xbf15bf0f,0xbdc9bda1,0xbe85be75,0xbedfbed3,0xbf23bf1c,0xbe0dbdf1,0xbe9bbe90,0xbef7beeb,0xbf32bf2a,
0xbc948000,0xbe28be15,0xbea2be98,0xbef8beec,0xbd5ebd14,0xbe4ebe3b,0xbeb7beac,0xbf07bf02,0xbdb9bd94,0xbe74be61,0xbeccbec1,0xbf13bf0d,0xbe02bdde,0xbe8ebe84,0xbee1bed6,0xbf20bf1a,
0xbc878000,0xbe19be08,0xbe93be8a,0xbee0bed6,0xbd4bbd07,0xbe3cbe2a,0xbea6be9d,0xbef4beea,0xbda9bd87,0xbe5fbe4d,0xbeb9beaf,0xbf05beff,0xbdedbdcb,0xbe81be71,0xbeccbec2,0xbf10bf0a,
0xbc758000,0xbe0bbdf6,0xbe85be7a,0xbec9bec0,0xbd38bcf5,0xbe2abe1a,0xbe96be8d,0xbedbbed2,0xbd99bd75,0xbe4abe3a,0xbea6be9e,0xbeedbee4,0xbdd7bdb8,0xbe6abe5a,0xbeb7beaf,0xbf00bef6,
0xbc5c8000,0xbdf9bddd,0xbe6ebe5f,0xbeb3beab,0xbd25bcdc,0xbe18be0a,0xbe85be7c,0xbec2beba,0xbd8abd5c,0xbe35be26,0xbe94be8d,0xbed2beca,0xbdc1bda5,0xbe51be43,0xbea3be9c,0xbee2beda,
0xbc438000,0xbddcbdc3,0xbe52be45,0xbe9dbe96,0xbd12bcc3,0xbe07bdf5,0xbe6bbe5f,0xbeaabea3,0xbd74bd43,0xbe20be13,0xbe83be78,0xbeb8beb1,0xbdabbd92,0xbe39be2c,0xbe90be89,0xbec6bebf,
0xbc2a8000,0xbdbfbdaa,0xbe36be2b,0xbe88be82,0xbcffbcaa,0xbdeabdd5,0xbe4cbe41,0xbe93be8d,0xbd54bd2a,0xbe0bbe00,0xbe62be57,0xbe9fbe99,0xbd95bd7f,0xbe20be15,0xbe79be6d,0xbeaabea4,
0xbc118000,0xbda3bd91,0xbe1bbe11,0xbe66be5c,0xbcd9bc91,0xbdc7bdb5,0xbe2dbe24,0xbe79be6f,0xbd35bd11,0xbdecbdda,0xbe40be37,0xbe86be81,0xbd7dbd59,0xbe08bdfe,0xbe53be49,0xbe90be8b,
0xbbef8000,0xbd86bd6f,0xbdffbdf0,0xbe3dbe35,0xbcb3bc6f,0xbda5bd95,0xbe0fbe07,0xbe4cbe44,0xbd15bcef,0xbdc3bdb4,0xbe1ebe16,0xbe5cbe54,0xbd51bd33,0xbde1bdd2,0xbe2dbe26,0xbe6bbe63,
0xbbbc8000,0xbd54bd3d,0xbdc9bdbd,0xbe14be0e,0xbc8dbc3d,0xbd82bd6c,0xbde1bdd5,0xbe20be1a,0xbcecbcbd,0xbd99bd8e,0xbdf9bded,0xbe2cbe26,0xbd25bd0d,0xbdb1bda5,0xbe08be02,0xbe39be32,
0xbb8a8000,0xbd1cbd0a,0xbd93bd8a,0xbdd9bdd0,0xbc4fbc0a,0xbd3ebd2d,0xbda5bd9c,0xbdeabde2,0xbcadbc8a,0xbd61bd50,0xbdb6bdad,0xbdfcbdf3,0xbcf2bccf,0xbd82bd72,0xbdc7bdbf,0xbe07be02,
0xbb308000,0xbcc6bcb0,0xbd3bbd30,0xbd8abd84,0xbc04bbb0,0xbcf2bcdc,0xbd51bd46,0xbd95bd8f,0xbc5cbc30,0xbd0fbd04,0xbd67bd5c,0xbda0bd9a,0xbc9abc84,0xbd25bd1a,0xbd7dbd72,0xbdabbda5,
0xba978000,0xbc2abc17,0xbca0bc97,0xbcecbce2,0xbb62bb17,0xbc4fbc3d,0xbcb3bcaa,0xbcffbcf5,0xbbbcbb97,0xbc75bc62,0xbcc6bcbd,0xbd09bd04,0xbc04bbe2,0xbc8dbc84,0xbcd9bccf,0xbd12bd0d,
0x39c90000,0x3b623b49,0x3bd63bc9,0x3c1d3c17,0x3a973a49,0x3b8a3b7b,0x3bef3be2,0x3c2a3c23,0x3afb3ac9,0x3ba33b97,0x3c043bfb,0x3c363c30,0x3b303b17,0x3bbc3bb0,0x3c113c0a,0x3c433c3d,
0x3afb0000,0x3c8d3c7b,0x3d063cfb,0x3d453d3d,0x3bbc3b7b,0x3cad3c9d,0x3d153d0d,0x3d543d4c,0x3c1d3bfb,0x3ccc3cbd,0x3d253d1d,0x3d643d5c,0x3c5c3c3d,0x3cec3cdc,0x3d353d2d,0x3d743d6c,
0x3b620000,0x3cff3ce2,0x3d713d62,0x3db13daa,0x3c2a3be2,0x3d1c3d0d,0x3d863d7f,0x3dbf3db8,0x3c8d3c62,0x3d383d2a,0x3d953d8e,0x3dce3dc7,0x3cc63caa,0x3d543d46,0x3da33d9c,0x3ddc3dd5,
0x3ba30000,0x3d383d23,0x3dae3da4,0x3e003df6,0x3c753c23,0x3d613d4c,0x3dc33db8,0x3e0b3e05,0x3ccc3ca3,0x3d853d75,0x3dd73dcd,0x3e153e10,0x3d0f3cf5,0x3d993d8f,0x3dec3de2,0x3e203e1a,
0x3bd60000,0x3d713d56,0x3de43dd6,0x3e283e22,0x3ca03c56,0x3d933d86,0x3dff3df1,0x3e363e2f,0x3d063cd6,0x3dae3da1,0x3e0d3e06,0x3e443e3d,0x3d3b3d20,0x3dc93dbb,0x3e1b3e14,0x3e523e4b,
0x3c040000,0x3d953d84,0x3e0d3e05,0x3e513e48,0x3cc63c84,0x3db63da5,0x3e1e3e15,0x3e623e5a,0x3d253d04,0x3dd73dc7,0x3e2f3e26,0x3e743e6b,0x3d673d46,0x3df93de8,0x3e403e37,0x3e833e7c,
0x3c1d0000,0x3db13d9d,0x3e283e1e,0x3e7a3e70,0x3cec3c9d,0x3dd93dc5,0x3e3d3e32,0x3e883e82,0x3d453d1d,0x3e003ded,0x3e513e47,0x3e923e8d,0x3d8a3d6c,0x3e143e0a,0x3e663e5b,0x3e9d3e97,
0x3c360000,0x3dce3db7,0x3e443e38,0x3e923e8c,0x3d093cb6,0x3dfc3de5,0x3e5c3e50,0x3e9f3e98,0x3d643d36,0x3e153e09,0x3e743e68,0x3eab3ea5,0x3da03d89,0x3e2c3e21,0x3e863e80,0x3eb83eb1,
0x3c4f0000,0x3dea3dd0,0x3e603e52,0x3ea83ea0,0x3d1c3ccf,0x3e0f3e02,0x3e7b3e6d,0x3eb63eaf,0x3d823d50,0x3e2a3e1d,0x3e8b3e84,0x3ec53ebd,0x3db63d9c,0x3e453e37,0x3e993e92,0x3ed43ecc,
0x3c680000,0x3e033de9,0x3e7c3e6d,0x3ebe3eb5,0x3d2e3ce9,0x3e213e12,0x3e8d3e86,0x3ece3ec6,0x3d923d69,0x3e3f3e30,0x3e9d3e95,0x3edf3ed7,0x3dcc3daf,0x3e5d3e4e,0x3ead3ea5,0x3ef13ee8,
0x3c810000,0x3e123e01,0x3e8c3e84,0x3ed43ecb,0x3d413d01,0x3e333e22,0x3e9e3e95,0x3ee73ede,0x3da13d81,0x3e543e44,0x3eaf3ea7,0x3efb3ef1,0x3de23dc2,0x3e763e65,0x3ec23eb9,0x3f083f03,
0x3c8d0000,0x3e203e0e,0x3e9b3e91,0x3eec3ee1,0x3d543d0d,0x3e453e32,0x3eae3ea4,0x3f013ef6,0x3db13d8e,0x3e6a3e57,0x3ec23eb8,0x3f0c3f06,0x3df93dd5,0x3e883e7c,0x3ed73ecc,0x3f183f12,
0x3c9a0000,0x3e2f3e1b,0x3ea93e9f,0x3f023ef8,0x3d673d1a,0x3e573e43,0x3ebf3eb4,0x3f0e3f08,0x3dc13d9a,0x3e7f3e6b,0x3ed53eca,0x3f1b3f15,0x3e073de8,0x3e943e8a,0x3eec3ee1,0x3f293f22,
0x3ca70000,0x3e3d3e28,0x3eb83ead,0x3f0f3f08,0x3d7a3d27,0x3e693e53,0x3ed03ec4,0x3f1d3f15,0x3dd13da7,0x3e8b3e7f,0x3ee93edc,0x3f2b3f24,0x3e133dfb,0x3ea13e96,0x3f013ef6,0x3f3b3f33,
0x3cb30000,0x3e4c3e35,0x3ec83ebb,0x3f1c3f14,0x3d863d33,0x3e7b3e63,0x3ee23ed5,0x3f2b3f23,0x3de13db4,0x3e963e89,0x3efd3eef,0x3f3c3f34,0x3e1e3e07,0x3eae3ea2,0x3f0d3f06,0x3f4e3f45,
0x3cc00000,0x3e5b3e42,0x3ed73ec9,0x3f293f21,0x3d903d40,0x3e873e74,0x3ef43ee5,0x3f3b3f32,0x3df13dc0,0x3ea13e94,0x3f093f01,0x3f4e3f45,0x3e293e11,0x3ebb3eae,0x3f193f11,0x3f633f58,
0x3f7f3f80,0x3f653f6b,0x3f2a3f33,0x3eaa3ec1,0x3f7c3f7e,0x3f593f60,0x3f163f20,0x3e753e92,0x3f773f7a,0x3f4b3f53,0x3f023f0c,0x3e143e45,0x3f6f3f73,0x3f3b3f44,0x3ed83eee,0x3d463dc6,
0x3f7c3f7e,0x3f5d3f63,0x3f213f2a,0x3e9f3eb5,0x3f773f7a,0x3f503f57,0x3f0e3f18,0x3e663e89,0x3f713f74,0x3f423f49,0x3ef43f04,0x3e0b3e38,0x3f683f6c,0x3f323f3a,0x3ecb3ee0,0x3d393db9,
0x3f773f7a,0x3f533f59,0x3f173f20,0x3e953eaa,0x3f713f74,0x3f463f4d,0x3f053f0f,0x3e563e80,0x3f693f6d,0x3f383f3f,0x3ee53ef8,0x3e013e2c,0x3f5f3f64,0x3f283f30,0x3ebe3ed2,0x3d2d3dad,
0x3f703f73,0x3f483f4f,0x3f0e3f16,0x3e8a3e9e,0x3f683f6c,0x3f3b3f42,0x3ef93f05,0x3e473e6e,0x3f5f3f64,0x3f2d3f34,0x3ed63ee8,0x3df03e20,0x3f543f5a,0x3f1e3f26,0x3eb13ec3,0x3d203da0,
0x3f663f6a,0x3f3d3f43,0x3f043f0c,0x3e803e92,0x3f5d3f62,0x3f303f36,0x3ee73ef8,0x3e383e5c,0x3f543f59,0x3f223f29,0x3ec63ed7,0x3ddd3e13,0x3f493f4e,0x3f133f1b,0x3ea33eb5,0x3d143d94,
0x3f5a3f5f,0x3f303f36,0x3ef33f01,0x3e6a3e86,0x3f513f56,0x3f233f2a,0x3ed53ee4,0x3e283e49,0x3f473f4c,0x3f163f1d,0x3eb63ec5,0x3dca3e07,0x3f3c3f42,0x3f083f0f,0x3e963ea6,0x3d073d87,
0x3f4d3f51,0x3f233f28,0x3ede3eec,0x3e553e73,0x3f433f48,0x3f163f1d,0x3ec23ed0,0x3e193e37,0x3f393f3e,0x3f0a3f10,0x3ea53eb4,0x3db83df4,0x3f2e3f34,0x3ef93f03,0x3e883e97,0x3cf53d75,
0x3f3d3f42,0x3f143f1a,0x3ec93ed5,0x3e3f3e5a,0x3f343f39,0x3f093f0f,0x3eaf3ebc,0x3e093e24,0x3f2a3f2f,0x3efa3f03,0x3e953ea2,0x3da53ddb,0x3f1f3f25,0x3ee23eee,0x3e753e88,0x3cdc3d5c,
0x3f2c3f31,0x3f053f0a,0x3eb33ebe,0x3e2a3e42,0x3f233f28,0x3ef53f00,0x3e9c3ea7,0x3df33e12,0x3f193f1e,0x3ee03eea,0x3e843e90,0x3d923dc2,0x3f0f3f14,0x3ec93ed4,0x3e593e71,0x3cc33d43,
0x3f193f1d,0x3eeb3ef4,0x3e9c3ea7,0x3e143e29,0x3f113f15,0x3ed83ee1,0x3e883e92,0x3dd43dfe,0x3f083f0c,0x3ec43ece,0x3e673e7c,0x3d7e3da9,0x3efd3f03,0x3eb13eba,0x3e3e3e53,0x3caa3d2a,
0x3f053f09,0x3eca3ed2,0x3e863e8f,0x3dfc3e10,0x3efb3f01,0x3eb93ec2,0x3e693e7a,0x3db43dd8,0x3eeb3ef3,0x3ea83eb1,0x3e453e57,0x3d593d90,0x3edb3ee3,0x3e973ea0,0x3e223e34,0x3c913d10,
0x3ee03ee6,0x3ea83eaf,0x3e5e3e6d,0x3dd13dee,0x3ed23ed9,0x3e9a3ea1,0x3e413e4f,0x3d953db3,0x3ec43ecb,0x3e8c3e93,0x3e233e32,0x3d333d6f,0x3eb63ebd,0x3e7b3e85,0x3e063e15,0x3c6f3cef,
0x3eb33eb8,0x3e863e8c,0x3e303e3b,0x3da53dbc,0x3ea83ead,0x3e753e80,0x3e193e24,0x3d6b3d8d,0x3e9c3ea2,0x3e5e3e6a,0x3e013e0d,0x3d0d3d3c,0x3e913e97,0x3e473e53,0x3dd43deb,0x3c3c3cbc,
0x3e843e89,0x3e453e4e,0x3e013e0a,0x3d723d8a,0x3e783e80,0x3e343e3d,0x3de03df1,0x3d2d3d4f,0x3e673e70,0x3e233e2c,0x3dbe3dcf,0x3ccf3d0a,0x3e563e5f,0x3e123e1b,0x3d9b3dad,0x3c0a3c8a,
0x3e2a3e2f,0x3dfc3e04,0x3da53db0,0x3d1a3d30,0x3e1f3e24,0x3de63df1,0x3d8f3d9a,0x3cdc3d04,0x3e143e19,0x3dd13ddb,0x3d723d84,0x3c843cb0,0x3e093e0e,0x3dbb3dc6,0x3d463d5c,0x3bb03c30,
0x3d923d97,0x3d593d62,0x3d0d3d17,0x3c843c97,0x3d893d8d,0x3d463d4f,0x3cf53d04,0x3c3c3c62,0x3d7e3d84,0x3d333d3c,0x3ccf3ce2,0x3be23c17,0x3d6b3d75,0x3d203d2a,0x3caa3cbc,0x3b173b97,
0xbcc3bcc9,0xbc91bc97,0xbc3cbc49,0xbbb0bbc9,0xbcb6bcbc,0xbc84bc8a,0xbc23bc30,0xbb7bbb97,0xbcaabcb0,0xbc6fbc7b,0xbc0abc17,0xbb17bb49,0xbc9dbca3,0xbc56bc62,0xbbe2bbfb,0xba49bac9,
0xbdf3bdfb,0xbdb4bdbc,0xbd6bbd7b,0xbcdcbcfb,0xbde3bdeb,0xbda5bdad,0xbd4cbd5c,0xbc9dbcbc,0xbdd4bddb,0xbd95bd9d,0xbd2dbd3c,0xbc3cbc7b,0xbdc4bdcc,0xbd85bd8d,0xbd0dbd1d,0xbb7bbbfb,
0xbe59be60,0xbe22be29,0xbdd4bde2,0xbd46bd62,0xbe4cbe53,0xbe14be1b,0xbdb8bdc6,0xbd0dbd2a,0xbe3ebe45,0xbe06be0d,0xbd9bbda9,0xbcaabce2,0xbe30be37,0xbdf0bdfe,0xbd7ebd8d,0xbbe2bc62,
0xbe9cbea1,0xbe69be73,0xbe19be23,0xbd8fbda3,0xbe92be97,0xbe55be5f,0xbe04be0e,0xbd4cbd75,0xbe88be8d,0xbe41be4b,0xbde0bdf4,0xbcf5bd23,0xbe7dbe83,0xbe2dbe37,0xbdb8bdcc,0xbc23bca3,
0xbec9becf,0xbe97be9e,0xbe47be54,0xbdbbbdd5,0xbebdbec3,0xbe8abe91,0xbe2dbe3a,0xbd85bda0,0xbeb1beb7,0xbe7bbe84,0xbe12be20,0xbd20bd56,0xbea4beaa,0xbe61be6e,0xbdf0be05,0xbc56bcd6,
0xbef5befc,0xbeb9bec1,0xbe75be82,0xbde6be04,0xbee7beee,0xbeaabeb2,0xbe55be65,0xbda5bdc6,0xbed8bedf,0xbe9abea2,0xbe34be45,0xbd46bd84,0xbec9bed0,0xbe8abe92,0xbe14be24,0xbc84bd04,
0xbf0fbf13,0xbedbbee3,0xbe91be9b,0xbe09be1c,0xbf07bf0b,0xbec9bed2,0xbe7dbe88,0xbdc4bdeb,0xbefdbf03,0xbeb6bec0,0xbe56be6a,0xbd6bbd9d,0xbeecbef5,0xbea4bead,0xbe30be43,0xbc9dbd1d,
0xbf23bf27,0xbefbbf02,0xbea8beb2,0xbe1fbe35,0xbf1abf1e,0xbee7bef1,0xbe92be9d,0xbde3be08,0xbf11bf15,0xbed2bedc,0xbe78be87,0xbd89bdb6,0xbf07bf0c,0xbebdbec8,0xbe4cbe62,0xbcb6bd36,
0xbf35bf39,0xbf0dbf12,0xbebebeca,0xbe34be4e,0xbf2bbf30,0xbf02bf07,0xbea5beb2,0xbe01be1b,0xbf22bf27,0xbeedbef8,0xbe8dbe99,0xbd9bbdcf,0xbf17bf1d,0xbed6bee1,0xbe67be80,0xbccfbd4f,
0xbf45bf4a,0xbf1bbf21,0xbed3bee1,0xbe4abe66,0xbf3cbf41,0xbf10bf16,0xbeb9bec6,0xbe11be2e,0xbf32bf37,0xbf03bf0a,0xbe9dbeab,0xbdaebde8,0xbf27bf2c,0xbeeebefa,0xbe81be8f,0xbce8bd68,
0xbf54bf58,0xbf29bf2f,0xbee9bef7,0xbe60be7f,0xbf4abf4f,0xbf1dbf23,0xbeccbeda,0xbe20be40,0xbf40bf45,0xbf10bf17,0xbeaebebd,0xbdc1be00,0xbf35bf3b,0xbf02bf09,0xbe8fbe9e,0xbd01bd81,
0xbf61bf65,0xbf37bf3d,0xbefdbf06,0xbe75be8c,0xbf58bf5c,0xbf2abf30,0xbedebeee,0xbe30be53,0xbf4ebf53,0xbf1cbf23,0xbebebece,0xbdd4be0d,0xbf42bf48,0xbf0ebf15,0xbe9cbead,0xbd0dbd8d,
0xbf6bbf6f,0xbf43bf49,0xbf09bf11,0xbe85be98,0xbf63bf67,0xbf36bf3c,0xbef0bf01,0xbe3fbe65,0xbf59bf5e,0xbf28bf2f,0xbecebedf,0xbde6be19,0xbf4fbf54,0xbf19bf20,0xbeaabebc,0xbd1abd9a,
0xbf74bf77,0xbf4ebf54,0xbf13bf1b,0xbe90bea4,0xbf6dbf70,0xbf41bf48,0xbf01bf0a,0xbe4fbe77,0xbf64bf68,0xbf33bf3a,0xbeddbef0,0xbdf9be26,0xbf5abf5f,0xbf23bf2b,0xbeb7beca,0xbd26bda6,
0xbf7abf7c,0xbf58bf5e,0xbf1cbf25,0xbe9abeaf,0xbf74bf77,0xbf4bbf52,0xbf0abf13,0xbe5ebe85,0xbf6dbf71,0xbf3dbf44,0xbeedbf00,0xbe06be32,0xbf63bf68,0xbf2dbf35,0xbec4bed9,0xbd33bdb3,
0xbf7ebf7f,0xbf61bf67,0xbf25bf2e,0xbea5bebb,0xbf7abf7c,0xbf55bf5b,0xbf12bf1c,0xbe6dbe8e,0xbf74bf77,0xbf47bf4e,0xbefcbf08,0xbe0fbe3f,0xbf6cbf70,0xbf37bf3f,0xbed1bee7,0xbd40bdbf,
0xbd468000,0xbed8bec1,0xbf3bbf33,0xbf6fbf6b,0xbe14bdc6,0xbf02beee,0xbf4bbf44,0xbf77bf73,0xbe75be45,0xbf16bf0c,0xbf59bf53,0xbf7cbf7a,0xbeaabe92,0xbf2abf20,0xbf65bf60,0xbf7fbf7e,
0xbd398000,0xbecbbeb5,0xbf32bf2a,0xbf68bf63,0xbe0bbdb9,0xbef4bee0,0xbf42bf3a,0xbf71bf6c,0xbe66be38,0xbf0ebf04,0xbf50bf49,0xbf77bf74,0xbe9fbe89,0xbf21bf18,0xbf5dbf57,0xbf7cbf7a,
0xbd2d8000,0xbebebeaa,0xbf28bf20,0xbf5fbf59,0xbe01bdad,0xbee5bed2,0xbf38bf30,0xbf69bf64,0xbe56be2c,0xbf05bef8,0xbf46bf3f,0xbf71bf6d,0xbe95be80,0xbf17bf0f,0xbf53bf4d,0xbf77bf74,
0xbd208000,0xbeb1be9e,0xbf1ebf16,0xbf54bf4f,0xbdf0bda0,0xbed6bec3,0xbf2dbf26,0xbf5fbf5a,0xbe47be20,0xbef9bee8,0xbf3bbf34,0xbf68bf64,0xbe8abe6e,0xbf0ebf05,0xbf48bf42,0xbf70bf6c,
0xbd148000,0xbea3be92,0xbf13bf0c,0xbf49bf43,0xbdddbd94,0xbec6beb5,0xbf22bf1b,0xbf54bf4e,0xbe38be13,0xbee7bed7,0xbf30bf29,0xbf5dbf59,0xbe80be5c,0xbf04bef8,0xbf3dbf36,0xbf66bf62,
0xbd078000,0xbe96be86,0xbf08bf01,0xbf3cbf36,0xbdcabd87,0xbeb6bea6,0xbf16bf0f,0xbf47bf42,0xbe28be07,0xbed5bec5,0xbf23bf1d,0xbf51bf4c,0xbe6abe49,0xbef3bee4,0xbf30bf2a,0xbf5abf56,
0xbcf58000,0xbe88be73,0xbef9beec,0xbf2ebf28,0xbdb8bd75,0xbea5be97,0xbf0abf03,0xbf39bf34,0xbe19bdf4,0xbec2beb4,0xbf16bf10,0xbf43bf3e,0xbe55be37,0xbedebed0,0xbf23bf1d,0xbf4dbf48,
0xbcdc8000,0xbe75be5a,0xbee2bed5,0xbf1fbf1a,0xbda5bd5c,0xbe95be88,0xbefabeee,0xbf2abf25,0xbe09bddb,0xbeafbea2,0xbf09bf03,0xbf34bf2f,0xbe3fbe24,0xbec9bebc,0xbf14bf0f,0xbf3dbf39,
0xbcc38000,0xbe59be42,0xbec9bebe,0xbf0fbf0a,0xbd92bd43,0xbe84be71,0xbee0bed4,0xbf19bf14,0xbdf3bdc2,0xbe9cbe90,0xbef5beea,0xbf23bf1e,0xbe2abe12,0xbeb3bea7,0xbf05bf00,0xbf2cbf28,
0xbcaa8000,0xbe3ebe29,0xbeb1bea7,0xbefdbef4,0xbd7ebd2a,0xbe67be53,0xbec4beba,0xbf08bf03,0xbdd4bda9,0xbe88be7c,0xbed8bece,0xbf11bf0c,0xbe14bdfe,0xbe9cbe92,0xbeebbee1,0xbf19bf15,
0xbc918000,0xbe22be10,0xbe97be8f,0xbedbbed2,0xbd59bd10,0xbe45be34,0xbea8bea0,0xbeebbee3,0xbdb4bd90,0xbe69be57,0xbeb9beb1,0xbefbbef3,0xbdfcbdd8,0xbe86be7a,0xbecabec2,0xbf05bf01,
0xbc6f8000,0xbe06bdee,0xbe7bbe6d,0xbeb6beaf,0xbd33bcef,0xbe23be15,0xbe8cbe85,0xbec4bebd,0xbd95bd6f,0xbe41be32,0xbe9abe93,0xbed2becb,0xbdd1bdb3,0xbe5ebe4f,0xbea8bea1,0xbee0bed9,
0xbc3c8000,0xbdd4bdbc,0xbe47be3b,0xbe91be8c,0xbd0dbcbc,0xbe01bdeb,0xbe5ebe53,0xbe9cbe97,0xbd6bbd3c,0xbe19be0d,0xbe75be6a,0xbea8bea2,0xbda5bd8d,0xbe30be24,0xbe86be80,0xbeb3bead,
0xbc0a8000,0xbd9bbd8a,0xbe12be0a,0xbe56be4e,0xbccfbc8a,0xbdbebdad,0xbe23be1b,0xbe67be5f,0xbd2dbd0a,0xbde0bdcf,0xbe34be2c,0xbe78be70,0xbd72bd4f,0xbe01bdf1,0xbe45be3d,0xbe84be80,
0xbbb08000,0xbd46bd30,0xbdbbbdb0,0xbe09be04,0xbc84bc30,0xbd72bd5c,0xbdd1bdc6,0xbe14be0e,0xbcdcbcb0,0xbd8fbd84,0xbde6bddb,0xbe1fbe19,0xbd1abd04,0xbda5bd9a,0xbdfcbdf1,0xbe2abe24,
0xbb178000,0xbcaabc97,0xbd20bd17,0xbd6bbd62,0xbbe2bb97,0xbccfbcbc,0xbd33bd2a,0xbd7ebd75,0xbc3cbc17,0xbcf5bce2,0xbd46bd3c,0xbd89bd84,0xbc84bc62,0xbd0dbd04,0xbd59bd4f,0xbd92bd8d,
0x3a490000,0x3be23bc9,0x3c563c49,0x3c9d3c97,0x3b173ac9,0x3c0a3bfb,0x3c6f3c62,0x3caa3ca3,0x3b7b3b49,0x3c233c17,0x3c843c7b,0x3cb63cb0,0x3bb03b97,0x3c3c3c30,0x3c913c8a,0x3cc33cbc,
0x3b7b0000,0x3d0d3cfb,0x3d853d7b,0x3dc43dbc,0x3c3c3bfb,0x3d2d3d1d,0x3d953d8d,0x3dd43dcc,0x3c9d3c7b,0x3d4c3d3c,0x3da53d9d,0x3de33ddb,0x3cdc3cbc,0x3d6b3d5c,0x3db43dad,0x3df33deb,
0x3be20000,0x3d7e3d62,0x3df03de2,0x3e303e29,0x3caa3c62,0x3d9b3d8d,0x3e063dfe,0x3e3e3e37,0x3d0d3ce2,0x3db83da9,0x3e143e0d,0x3e4c3e45,0x3d463d2a,0x3dd43dc6,0x3e223e1b,0x3e593e53,
0x3c230000,0x3db83da3,0x3e2d3e23,0x3e7d3e73,0x3cf53ca3,0x3de03dcc,0x3e413e37,0x3e883e83,0x3d4c3d23,0x3e043df4,0x3e553e4b,0x3e923e8d,0x3d8f3d75,0x3e193e0e,0x3e693e5f,0x3e9c3e97,
0x3c560000,0x3df03dd5,0x3e613e54,0x3ea43e9e,0x3d203cd6,0x3e123e05,0x3e7b3e6e,0x3eb13eaa,0x3d853d56,0x3e2d3e20,0x3e8a3e84,0x3ebd3eb7,0x3dbb3da0,0x3e473e3a,0x3e973e91,0x3ec93ec3,
0x3c840000,0x3e143e04,0x3e8a3e82,0x3ec93ec1,0x3d463d04,0x3e343e24,0x3e9a3e92,0x3ed83ed0,0x3da53d84,0x3e553e45,0x3eaa3ea2,0x3ee73edf,0x3de63dc6,0x3e753e65,0x3eb93eb2,0x3ef53eee,
0x3c9d0000,0x3e303e1c,0x3ea43e9b,0x3eec3ee3,0x3d6b3d1d,0x3e563e43,0x3eb63ead,0x3efd3ef5,0x3dc43d9d,0x3e7d3e6a,0x3ec93ec0,0x3f073f03,0x3e093deb,0x3e913e88,0x3edb3ed2,0x3f0f3f0b,
0x3cb60000,0x3e4c3e35,0x3ebd3eb2,0x3f073f02,0x3d893d36,0x3e783e62,0x3ed23ec8,0x3f113f0c,0x3de33db6,0x3e923e87,0x3ee73edc,0x3f1a3f15,0x3e1f3e08,0x3ea83e9d,0x3efb3ef1,0x3f233f1e,
0x3ccf0000,0x3e673e4e,0x3ed63eca,0x3f173f12,0x3d9b3d4f,0x3e8d3e80,0x3eed3ee1,0x3f223f1d,0x3e013dcf,0x3ea53e99,0x3f023ef8,0x3f2b3f27,0x3e343e1b,0x3ebe3eb2,0x3f0d3f07,0x3f353f30,
0x3ce80000,0x3e813e66,0x3eee3ee1,0x3f273f21,0x3dae3d68,0x3e9d3e8f,0x3f033efa,0x3f323f2c,0x3e113de8,0x3eb93eab,0x3f103f0a,0x3f3c3f37,0x3e4a3e2e,0x3ed33ec6,0x3f1b3f16,0x3f453f41,
0x3d010000,0x3e8f3e7f,0x3f023ef7,0x3f353f2f,0x3dc13d81,0x3eae3e9e,0x3f103f09,0x3f403f3b,0x3e203e00,0x3ecc3ebd,0x3f1d3f17,0x3f4a3f45,0x3e603e40,0x3ee93eda,0x3f293f23,0x3f543f4f,
0x3d0d0000,0x3e9c3e8c,0x3f0e3f06,0x3f423f3d,0x3dd43d8d,0x3ebe3ead,0x3f1c3f15,0x3f4e3f48,0x3e303e0d,0x3ede3ece,0x3f2a3f23,0x3f583f53,0x3e753e53,0x3efd3eee,0x3f373f30,0x3f613f5c,
0x3d1a0000,0x3eaa3e98,0x3f193f11,0x3f4f3f49,0x3de63d9a,0x3ece3ebc,0x3f283f20,0x3f593f54,0x3e3f3e19,0x3ef03edf,0x3f363f2f,0x3f633f5e,0x3e853e65,0x3f093f01,0x3f433f3c,0x3f6b3f67,
0x3d260000,0x3eb73ea4,0x3f233f1b,0x3f5a3f54,0x3df93da6,0x3edd3eca,0x3f333f2b,0x3f643f5f,0x3e4f3e26,0x3f013ef0,0x3f413f3a,0x3f6d3f68,0x3e903e77,0x3f133f0a,0x3f4e3f48,0x3f743f70,
0x3d330000,0x3ec43eaf,0x3f2d3f25,0x3f633f5e,0x3e063db3,0x3eed3ed9,0x3f3d3f35,0x3f6d3f68,0x3e5e3e32,0x3f0a3f00,0x3f4b3f44,0x3f743f71,0x3e9a3e85,0x3f1c3f13,0x3f583f52,0x3f7a3f77,
0x3d400000,0x3ed13ebb,0x3f373f2e,0x3f6c3f67,0x3e0f3dbf,0x3efc3ee7,0x3f473f3f,0x3f743f70,0x3e6d3e3f,0x3f123f08,0x3f553f4e,0x3f7a3f77,0x3ea53e8e,0x3f253f1c,0x3f613f5b,0x3f7e3f7c
};
#define DBG_END(z)
#define TS(i)
#define TZ(z, i)

struct Params {
  alignas(64) CUtensorMap x_g1, w1_a, w1_b2, w1_b1, k, v, w1_cs, kvz, h_st, h_st2, w2, h_ld, y_ld, x_ep, out_st, f_ld, y_st;
  const bf16 *x, *shift_k, *ssm_k, *ssm_D, *b1, *b2, *w2p, *w1p;
  bf16* kvZ;
  const uint32_t* tab;
  uint2 *stats, *cs;
  unsigned* flags;
  unsigned zero;
  unsigned char cnt[64];
  uchar4 map[NCTA];
};

constexpr int G1_W = 28672, G1_X = 16384, G1_NST = 4, OFF_X = G1_NST * G1_W;
constexpr int G2_STAGE = G1_W, G2_B = 16384, G2_NST = 6;
constexpr int CS_STAGE = 57344;
constexpr int RING = G1_NST * (G1_W + G1_X);
constexpr int OFF_C = RING;
constexpr int OFF_SR = OFF_C;
constexpr int OFF_DFT = OFF_C, OFF_G = OFF_C + 8192;
constexpr int KV_SLOT = 35 * 256, KV_V = 19 * 256;
constexpr int OFF_KVS = OFF_C + 20480, OFF_KV = OFF_KVS + 4096;
constexpr int OFF_T0 = OFF_C + 12288, OFF_T1 = OFF_C + 34816, OFF_T2 = OFF_C + 20480, OFF_T3 = OFF_X + 57344;
constexpr int OFF_Y0 = OFF_C + 28672;
constexpr int OFF_XT = OFF_C + 20480, XT_STEP = 13312, OFF_YT = OFF_C;
constexpr int OFF_EXT = 224256;
constexpr int OFF_ST1 = OFF_EXT + 3584;
constexpr int OFF_ST2 = OFF_ST1 + 2048;
constexpr int OFF_MISC = OFF_ST2 + 800;
constexpr int OFF_BAR = OFF_MISC + 32;
enum { B_FULL1 = 0  , B_KV = 4  , B_STAT = 6, B_FIRST = 7, B_EMPTY1 = 7  , B_FULL2 = 11  , B_EMPTY2 = 17  , B_G1FREE = 23, B_CX = 24  , B_RD = 29  ,
       B_EPOCH = 34, B_SKEW = 35, B_TAB = 36, B_EP = 37, B_EPY = 38, B_KVS = 39  , B_GO = 42, B_DONE = 43, B_STATFREE = 44, B_HS = 45  ,
       B_KVR = 53, B_LATE = 54, B_DFT = 55, B_HB = 56, B_H1 = 57, B_VD = 58, B_RT = 59, B_KVB = 60, B_KVC = 61, B_DBG = 62, B_COUNT = 64 };
constexpr int OFF_DBG = OFF_BAR + B_COUNT * 8;
constexpr int SMEM_BYTES = OFF_DBG + (DBG_TIME ? 768 : 0);
static_assert(SMEM_BYTES <= 232448, "smem");
static_assert(OFF_XT + XT_STEP + 10240 <= OFF_EXT && OFF_KV + 2 * KV_SLOT <= OFF_EXT && OFF_T1 + 8192 <= OFF_EXT && OFF_T1 >= OFF_KV + KV_SLOT && OFF_T2 + 8192 <= OFF_KV + KV_SLOT, "layout");
static_assert(OFF_EXT % 1024 == 0 && OFF_XT % 1024 == 0 && XT_STEP % 1024 == 0 && OFF_T1 % 1024 == 0 && 5 * G2_STAGE + 26624 <= OFF_T3 && 3 * CS_STAGE <= RING, "layout");

#define DEV __device__ __forceinline__
#define HD __host__ __device__ constexpr
DEV uint32_t smem_u32(const void* p) { return (uint32_t)__cvta_generic_to_shared(p); }
DEV uint64_t make_desc(uint32_t addr, uint32_t lbo, uint32_t sbo, uint32_t swz) {
  uint64_t d;
  asm volatile("mov.b64 %0, {%1, %2};" : "=l"(d) : "r"(((addr & 0x3FFFF) >> 4) | ((lbo >> 4) << 16)), "r"((sbo >> 4) | (swz << 30)));
  return d;
}
DEV void wg_fence() { asm volatile("wgmma.fence.sync.aligned;" ::: "memory"); }
DEV void wg_commit() { asm volatile("wgmma.commit_group.sync.aligned;" ::: "memory"); }
template <int n> DEV void wg_wait() { asm volatile("wgmma.wait_group.sync.aligned %0;" ::"n"(n) : "memory"); }
DEV void mbar_init(uint32_t bar, int cnt) { asm volatile("mbarrier.init.shared::cta.b64 [%0], %1;" ::"r"(bar), "r"(cnt) : "memory"); }
DEV void mbar_expect(uint32_t bar, int bytes) { asm volatile("mbarrier.arrive.expect_tx.shared::cta.b64 _, [%0], %1;" ::"r"(bar), "r"(bytes) : "memory"); }
DEV void mbar_arrive(uint32_t bar) { asm volatile("mbarrier.arrive.shared::cta.b64 _, [%0];" ::"r"(bar) : "memory"); }
DEV void mbar_wait(uint32_t bar, uint32_t parity) {
  asm volatile("{\n.reg .pred p;\nW: mbarrier.try_wait.parity.shared::cta.b64 p, [%0], %1;\n@p bra X;\nbra W;\nX:\n}" ::"r"(bar), "r"(parity) : "memory");
}
DEV void mbar_wait_b(uint32_t bar, uint32_t parity) {
  asm volatile("{\n.reg .pred p;\n.reg .u32 i;\nmov.u32 i, 0;\n"
               "W: mbarrier.try_wait.parity.shared::cta.b64 p, [%0], %1;\n@p bra X;\nadd.u32 i, i, 1;\nsetp.lt.u32 p, i, 262144;\n@p bra W;\ntrap;\nX:\n}"
               ::"r"(bar), "r"(parity) : "memory");
}
DEV void trap_above(int n, int lim) { asm volatile("{\n.reg .pred p;\nsetp.gt.s32 p, %0, %1;\n@p trap;\n}" ::"r"(n), "r"(lim)); }
DEV unsigned flag_load(const unsigned* p) {
  unsigned v;
  asm volatile("ld.acquire.gpu.global.u32 %0, [%1];" : "=r"(v) : "l"(p) : "memory");
  return v;
}
template <bool BOUNDED> DEV void flag_wait(const unsigned* p, unsigned target) {
#pragma unroll 1
  for (int i = 0; !BOUNDED || i < (1 << 22); i++)
    if ((int)(flag_load(p) - target) >= 0) return;
  __trap();
}
DEV void tag_store(uint2* p, float a, float b, unsigned ep) {
  const unsigned long long v = (unsigned long long)__float_as_uint(a) | ((unsigned long long)((__float_as_uint(b) & ~255u) | (ep & 255u)) << 32);
  asm volatile("st.relaxed.gpu.global.u64 [%0], %1;" ::"l"(p), "l"(v) : "memory");
}
DEV uint2 tag_load(const uint2* p) { uint2 v; asm volatile("{\n.reg .b64 t;\nld.relaxed.gpu.global.b64 t, [%2];\nmov.b64 {%0,%1}, t;\n}" : "=r"(v.x), "=r"(v.y) : "l"(p) : "memory"); return v; }
template <int N> DEV void tag_wait(const uint2* const (&p)[N], uint2 (&v)[N], unsigned ep) {
#pragma unroll 1
  for (;;) {
    unsigned bad = 0;
#pragma unroll
    for (int j = 0; j < N; j++) bad |= v[j].y ^ ep;
    if (!__any_sync(0xffffffffu, (bad & 255u) != 0)) break;
#pragma unroll
    for (int j = 0; j < N; j++) v[j] = tag_load(p[j]);
  }
#pragma unroll
  for (int j = 0; j < N; j++) v[j].y &= ~255u;
}
#define REL 4
DEV void pub_fence(int bit) { if (REL & bit) asm volatile("fence.acq_rel.gpu;" ::: "memory"); }
DEV void flag_add_rlx(unsigned* p, unsigned n) { asm volatile("red.relaxed.gpu.global.add.u32 [%0], %1;" ::"l"(p), "r"(n) : "memory"); }
DEV void fence_async_smem() { asm volatile("fence.proxy.async.shared::cta;" ::: "memory"); }
#define RF 15
DEV void wfence(int bit) { if (!(RF & bit)) fence_async_smem(); }
DEV void rfence(int bit) { if ((RF & bit) && !(RF & 16)) fence_async_smem(); }
DEV void fence_async_global() { asm volatile("fence.proxy.async.global;" ::: "memory"); }
DEV void bar_sync(int id) { asm volatile("bar.sync %0, 128;" ::"r"(id) : "memory"); }
DEV bool elect() {
  uint32_t p;
  asm volatile("{\n.reg .pred p;\nelect.sync _|p, 0xffffffff;\nselp.u32 %0, 1, 0, p;\n}" : "=r"(p));
  return p;
}
DEV void warp_arrive(uint32_t bar) { __syncwarp(); if (elect()) mbar_arrive(bar); }
DEV void bulk_g2s(uint32_t dst, const void* src, int bytes, uint32_t bar) {
  asm volatile("cp.async.bulk.shared::cluster.global.mbarrier::complete_tx::bytes [%0], [%1], %2, [%3];" ::"r"(dst), "l"(src), "r"(bytes), "r"(bar) : "memory");
}
DEV void bulk_s2g(void* dst, uint32_t src, int bytes) { asm volatile("cp.async.bulk.global.shared::cta.bulk_group [%0], [%1], %2;" ::"l"(dst), "r"(src), "r"(bytes) : "memory"); }
DEV void bulk_prefetch(const void* src, int bytes) { asm volatile("cp.async.bulk.prefetch.L2.global [%0], %1;" ::"l"(src), "r"(bytes) : "memory"); }
DEV void tma2d(uint32_t dst, const CUtensorMap* m, int c0, int c1, uint32_t bar) {
  asm volatile("cp.async.bulk.tensor.2d.shared::cluster.global.mbarrier::complete_tx::bytes [%0], [%1, {%3, %4}], [%2];" ::"r"(dst), "l"(m), "r"(bar), "r"(c0), "r"(c1) : "memory");
}
DEV void tma3d(uint32_t dst, const CUtensorMap* m, int c0, int c1, int c2, uint32_t bar) {
  asm volatile("cp.async.bulk.tensor.3d.shared::cluster.global.mbarrier::complete_tx::bytes [%0], [%1, {%3, %4, %5}], [%2];" ::"r"(dst), "l"(m), "r"(bar), "r"(c0), "r"(c1), "r"(c2) : "memory");
}
DEV void tma2d_st(const CUtensorMap* m, int c0, int c1, uint32_t src) {
  asm volatile("cp.async.bulk.tensor.2d.global.shared::cta.bulk_group [%0, {%2, %3}], [%1];" ::"l"(m), "r"(src), "r"(c0), "r"(c1) : "memory");
}
DEV void bulk_commit() { asm volatile("cp.async.bulk.commit_group;" ::: "memory"); }
DEV void bulk_wait_read() { asm volatile("cp.async.bulk.wait_group.read 0;" ::: "memory"); }
DEV void bulk_wait_all() { asm volatile("cp.async.bulk.wait_group 0;" ::: "memory"); }
DEV void prefetch_map(const CUtensorMap* m) { asm volatile("prefetch.tensormap [%0];" ::"l"(m) : "memory"); }
DEV uint32_t lds32(uint32_t a) { uint32_t v; asm volatile("ld.shared.b32 %0, [%1];" : "=r"(v) : "r"(a) : "memory"); return v; }
DEV uint2 lds64(uint32_t a) { uint2 v; asm volatile("ld.shared.v2.b32 {%0,%1}, [%2];" : "=r"(v.x), "=r"(v.y) : "r"(a) : "memory"); return v; }
DEV uint4 lds128(uint32_t a) { uint4 v; asm volatile("ld.shared.v4.b32 {%0,%1,%2,%3}, [%4];" : "=r"(v.x), "=r"(v.y), "=r"(v.z), "=r"(v.w) : "r"(a) : "memory"); return v; }
DEV void sts32(uint32_t a, uint32_t v) { asm volatile("st.shared.b32 [%0], %1;" ::"r"(a), "r"(v) : "memory"); }
DEV void sts128(uint32_t a, uint4 v) { asm volatile("st.shared.v4.b32 [%0], {%1,%2,%3,%4};" ::"r"(a), "r"(v.x), "r"(v.y), "r"(v.z), "r"(v.w) : "memory"); }
DEV void stsm4(uint32_t a, uint32_t r0, uint32_t r1, uint32_t r2, uint32_t r3) { asm volatile("stmatrix.sync.aligned.m8n8.x4.shared.b16 [%0], {%1,%2,%3,%4};" ::"r"(a), "r"(r0), "r"(r1), "r"(r2), "r"(r3) : "memory"); }
DEV void stsm4t(uint32_t a, uint32_t r0, uint32_t r1, uint32_t r2, uint32_t r3) { asm volatile("stmatrix.sync.aligned.m8n8.x4.trans.shared.b16 [%0], {%1,%2,%3,%4};" ::"r"(a), "r"(r0), "r"(r1), "r"(r2), "r"(r3) : "memory"); }
DEV void ldsm4(uint32_t a, uint32_t (&r)[4]) { asm volatile("ldmatrix.sync.aligned.m8n8.x4.shared.b16 {%0,%1,%2,%3}, [%4];" : "=r"(r[0]), "=r"(r[1]), "=r"(r[2]), "=r"(r[3]) : "r"(a) : "memory"); }
DEV void ldsm4t(uint32_t a, uint32_t (&r)[4]) { asm volatile("ldmatrix.sync.aligned.m8n8.x4.trans.shared.b16 {%0,%1,%2,%3}, [%4];" : "=r"(r[0]), "=r"(r[1]), "=r"(r[2]), "=r"(r[3]) : "r"(a) : "memory"); }
DEV uint32_t pack2(float lo, float hi) { uint32_t r; asm("cvt.rn.bf16x2.f32 %0, %1, %2;" : "=r"(r) : "f"(hi), "f"(lo)); return r; }
DEV uint32_t pack2v(float lo, float hi) { uint32_t r; asm volatile("cvt.rn.bf16x2.f32 %0, %1, %2;" : "=r"(r) : "f"(hi), "f"(lo)); return r; }
DEV float faddv(float a, float b) { float r; asm volatile("add.rn.f32 %0, %1, %2;" : "=f"(r) : "f"(a), "f"(b)); return r; }
DEV float blo(uint32_t u) { return __uint_as_float(u << 16); }
DEV float bhi(uint32_t u) { return __uint_as_float(u & 0xffff0000u); }
DEV float rcp_fast(float x) { float y; asm("rcp.approx.ftz.f32 %0, %1;" : "=f"(y) : "f"(x)); return y; }
DEV float tanh_fast(float x) { float y; asm("tanh.approx.f32 %0, %1;" : "=f"(y) : "f"(x)); return y; }
DEV uint32_t htanh2(uint32_t a) { uint32_t r; asm("tanh.approx.bf16x2 %0, %1;" : "=r"(r) : "r"(a)); return r; }
DEV uint32_t hadd2(uint32_t a, uint32_t b) { uint32_t r; asm("add.rn.bf16x2 %0, %1, %2;" : "=r"(r) : "r"(a), "r"(b)); return r; }
DEV uint32_t hmul2(uint32_t a, uint32_t b) { uint32_t r; asm("mul.rn.bf16x2 %0, %1, %2;" : "=r"(r) : "r"(a), "r"(b)); return r; }
DEV uint32_t hfma2(uint32_t a, uint32_t b, uint32_t c) { uint32_t r; asm("fma.rn.bf16x2 %0, %1, %2, %3;" : "=r"(r) : "r"(a), "r"(b), "r"(c)); return r; }
DEV uint32_t hfma2v(uint32_t a, uint32_t b, uint32_t c) { uint32_t r; asm volatile("fma.rn.bf16x2 %0, %1, %2, %3;" : "=r"(r) : "r"(a), "r"(b), "r"(c)); return r; }
DEV uint32_t hfms2(uint32_t a, uint32_t b, uint32_t c) { uint32_t r; asm("{\n.reg .b32 t;\nmul.bf16x2 t, %1, %2;\nsub.bf16x2 %0, %3, t;\n}" : "=r"(r) : "r"(a), "r"(b), "r"(c)); return r; }
DEV uint4 ldg128(const void* p) { uint4 v; asm volatile("ld.global.nc.v4.b32 {%0,%1,%2,%3}, [%4];" : "=r"(v.x), "=r"(v.y), "=r"(v.z), "=r"(v.w) : "l"(p)); return v; }
DEV uint32_t ldg32(const void* p) { uint32_t v; asm volatile("ld.global.nc.b32 %0, [%1];" : "=r"(v) : "l"(p)); return v; }
DEV float ldg_bf16(const bf16* p) { unsigned short v; asm volatile("ld.global.nc.u16 %0, [%1];" : "=h"(v) : "l"(p)); return __uint_as_float((uint32_t)v << 16); }
DEV float bf_round(float v) { return __bfloat162float(__float2bfloat16(v)); }
DEV uint32_t gelu2(float a, float b, float c1, float c2) {
  const uint32_t p = pack2(a, b);
  return hfma2(p, htanh2(hmul2(p, hfma2(hmul2(p, p), __float_as_uint(c2), __float_as_uint(c1)))), p);
}

DEV void wgmma_ssp_80_10(float* d, uint64_t da, uint64_t db, int keep) {
  asm volatile("{\n.reg .pred p;\nsetp.ne.b32 p, %42, 0;\nwgmma.mma_async.sync.aligned.m64n80k16.f32.bf16.bf16 {%0, %1, %2, %3, %4, %5, %6, %7, %8, %9, %10, %11, %12, %13, %14, %15, %16, %17, %18, %19, %20, %21, %22, %23, %24, %25, %26, %27, %28, %29, %30, %31, %32, %33, %34, %35, %36, %37, %38, %39}, %40, %41, p, 1, 1, 1, 0;\n}\n"
    : "+f"(d[0]), "+f"(d[1]), "+f"(d[2]), "+f"(d[3]), "+f"(d[4]), "+f"(d[5]), "+f"(d[6]), "+f"(d[7]), "+f"(d[8]), "+f"(d[9]), "+f"(d[10]), "+f"(d[11]), "+f"(d[12]), "+f"(d[13]), "+f"(d[14]), "+f"(d[15]), "+f"(d[16]), "+f"(d[17]), "+f"(d[18]), "+f"(d[19]), "+f"(d[20]), "+f"(d[21]), "+f"(d[22]), "+f"(d[23]), "+f"(d[24]), "+f"(d[25]), "+f"(d[26]), "+f"(d[27]), "+f"(d[28]), "+f"(d[29]), "+f"(d[30]), "+f"(d[31]), "+f"(d[32]), "+f"(d[33]), "+f"(d[34]), "+f"(d[35]), "+f"(d[36]), "+f"(d[37]), "+f"(d[38]), "+f"(d[39])
    : "l"(da), "l"(db), "r"(keep));
}
DEV void wgmma_ss_128_01(float* d, uint64_t da, uint64_t db) {
  asm volatile("{\n.reg .pred p;\nsetp.ne.b32 p, 1, 0;\nwgmma.mma_async.sync.aligned.m64n128k16.f32.bf16.bf16 {%0, %1, %2, %3, %4, %5, %6, %7, %8, %9, %10, %11, %12, %13, %14, %15, %16, %17, %18, %19, %20, %21, %22, %23, %24, %25, %26, %27, %28, %29, %30, %31, %32, %33, %34, %35, %36, %37, %38, %39, %40, %41, %42, %43, %44, %45, %46, %47, %48, %49, %50, %51, %52, %53, %54, %55, %56, %57, %58, %59, %60, %61, %62, %63}, %64, %65, p, 1, 1, 0, 1;\n}\n"
    : "+f"(d[0]), "+f"(d[1]), "+f"(d[2]), "+f"(d[3]), "+f"(d[4]), "+f"(d[5]), "+f"(d[6]), "+f"(d[7]), "+f"(d[8]), "+f"(d[9]), "+f"(d[10]), "+f"(d[11]), "+f"(d[12]), "+f"(d[13]), "+f"(d[14]), "+f"(d[15]), "+f"(d[16]), "+f"(d[17]), "+f"(d[18]), "+f"(d[19]), "+f"(d[20]), "+f"(d[21]), "+f"(d[22]), "+f"(d[23]), "+f"(d[24]), "+f"(d[25]), "+f"(d[26]), "+f"(d[27]), "+f"(d[28]), "+f"(d[29]), "+f"(d[30]), "+f"(d[31]), "+f"(d[32]), "+f"(d[33]), "+f"(d[34]), "+f"(d[35]), "+f"(d[36]), "+f"(d[37]), "+f"(d[38]), "+f"(d[39]), "+f"(d[40]), "+f"(d[41]), "+f"(d[42]), "+f"(d[43]), "+f"(d[44]), "+f"(d[45]), "+f"(d[46]), "+f"(d[47]), "+f"(d[48]), "+f"(d[49]), "+f"(d[50]), "+f"(d[51]), "+f"(d[52]), "+f"(d[53]), "+f"(d[54]), "+f"(d[55]), "+f"(d[56]), "+f"(d[57]), "+f"(d[58]), "+f"(d[59]), "+f"(d[60]), "+f"(d[61]), "+f"(d[62]), "+f"(d[63])
    : "l"(da), "l"(db));
}
DEV void wgmma_ss_96_01(float* d, uint64_t da, uint64_t db) {
  asm volatile("{\n.reg .pred p;\nsetp.ne.b32 p, 1, 0;\nwgmma.mma_async.sync.aligned.m64n96k16.f32.bf16.bf16 {%0, %1, %2, %3, %4, %5, %6, %7, %8, %9, %10, %11, %12, %13, %14, %15, %16, %17, %18, %19, %20, %21, %22, %23, %24, %25, %26, %27, %28, %29, %30, %31, %32, %33, %34, %35, %36, %37, %38, %39, %40, %41, %42, %43, %44, %45, %46, %47}, %48, %49, p, 1, 1, 0, 1;\n}\n"
    : "+f"(d[0]), "+f"(d[1]), "+f"(d[2]), "+f"(d[3]), "+f"(d[4]), "+f"(d[5]), "+f"(d[6]), "+f"(d[7]), "+f"(d[8]), "+f"(d[9]), "+f"(d[10]), "+f"(d[11]), "+f"(d[12]), "+f"(d[13]), "+f"(d[14]), "+f"(d[15]), "+f"(d[16]), "+f"(d[17]), "+f"(d[18]), "+f"(d[19]), "+f"(d[20]), "+f"(d[21]), "+f"(d[22]), "+f"(d[23]), "+f"(d[24]), "+f"(d[25]), "+f"(d[26]), "+f"(d[27]), "+f"(d[28]), "+f"(d[29]), "+f"(d[30]), "+f"(d[31]), "+f"(d[32]), "+f"(d[33]), "+f"(d[34]), "+f"(d[35]), "+f"(d[36]), "+f"(d[37]), "+f"(d[38]), "+f"(d[39]), "+f"(d[40]), "+f"(d[41]), "+f"(d[42]), "+f"(d[43]), "+f"(d[44]), "+f"(d[45]), "+f"(d[46]), "+f"(d[47])
    : "l"(da), "l"(db));
}
DEV void wgmma_ss_80_10(float* d, uint64_t da, uint64_t db) {
  asm volatile("{\n.reg .pred p;\nsetp.ne.b32 p, 1, 0;\nwgmma.mma_async.sync.aligned.m64n80k16.f32.bf16.bf16 {%0, %1, %2, %3, %4, %5, %6, %7, %8, %9, %10, %11, %12, %13, %14, %15, %16, %17, %18, %19, %20, %21, %22, %23, %24, %25, %26, %27, %28, %29, %30, %31, %32, %33, %34, %35, %36, %37, %38, %39}, %40, %41, p, 1, 1, 1, 0;\n}\n"
    : "+f"(d[0]), "+f"(d[1]), "+f"(d[2]), "+f"(d[3]), "+f"(d[4]), "+f"(d[5]), "+f"(d[6]), "+f"(d[7]), "+f"(d[8]), "+f"(d[9]), "+f"(d[10]), "+f"(d[11]), "+f"(d[12]), "+f"(d[13]), "+f"(d[14]), "+f"(d[15]), "+f"(d[16]), "+f"(d[17]), "+f"(d[18]), "+f"(d[19]), "+f"(d[20]), "+f"(d[21]), "+f"(d[22]), "+f"(d[23]), "+f"(d[24]), "+f"(d[25]), "+f"(d[26]), "+f"(d[27]), "+f"(d[28]), "+f"(d[29]), "+f"(d[30]), "+f"(d[31]), "+f"(d[32]), "+f"(d[33]), "+f"(d[34]), "+f"(d[35]), "+f"(d[36]), "+f"(d[37]), "+f"(d[38]), "+f"(d[39])
    : "l"(da), "l"(db));
}
DEV void wgmma_ss_8_10(float* d, uint64_t da, uint64_t db) {
  asm volatile("{\n.reg .pred p;\nsetp.ne.b32 p, 1, 0;\nwgmma.mma_async.sync.aligned.m64n8k16.f32.bf16.bf16 {%0, %1, %2, %3}, %4, %5, p, 1, 1, 1, 0;\n}\n"
    : "+f"(d[0]), "+f"(d[1]), "+f"(d[2]), "+f"(d[3])
    : "l"(da), "l"(db));
}
DEV void wgmma_ss_32_10(float* d, uint64_t da, uint64_t db) {
  asm volatile("{\n.reg .pred p;\nsetp.ne.b32 p, 1, 0;\nwgmma.mma_async.sync.aligned.m64n32k16.f32.bf16.bf16 {%0, %1, %2, %3, %4, %5, %6, %7, %8, %9, %10, %11, %12, %13, %14, %15}, %16, %17, p, 1, 1, 1, 0;\n}\n"
    : "+f"(d[0]), "+f"(d[1]), "+f"(d[2]), "+f"(d[3]), "+f"(d[4]), "+f"(d[5]), "+f"(d[6]), "+f"(d[7]), "+f"(d[8]), "+f"(d[9]), "+f"(d[10]), "+f"(d[11]), "+f"(d[12]), "+f"(d[13]), "+f"(d[14]), "+f"(d[15])
    : "l"(da), "l"(db));
}
DEV void wgmma_ssz_32_10(float* d, uint64_t da, uint64_t db) {
  asm volatile("{\n.reg .pred p;\nsetp.ne.b32 p, 0, 0;\nwgmma.mma_async.sync.aligned.m64n32k16.f32.bf16.bf16 {%0, %1, %2, %3, %4, %5, %6, %7, %8, %9, %10, %11, %12, %13, %14, %15}, %16, %17, p, 1, 1, 1, 0;\n}\n"
    : "=f"(d[0]), "=f"(d[1]), "=f"(d[2]), "=f"(d[3]), "=f"(d[4]), "=f"(d[5]), "=f"(d[6]), "=f"(d[7]), "=f"(d[8]), "=f"(d[9]), "=f"(d[10]), "=f"(d[11]), "=f"(d[12]), "=f"(d[13]), "=f"(d[14]), "=f"(d[15])
    : "l"(da), "l"(db));
}
DEV void wgmma_rs_64_0(float* d, const uint32_t* a, uint64_t db) {
  asm volatile("{\n.reg .pred p;\nsetp.ne.b32 p, 1, 0;\nwgmma.mma_async.sync.aligned.m64n64k16.f32.bf16.bf16 {%0, %1, %2, %3, %4, %5, %6, %7, %8, %9, %10, %11, %12, %13, %14, %15, %16, %17, %18, %19, %20, %21, %22, %23, %24, %25, %26, %27, %28, %29, %30, %31}, {%32, %33, %34, %35}, %36, p, 1, 1, 0;\n}\n"
    : "+f"(d[0]), "+f"(d[1]), "+f"(d[2]), "+f"(d[3]), "+f"(d[4]), "+f"(d[5]), "+f"(d[6]), "+f"(d[7]), "+f"(d[8]), "+f"(d[9]), "+f"(d[10]), "+f"(d[11]), "+f"(d[12]), "+f"(d[13]), "+f"(d[14]), "+f"(d[15]), "+f"(d[16]), "+f"(d[17]), "+f"(d[18]), "+f"(d[19]), "+f"(d[20]), "+f"(d[21]), "+f"(d[22]), "+f"(d[23]), "+f"(d[24]), "+f"(d[25]), "+f"(d[26]), "+f"(d[27]), "+f"(d[28]), "+f"(d[29]), "+f"(d[30]), "+f"(d[31])
    : "r"(a[0]), "r"(a[1]), "r"(a[2]), "r"(a[3]), "l"(db));
}
DEV void wgmma_rsz_64_0(float* d, const uint32_t* a, uint64_t db) {
  asm volatile("{\n.reg .pred p;\nsetp.ne.b32 p, 0, 0;\nwgmma.mma_async.sync.aligned.m64n64k16.f32.bf16.bf16 {%0, %1, %2, %3, %4, %5, %6, %7, %8, %9, %10, %11, %12, %13, %14, %15, %16, %17, %18, %19, %20, %21, %22, %23, %24, %25, %26, %27, %28, %29, %30, %31}, {%32, %33, %34, %35}, %36, p, 1, 1, 0;\n}\n"
    : "=f"(d[0]), "=f"(d[1]), "=f"(d[2]), "=f"(d[3]), "=f"(d[4]), "=f"(d[5]), "=f"(d[6]), "=f"(d[7]), "=f"(d[8]), "=f"(d[9]), "=f"(d[10]), "=f"(d[11]), "=f"(d[12]), "=f"(d[13]), "=f"(d[14]), "=f"(d[15]), "=f"(d[16]), "=f"(d[17]), "=f"(d[18]), "=f"(d[19]), "=f"(d[20]), "=f"(d[21]), "=f"(d[22]), "=f"(d[23]), "=f"(d[24]), "=f"(d[25]), "=f"(d[26]), "=f"(d[27]), "=f"(d[28]), "=f"(d[29]), "=f"(d[30]), "=f"(d[31])
    : "r"(a[0]), "r"(a[1]), "r"(a[2]), "r"(a[3]), "l"(db));
}
DEV void wgmma_rs_64_1(float* d, const uint32_t* a, uint64_t db) {
  asm volatile("{\n.reg .pred p;\nsetp.ne.b32 p, 1, 0;\nwgmma.mma_async.sync.aligned.m64n64k16.f32.bf16.bf16 {%0, %1, %2, %3, %4, %5, %6, %7, %8, %9, %10, %11, %12, %13, %14, %15, %16, %17, %18, %19, %20, %21, %22, %23, %24, %25, %26, %27, %28, %29, %30, %31}, {%32, %33, %34, %35}, %36, p, 1, 1, 1;\n}\n"
    : "+f"(d[0]), "+f"(d[1]), "+f"(d[2]), "+f"(d[3]), "+f"(d[4]), "+f"(d[5]), "+f"(d[6]), "+f"(d[7]), "+f"(d[8]), "+f"(d[9]), "+f"(d[10]), "+f"(d[11]), "+f"(d[12]), "+f"(d[13]), "+f"(d[14]), "+f"(d[15]), "+f"(d[16]), "+f"(d[17]), "+f"(d[18]), "+f"(d[19]), "+f"(d[20]), "+f"(d[21]), "+f"(d[22]), "+f"(d[23]), "+f"(d[24]), "+f"(d[25]), "+f"(d[26]), "+f"(d[27]), "+f"(d[28]), "+f"(d[29]), "+f"(d[30]), "+f"(d[31])
    : "r"(a[0]), "r"(a[1]), "r"(a[2]), "r"(a[3]), "l"(db));
}
DEV void wgmma_rsz_64_1(float* d, const uint32_t* a, uint64_t db) {
  asm volatile("{\n.reg .pred p;\nsetp.ne.b32 p, 0, 0;\nwgmma.mma_async.sync.aligned.m64n64k16.f32.bf16.bf16 {%0, %1, %2, %3, %4, %5, %6, %7, %8, %9, %10, %11, %12, %13, %14, %15, %16, %17, %18, %19, %20, %21, %22, %23, %24, %25, %26, %27, %28, %29, %30, %31}, {%32, %33, %34, %35}, %36, p, 1, 1, 1;\n}\n"
    : "=f"(d[0]), "=f"(d[1]), "=f"(d[2]), "=f"(d[3]), "=f"(d[4]), "=f"(d[5]), "=f"(d[6]), "=f"(d[7]), "=f"(d[8]), "=f"(d[9]), "=f"(d[10]), "=f"(d[11]), "=f"(d[12]), "=f"(d[13]), "=f"(d[14]), "=f"(d[15]), "=f"(d[16]), "=f"(d[17]), "=f"(d[18]), "=f"(d[19]), "=f"(d[20]), "=f"(d[21]), "=f"(d[22]), "=f"(d[23]), "=f"(d[24]), "=f"(d[25]), "=f"(d[26]), "=f"(d[27]), "=f"(d[28]), "=f"(d[29]), "=f"(d[30]), "=f"(d[31])
    : "r"(a[0]), "r"(a[1]), "r"(a[2]), "r"(a[3]), "l"(db));
}
DEV void wgmma_rs_128_1(float* d, const uint32_t* a, uint64_t db) {
  asm volatile("{\n.reg .pred p;\nsetp.ne.b32 p, 1, 0;\nwgmma.mma_async.sync.aligned.m64n128k16.f32.bf16.bf16 {%0, %1, %2, %3, %4, %5, %6, %7, %8, %9, %10, %11, %12, %13, %14, %15, %16, %17, %18, %19, %20, %21, %22, %23, %24, %25, %26, %27, %28, %29, %30, %31, %32, %33, %34, %35, %36, %37, %38, %39, %40, %41, %42, %43, %44, %45, %46, %47, %48, %49, %50, %51, %52, %53, %54, %55, %56, %57, %58, %59, %60, %61, %62, %63}, {%64, %65, %66, %67}, %68, p, 1, 1, 1;\n}\n"
    : "+f"(d[0]), "+f"(d[1]), "+f"(d[2]), "+f"(d[3]), "+f"(d[4]), "+f"(d[5]), "+f"(d[6]), "+f"(d[7]), "+f"(d[8]), "+f"(d[9]), "+f"(d[10]), "+f"(d[11]), "+f"(d[12]), "+f"(d[13]), "+f"(d[14]), "+f"(d[15]), "+f"(d[16]), "+f"(d[17]), "+f"(d[18]), "+f"(d[19]), "+f"(d[20]), "+f"(d[21]), "+f"(d[22]), "+f"(d[23]), "+f"(d[24]), "+f"(d[25]), "+f"(d[26]), "+f"(d[27]), "+f"(d[28]), "+f"(d[29]), "+f"(d[30]), "+f"(d[31]), "+f"(d[32]), "+f"(d[33]), "+f"(d[34]), "+f"(d[35]), "+f"(d[36]), "+f"(d[37]), "+f"(d[38]), "+f"(d[39]), "+f"(d[40]), "+f"(d[41]), "+f"(d[42]), "+f"(d[43]), "+f"(d[44]), "+f"(d[45]), "+f"(d[46]), "+f"(d[47]), "+f"(d[48]), "+f"(d[49]), "+f"(d[50]), "+f"(d[51]), "+f"(d[52]), "+f"(d[53]), "+f"(d[54]), "+f"(d[55]), "+f"(d[56]), "+f"(d[57]), "+f"(d[58]), "+f"(d[59]), "+f"(d[60]), "+f"(d[61]), "+f"(d[62]), "+f"(d[63])
    : "r"(a[0]), "r"(a[1]), "r"(a[2]), "r"(a[3]), "l"(db));
}
DEV void wgmma_rs_96_1(float* d, const uint32_t* a, uint64_t db) {
  asm volatile("{\n.reg .pred p;\nsetp.ne.b32 p, 1, 0;\nwgmma.mma_async.sync.aligned.m64n96k16.f32.bf16.bf16 {%0, %1, %2, %3, %4, %5, %6, %7, %8, %9, %10, %11, %12, %13, %14, %15, %16, %17, %18, %19, %20, %21, %22, %23, %24, %25, %26, %27, %28, %29, %30, %31, %32, %33, %34, %35, %36, %37, %38, %39, %40, %41, %42, %43, %44, %45, %46, %47}, {%48, %49, %50, %51}, %52, p, 1, 1, 1;\n}\n"
    : "+f"(d[0]), "+f"(d[1]), "+f"(d[2]), "+f"(d[3]), "+f"(d[4]), "+f"(d[5]), "+f"(d[6]), "+f"(d[7]), "+f"(d[8]), "+f"(d[9]), "+f"(d[10]), "+f"(d[11]), "+f"(d[12]), "+f"(d[13]), "+f"(d[14]), "+f"(d[15]), "+f"(d[16]), "+f"(d[17]), "+f"(d[18]), "+f"(d[19]), "+f"(d[20]), "+f"(d[21]), "+f"(d[22]), "+f"(d[23]), "+f"(d[24]), "+f"(d[25]), "+f"(d[26]), "+f"(d[27]), "+f"(d[28]), "+f"(d[29]), "+f"(d[30]), "+f"(d[31]), "+f"(d[32]), "+f"(d[33]), "+f"(d[34]), "+f"(d[35]), "+f"(d[36]), "+f"(d[37]), "+f"(d[38]), "+f"(d[39]), "+f"(d[40]), "+f"(d[41]), "+f"(d[42]), "+f"(d[43]), "+f"(d[44]), "+f"(d[45]), "+f"(d[46]), "+f"(d[47])
    : "r"(a[0]), "r"(a[1]), "r"(a[2]), "r"(a[3]), "l"(db));
}

struct Dft { uint32_t E[8], tt[8], ts[8]; };
DEV void dft_load(Dft& k, const uint32_t* tab, int tid) {
#pragma unroll
  for (int q = 0; q < 6; q++) {
    const uint4 v = ldg128(tab + 3072 + 512 * q + 4 * tid);
    uint32_t* d = (q < 2 ? k.E : q < 4 ? k.tt : k.ts) + 4 * (q & 1);
    d[0] = v.x; d[1] = v.y; d[2] = v.z; d[3] = v.w;
  }
}
template <int SG> DEV void rotate(const float* d, const Dft& k, uint32_t* o) {
#pragma unroll
  for (int j = 0; j < 8; j++) {
    const uint32_t re = pack2(d[4 * j], d[4 * j + 1]), im = pack2(d[4 * j + 2], d[4 * j + 3]);
    uint32_t a, b;
    if (SG > 0) { a = hfms2(k.tt[j], im, re); b = hfma2(k.ts[j], a, im); a = hfms2(k.tt[j], b, a); }
    else { a = hfma2(k.tt[j], im, re); b = hfms2(k.ts[j], a, im); a = hfma2(k.tt[j], b, a); }
    o[2 * j] = a; o[2 * j + 1] = b;
  }
}
DEV void dft64(float* d, const uint32_t* a, uint64_t db) {
  wgmma_rsz_64_1(d, a, db);
#pragma unroll
  for (int kk = 1; kk < 4; kk++) wgmma_rs_64_1(d, a + 4 * kk, db + kk * (2048 >> 4));
}
DEV bool conv(const Dft& k, uint32_t sb, uint32_t t, uint32_t ty, float dv, int bar, int w, int lane, unsigned* go, uint32_t ep, uint32_t zero) {
  const uint32_t tag = KVCHK ? lds32(t + 1024 * w + 32 * lane + 4 * (lane & 4)) : ep;
  dv = __uint_as_float(__float_as_uint(dv) | (tag & zero));
  float dh[32], dx[32];
  uint32_t ah[16], ax[16];
  const uint64_t cs = make_desc(sb + OFF_DFT, 16, 1024, 1), bh = make_desc(t + 4096, 16, 1024, 1), bx = make_desc(t, 1024, 256, 3);
  wg_fence();
  wgmma_rsz_64_1(dh, k.E, bh); wgmma_rs_64_1(dh, k.E + 4, bh + (2048 >> 4)); wg_commit();
  wgmma_rsz_64_1(dx, k.E, bx); wgmma_rs_64_1(dx, k.E + 4, bx + (512 >> 4)); wg_commit();
  wg_wait<1>();
  dh[0] = fmaf(dv, blo(k.E[0]), dh[0]); dh[2] = fmaf(dv, blo(k.E[1]), dh[2]);
  rotate<1>(dh, k, ah);
  wg_fence(); dft64(dh, ah, cs); wg_commit();
  if (GO_AT == 1 && go) flag_add_rlx(go, 1);
  wg_wait<1>();
  rotate<1>(dx, k, ax);
  wg_fence(); dft64(dx, ax, cs); wg_commit();
  wg_wait<1>();
#pragma unroll
  for (int j = 0; j < 8; j++) { ah[2 * j] = pack2(dh[4 * j], dh[4 * j + 1]); ah[2 * j + 1] = pack2(dh[4 * j + 2], dh[4 * j + 3]); }
  wg_wait<0>();
#pragma unroll
  for (int j = 0; j < 4; j++) {
    const uint32_t pr = pack2(dx[4 * j], dx[4 * j + 1]), pi = pack2(dx[4 * j + 2], dx[4 * j + 3]);
    const uint32_t qr = pack2(dx[16 + 4 * j], dx[17 + 4 * j]), qi = pack2(dx[18 + 4 * j], dx[19 + 4 * j]);
    const uint32_t rr = ah[2 * j], ri = ah[2 * j + 1], sr = ah[8 + 2 * j], si = ah[9 + 2 * j];
    ax[2 * j] = hfma2(qi, si, hfms2(qr, sr, hfms2(pi, ri, hmul2(pr, rr))));
    ax[2 * j + 1] = hfms2(qi, sr, hfms2(qr, si, hfma2(pi, rr, hmul2(pr, ri))));
    ax[8 + 2 * j] = hfms2(qi, ri, hfma2(qr, rr, hfms2(pi, si, hmul2(pr, sr))));
    ax[9 + 2 * j] = hfma2(qi, rr, hfma2(qr, ri, hfma2(pi, sr, hmul2(pr, si))));
  }
  wg_fence();
  wgmma_rsz_64_0(dx, ax, cs);
#pragma unroll
  for (int kk = 1; kk < 4; kk++) wgmma_rs_64_0(dx, ax + 4 * kk, cs + 2 * kk);
  wg_commit();
  if (GO_AT == 2 && go) flag_add_rlx(go, 1);
  wg_wait<0>();
  rotate<-1>(dx, k, ah);
  const int m = lane >> 3, i = lane & 7;
  const uint32_t za = t + (16 * w + 8 * (m & 1) + i) * 128;
#pragma unroll
  for (int q = 0; q < 4; q++) stsm4(za + (((2 * q + (m >> 1)) ^ i) << 4), ah[4 * q], ah[4 * q + 1], ah[4 * q + 2], ah[4 * q + 3]);
  fence_async_smem();
  uint32_t ok;
  asm volatile("{\n.reg .pred p, q;\nsetp.eq.u32 p, %1, 0;\nbarrier.red.and.aligned.pred q, %2, 128, p;\nselp.u32 %0, 1, 0, q;\n}" : "=r"(ok) : "r"((tag ^ ep) & 1), "r"(bar) : "memory");
  const uint64_t da = make_desc(t, 16, 1024, 1), db = make_desc(sb + OFF_G, 16, 1024, 1);
  wg_fence();
  wgmma_ssz_32_10(dh, da, db);
#pragma unroll
  for (int kk = 1; kk < 4; kk++) wgmma_ss_32_10(dh, da + kk * (2048 >> 4), db + 2 * kk);
  wg_commit();
  if (GO_AT == 3 && go) flag_add_rlx(go, 1);
  wg_wait<0>();
  mbar_wait(sb + OFF_BAR + 8 * B_KVC, 0);
  const uint32_t ya = ty + (8 * (m >> 1) + i) * 128 + (((2 * w + (m & 1)) ^ i) << 4);
#pragma unroll
  for (int q = 0; q < 2; q++)
    stsm4t(ya + q * 2048, pack2(dh[8 * q], dh[8 * q + 1]), pack2(dh[8 * q + 2], dh[8 * q + 3]), pack2(dh[8 * q + 4], dh[8 * q + 5]), pack2(dh[8 * q + 6], dh[8 * q + 7]));
  wfence(4);
  return !KVCHK || __all_sync(0xffffffffu, ok);
}

DEV void g1_issue(const Params& P, uint32_t sb, int s, uint32_t fb, int kb, int rb, int fs) {
  const uint32_t st = sb + s * G1_W;
  mbar_expect(fb, G1_W + G1_X);
  tma2d(sb + OFF_X + s * G1_X, &P.x_g1, 64 * kb, 128 * rb, fb);
  tma3d(st, &P.w1_a, 0, 64 * kb, 3 * fs, fb);
  tma3d(st + 16384, &P.w1_b2, 0, 64 * kb, 6 * fs + 4, fb);
  tma3d(st + 24576, &P.w1_b1, 0, 64 * kb, 48 + fs, fb);
}
DEV void kv_issue(const Params& P, uint32_t dst, uint32_t bar, int r, int g1) {
  mbar_expect(bar, KV_SLOT);
  tma2d(dst, &P.k, 128 * r, 16 * g1 - 3, bar);
  tma2d(dst + 19 * 256, &P.v, 128 * r, 16 * g1, bar);
}
DEV void h_flag(const Params& P, int rb, int o) {
  const int j0 = (128 * rb) / 80;
  flag_add_rlx(P.flags + FL_H + 32 * (o + j0), 1); flag_add_rlx(P.flags + FL_H + 32 * (o + j0 + 1), 1);
  if (80 * (j0 + 2) < 128 * rb + 128) flag_add_rlx(P.flags + FL_H + 32 * (o + j0 + 2), 1);
}
DEV void h_wait(const Params& P, int tj, int o, unsigned ep) {
  flag_wait<false>(P.flags + FL_H + 32 * (o + tj), ep * (((80 * tj) >> 7) == (min(80 * tj + 79, S_ - 1) >> 7) ? 8 : 16));
  fence_async_global();
}
DEV uint32_t h_tag(uint32_t sb, int tj, int q, int lane) {
  const int r = min(q < 2 ? 32 * q + lane : 64 + (lane & 15), S_ - 1 - 80 * tj);
  return sb + G2_B + r * 128 + ((r & 7) << 4) + 4 * ((2 * tj + (r >> 3)) & 3);
}
DEV uint32_t conv_tile(uint32_t sb, int c) { return sb + (c == 1 ? OFF_T1 : c == 2 ? OFF_T2 : c == 3 ? OFF_T3 : OFF_T0); }
DEV void conv_issue_f(const Params& P, uint32_t t, int ch, uint32_t bar) { mbar_expect(bar, 4096); tma2d(t + 4096, &P.f_ld, 0, 32 * ch, bar); }
DEV void conv_issue_x(const Params& P, uint32_t t, int ch, uint32_t bar) {
  mbar_expect(bar, 4096);
  tma3d(t, &P.kvz, 16 * ((ch & ~63) | ((ch & 3) << 4) | ((ch & 63) >> 2)), 0, 0, bar);
}
HD int h_slot(int j) { return SPLIT9 && j ? 3 - j : j; }
DEV int g2_block(int i) { return i < 24 ? 3 * (i & 7) + (i >> 3) : i; }
DEV int ext_col(int n, int fs) { return min(n < 192 ? 192 * fs + n : 1344 + 32 * fs + n, F_ - 2); }
DEV uint32_t ext_off(int n, int k) {
  const int m = n - 128;
  return n < 128 ? (n >> 6) * 1024 + k * 128 + ((((n & 63) >> 3) ^ k) << 4) + (n & 7) * 2
                 : 2048 + (m >> 5) * 512 + k * 64 + ((((m & 31) >> 3) ^ (k >> 1)) << 4) + (m & 7) * 2;
}
DEV uint32_t kv_elem(uint32_t k0, uint32_t k1, uint32_t k2, uint32_t k3, const uint32_t (&w)[4], uint32_t v) {
  if (MIM & 2) return hmul2(hadd2(hadd2(hadd2(hmul2(k0, w[3]), hmul2(k1, w[2])), hmul2(k2, w[1])), hmul2(k3, w[0])), v);
  return hmul2(hfma2(k3, w[0], hfma2(k2, w[1], hfma2(k1, w[2], hmul2(k0, w[3])))), v);
}
DEV void kv_store(uint32_t z, const uint32_t (&p)[8]) {
  sts128(z, make_uint4(__byte_perm(p[0], p[1], 0x5410), __byte_perm(p[2], p[3], 0x5410), __byte_perm(p[4], p[5], 0x5410), __byte_perm(p[6], p[7], 0x5410)));
  sts128(z + 512, make_uint4(__byte_perm(p[0], p[1], 0x7632), __byte_perm(p[2], p[3], 0x7632), __byte_perm(p[4], p[5], 0x7632), __byte_perm(p[6], p[7], 0x7632)));
}
DEV void kv_out(const Params& P, uint32_t src, int r, int g1) { bulk_s2g(reinterpret_cast<uint8_t*>(P.kvZ) + g1 * 20480 + r * 4096, src, 4096); }
DEV void tap_split(uint4 q, uint32_t (&w)[4]) {
  w[0] = __byte_perm(q.x, q.z, 0x5410); w[1] = __byte_perm(q.x, q.z, 0x7632); w[2] = __byte_perm(q.y, q.w, 0x5410); w[3] = __byte_perm(q.y, q.w, 0x7632);
}

}

__global__ void __launch_bounds__(512, 1) h3_fused_kernel(const __grid_constant__ Params P) {
  extern __shared__ __align__(1024) uint8_t smem_raw[];
  constexpr uint32_t sb = 1024;
#define BAR(i) (sb + OFF_BAR + 8 * (i))
  const int warp = __shfl_sync(0xffffffffu, threadIdx.x >> 5, 0);
  const int wg = warp >> 2;
  const int tid = threadIdx.x & 127, lane = threadIdx.x & 31;
  uint32_t smid, nsmid;
  asm volatile("mov.u32 %0, %%smid;" : "=r"(smid));
  asm volatile("mov.u32 %0, %%nsmid;" : "=r"(nsmid));
  const uint32_t cta = nsmid == NCTA ? smid : blockIdx.x;
  const uchar4 mp = P.map[cta];
  const int g1 = mp.x, g2 = mp.y;
  const bool has1 = g1 < 128, has2 = g2 != 255;
  const int fs = g1 & 7, rb = g1 >> 3;
  const int tj = g2 >> 3, dt = g2 & 7;

  if (warp != 12) {
    if (elect()) {
      if (smem_u32(smem_raw) != sb) __trap();
#pragma unroll 1
      for (int b = B_FIRST + warp - (warp > 12); b < B_COUNT; b += 15) mbar_init(BAR(b), P.cnt[b]);
      fence_async_smem();
    }
    __syncwarp();
    asm volatile("bar.arrive 7, 512;" ::: "memory");
    asm volatile("bar.sync 0, 512;" ::: "memory");
  }

  if (wg < 3) {
    const int w4 = warp & 3, g = lane >> 2, c = lane & 3;
    asm volatile("setmaxnreg.inc.sync.aligned.u32 %0;" ::"n"(R_G));
    Dft dft;
    uint32_t ep, dq[3];
    auto misc_load = [&]() {
      const int l = wg == 0 ? CH_W0 : wg == 1 ? CH_W1 : CH_W2;
      ep = lds32(sb + OFF_MISC);
#pragma unroll
      for (int j = 0; j < 3; j++) dq[j] = lds32(sb + OFF_MISC + 4 + 4 * ((l >> (4 * j)) & 7));
    };
    if (wg < 2) {
      if (has1) {
        float acc[112];
        const uint64_t da0 = make_desc(sb + OFF_X + wg * 8192, 16, 1024, 1), db0 = make_desc(sb, 8192, 1024, 1), dc0 = make_desc(sb + 16384, 4096, 512, 2);
        const bool lead = tid == 0;
#pragma unroll
        for (int i = 0; i < 112; i++) acc[i] = 0.f;
        auto block = [&](int kb) {
          const int s = kb & 3;
          const uint64_t o = s * (G1_W >> 4), da = da0 + s * (G1_X >> 4), db = db0 + o, dc = dc0 + o;
          mbar_wait(BAR(B_FULL1 + s), (kb >> 2) & 1);
          TZ(tid, 64 + 10 * wg + kb);
          wg_fence();
#pragma unroll
          for (int kk = 0; kk < 4; kk++) {
            wgmma_ss_128_01(acc, da + 2 * kk, db + kk * (2048 >> 4));
            wgmma_ss_96_01(acc + 64, da + 2 * kk, dc + kk * (1024 >> 4));
            if (kk == EREL - 1) {
              wg_commit(); wg_wait<1>();
              if (lead && kb && kb < 7) mbar_arrive(BAR(B_EMPTY1 + ((kb - 1) & 3)));
            }
          }
          wg_commit();
        };
#pragma unroll 1
        for (int kb = 0; kb < 10 - SPLIT9; kb++) {
          block(kb);
          if (!EREL) {
            wg_wait<1>();
            if (lead && kb && kb < 7) mbar_arrive(BAR(B_EMPTY1 + ((kb - 1) & 3)));
          }
        }
        mbar_wait(BAR(B_TAB), 0);
        TZ(tid, 8 + wg);
        const uint32_t sa = sb + OFF_ST1 + 16 * (64 * wg + 16 * w4 + g);
        const float r0 = __uint_as_float(lds32(sa + 12)), r1 = __uint_as_float(lds32(sa + 128 + 12));
        {
          uint32_t ax[4];
          ax[0] = lds32(sa + 4 * c); ax[1] = lds32(sa + 128 + 4 * c);
          if (c == 3) { ax[0] = 0; ax[1] = 0; }
          asm volatile("mov.b32 %0, 0;" : "=r"(ax[2])); asm volatile("mov.b32 %0, 0;" : "=r"(ax[3]));
          if (SPLIT9) {
            const uint64_t da = da0 + (G1_X >> 4), db = db0 + (G1_W >> 4), dc = dc0 + (G1_W >> 4);
            wg_fence();
            wgmma_rs_128_1(acc, ax, make_desc(sb + OFF_EXT, 1024, 0, 1));
            wgmma_rs_96_1(acc + 64, ax, make_desc(sb + OFF_EXT + 2048, 512, 0, 2));
            mbar_wait(BAR(B_FULL1 + 1), 0);
            TZ(tid, 64 + 10 * wg + 9);
#pragma unroll
            for (int kk = 0; kk < 4; kk++) wgmma_ss_128_01(acc, da + 2 * kk, db + kk * (2048 >> 4));
            wg_commit();
#pragma unroll
            for (int kk = 0; kk < 4; kk++) wgmma_ss_96_01(acc + 64, da + 2 * kk, dc + kk * (1024 >> 4));
            wg_commit();
          } else {
          wg_fence();
          wgmma_rs_128_1(acc, ax, make_desc(sb + OFF_EXT, 1024, 0, 1));
          wgmma_rs_96_1(acc + 64, ax, make_desc(sb + OFF_EXT + 2048, 512, 0, 2));
          wg_commit();
          }
        }
        constexpr float K1 = 0.7978845608028654f, K2 = 0.7978845608028654f * 0.044715f;
        float c10 = K1 * r0, c11 = K1 * r1, c20 = K2 * r0 * r0 * r0, c21 = K2 * r1 * r1 * r1;
        c10 = __uint_as_float(pack2(c10, c10)); c11 = __uint_as_float(pack2(c11, c11)); c20 = __uint_as_float(pack2(c20, c20)); c21 = __uint_as_float(pack2(c21, c21));
        const int hr = 16 * w4 + ((lane >> 3) & 1) * 8 + (lane & 7);
        const uint32_t hs = sb + OFF_X + wg * 8192 + hr * 128, hx = (lane >> 4) ^ (lane & 7);
        const uint32_t hs2 = sb + OFF_X + 3 * G1_X + wg * 4096 + hr * 64, hx2 = (lane >> 4) ^ ((lane >> 1) & 3);
        if (SPLIT9) wg_wait<1>(); else wg_wait<0>();
        TZ(tid, 2 + wg);
        if (!SPLIT9 && tid < 5) mbar_arrive(BAR(tid < 4 ? B_EMPTY2 + tid : B_G1FREE));
        uint32_t zn = 0;
        misc_load();
        const uint32_t par = ep & 1;
#pragma unroll
        for (int i = 0; i < 28; i += 2) {
          if (i == 24) { if (fs >= 6) break; if (wg) mbar_wait(BAR(B_G1FREE), 0); }
          if (i && i % GELU_BF16 == 0) {
            const uint32_t z = LOOKAHEAD ? zn : lds32(sb + OFF_MISC + 24);
            c20 = __uint_as_float(__float_as_uint(c20) + z); c21 = __uint_as_float(__float_as_uint(c21) + z);
          }
          if (LOOKAHEAD && (i + LOOKAHEAD) % GELU_BF16 == 0) zn = lds32(sb + OFF_MISC + 24);
          if (SPLIT9 && i == 16) { wg_wait<0>(); if (tid < 5) mbar_arrive(BAR(tid < 4 ? B_EMPTY2 + tid : B_G1FREE)); }
          if (i == DFT_AT) dft_load(dft, P.tab, tid);
          const float* a = &acc[4 * i];
          uint32_t p0 = gelu2(a[0], a[1], c10, c20), p1 = gelu2(a[2], a[3], c11, c21);
          if (!(i & 7)) { if (c == ((2 * w4) & 3)) p0 = (p0 & ~1u) | par; if (c == ((2 * w4 + 1) & 3)) p1 = (p1 & ~1u) | par; }
          const uint32_t p2 = gelu2(a[4], a[5], c10, c20), p3 = gelu2(a[6], a[7], c11, c21);
          if (i > HS_LAG && !((i - HS_LAG) & 7)) { wfence(2); warp_arrive(BAR(B_HS + 4 * wg + (i >> 3) - 1)); }
          if (i < 24) stsm4(hs + h_slot(i >> 3) * G1_X + ((hx ^ (i & 7)) << 4), p0, p1, p2, p3);
          else stsm4(hs2 + ((hx2 ^ (i & 3)) << 4), p0, p1, p2, p3);
          if ((i == 22 && fs >= 6) || i == 26) { wfence(2); warp_arrive(BAR(B_HS + 4 * wg + (i >> 3))); }
        }
        TZ(tid, 4 + wg);
      } else if (wg == 1) {
        float cs[7][4];
#pragma unroll
        for (int j = 0; j < 7; j++) cs[j][0] = cs[j][1] = cs[j][2] = cs[j][3] = 0.f;
        if (tid < 64) sts32(sb + OFF_EXT + 4 * tid, 0x3f803f80u);
        fence_async_smem();
        bar_sync(4);
        const uint64_t da0 = make_desc(sb, 16, 1024, 1), db = make_desc(sb + OFF_EXT, 128, 128, 0);
        int s = 0, ph = 0;
#pragma unroll 1
        for (int kb = CS_KB; kb < 10; kb++) {
          mbar_wait(BAR(B_FULL1 + s), ph);
          wg_fence();
#pragma unroll 1
          for (int kk = 0; kk < 4; kk++) {
#pragma unroll
            for (int j = 0; j < 7; j++) wgmma_ss_8_10(cs[j], da0 + (s * (CS_STAGE >> 4) + kk * (2048 >> 4)) + j * (8192 >> 4), db);
            wg_commit();
          }
          wg_wait<0>();
          if (tid < 4) mbar_arrive(BAR(B_EMPTY1 + s));
          if (++s == 3) { s = 0; ph ^= 1; }
        }
        mbar_wait(BAR(B_EPOCH), 0);
        ep = lds32(sb + OFF_MISC);
#pragma unroll
        for (int j = 0; j < 7; j++) {
          const float a = (c & 1) ? cs[j][2] : cs[j][0], b = __shfl_down_sync(0xffffffffu, a, 4);
          if (c < 2 && !(g & 1)) tag_store(P.cs + CSP + 32 * (7 * (g1 - 128) + j) + 8 * w4 + 4 * c + (g >> 1), a, b, ep);
        }
        TZ(tid, 24);
        if (tid < 2 * G2_NST) mbar_arrive(BAR(B_EMPTY2 + (tid >> 1)));
      }
    } else {
      if (has1) {
        const bf16* skp = P.shift_k + (128 * (w4 >> 1) + 64 * (w4 & 1) + 4 * (lane & 15)) * 4;
        uint4 tap0 = ldg128(skp), tap1 = ldg128(skp + 8);
        auto stats = [&]() {
        mbar_wait(BAR(B_STAT), 0);
        TZ(tid, 19);
        float sum = 0.f, sq = 0.f;
        const uint32_t sa = sb + OFF_SR + (tid >> 3) * 1280 + 16 * (lane & 7);
        uint4 nq[2] = {lds128(sa), lds128(sa + 128)};
#pragma unroll 1
        for (int z = 0; z < 5; z++) {
          const uint4 xq[2] = {nq[0], nq[1]};
          if (z < 4) { nq[0] = lds128(sa + 256 * z + 256); nq[1] = lds128(sa + 256 * z + 384); }
          else warp_arrive(BAR(B_STATFREE) + ((xq[0].x | xq[1].x) & P.zero));
#pragma unroll
          for (int i = 0; i < 2; i++) {
            const uint32_t u[4] = {xq[i].x, xq[i].y, xq[i].z, xq[i].w};
#pragma unroll
            for (int e = 0; e < 4; e++) { const float a = blo(u[e]), b = bhi(u[e]); sum += a + b; sq = fmaf(a, a, fmaf(b, b, sq)); }
          }
        }
#pragma unroll
        for (int o = 1; o < 8; o *= 2) { sum += __shfl_xor_sync(0xffffffffu, sum, o); sq += __shfl_xor_sync(0xffffffffu, sq, o); }
        const float mean = sum * (1.f / D_), var = fmaxf(fmaf(-mean, mean, sq * (1.f / D_)), 0.f);
        const float ve = bf_round(bf_round(var) + 1e-5f);
        if ((lane & 7) == 0) tag_store(P.stats + 16 * g1 + (tid >> 3), MIM & 1 ? bf_round(mean) : mean, MIM & 1 ? rcp_fast(bf_round(ve * rsqrtf(ve))) : rsqrtf(var + 1e-5f), ep);
        TZ(tid, 22);
        };
        const uint32_t slot = sb + OFF_KV + (w4 >> 1) * KV_SLOT;
        const uint32_t ka = slot + 8 * (lane >> 4) * 256 + 128 * (w4 & 1) + 8 * (lane & 15);
        const uint32_t zo = (64 * (w4 & 1) + (lane & 15)) * 32 + (lane >> 4) * 16;
        if (DFT_EARLY == 2) dft_load(dft, P.tab, tid);
        mbar_wait(BAR(B_EPOCH), 0);
        misc_load();
        const uint32_t tagm = lane < 16 ? 0x00010001u : 0u, tagv = (ep & 1) ? tagm : 0u;
#pragma unroll 1
        for (int r = w4 >> 1; r < 5; r += 2) {
          uint32_t wa[4], wb[4], p[8], q[8];
          uint2 kk[11];
          tap_split(tap0, wa); tap_split(tap1, wb);
          if (r < 3) { skp += 1024; tap0 = ldg128(skp); tap1 = ldg128(skp + 8); }
          else if (DFT_EARLY == 3) dft_load(dft, P.tab, tid);
          mbar_wait(BAR(B_KV + (r & 1)), (r >> 1) & 1);
          TZ(tid & 63, 58 + r);
#pragma unroll
          for (int j = 0; j < 11; j++) kk[j] = lds64(ka + j * 256);
#pragma unroll
          for (int j = 0; j < 8; j++) { const uint2 vv = lds64(ka + (19 + j) * 256); p[j] = vv.x; q[j] = vv.y; }
#pragma unroll
          for (int j = 0; j < 8; j++) {
            p[j] = kv_elem(kk[j].x, kk[j + 1].x, kk[j + 2].x, kk[j + 3].x, wa, p[j]);
            q[j] = kv_elem(kk[j].y, kk[j + 1].y, kk[j + 2].y, kk[j + 3].y, wb, q[j]);
          }
          asm volatile("bar.sync %0, 64;" ::"r"(5 + (r & 1) + ((p[0] | p[1] | p[2] | p[3] | p[4] | p[5] | p[6] | p[7]) & P.zero)) : "memory");
          TZ(tid | (r ^ 2), 10);
          if (r < 4 && w4 == 0 && elect()) kv_issue(P, slot, BAR(B_KV), r + 2, g1);
          if (r == 2) mbar_wait(BAR(B_KVR), 0);
          TZ(tid | (r ^ 2), 45);
          const uint32_t z = zo + (r < 4 && w4 < 2 ? sb + OFF_KVS : slot + KV_V);
          p[0] = (p[0] & ~tagm) | tagv; q[0] = (q[0] & ~tagm) | tagv;
          kv_store(z, p); kv_store(z + 1024, q);
          wfence(1);
          warp_arrive(BAR(B_KVS + (r >> 1)));
          TZ(tid | (r ^ 2), 49);
          if (r < 2) stats();
        }
        TZ(tid, 21);
        if (!DFT_EARLY) dft_load(dft, P.tab, tid);
      }
    }

    if (has1) {
      mbar_wait(BAR(B_DFT), 0);
      int tries = 0;
#pragma unroll 1
      for (int l = wg == 0 ? CH_W0 : wg == 1 ? CH_W1 : CH_W2; (l & 15) != 15;) {
        const int i = l & 15;
        const float dv = c == 0 ? __uint_as_float(dq[0]) : 0.f;
        TZ(tid, 31 + 4 * i);
        mbar_wait(BAR(B_CX + i), tries & 1);
        TZ(tid, 30 + 4 * i);
        if (conv(dft, sb, conv_tile(sb, i), i ? conv_tile(sb, i) : sb + OFF_Y0, dv, 1 + wg, w4, lane, tid == 0 && ((GO_WG >> wg) & 1) && (l >> 4) == 15 && !tries ? P.flags + FL_G2 + 32 * mp.z : nullptr, ep, P.zero)) {
          warp_arrive(BAR(B_RD + i));
          l >>= 4; tries = 0; dq[0] = dq[1]; dq[1] = dq[2];
        } else {
          fence_async_smem();
          bar_sync(1 + wg);
          trap_above(++tries, 100000);
          if (tid == 0) { conv_issue_f(P, conv_tile(sb, i), g1 + 128 * i, BAR(B_CX + i)); conv_issue_x(P, conv_tile(sb, i), g1 + 128 * i, BAR(B_CX + i)); }
        }
        TZ(tid, 32 + 4 * i);
      }
    }
    if (wg == 2 && has2) {
      const uint2* const ps[1] = {P.stats + min(80 * tj + tid, S_ - 1)};
      uint2 sv[1] = {tag_load(ps[0])};
      mbar_wait(BAR(B_EPOCH), 0);
      tag_wait<1>(ps, sv, lds32(sb + OFF_MISC));
      const float r = __uint_as_float(sv[0].y), mr = -__uint_as_float(sv[0].x) * (MIM & 1 ? 1.f : r);
      const float r2 = __shfl_down_sync(0xffffffffu, r, 1), mr2 = __shfl_down_sync(0xffffffffu, mr, 1);
      if (tid < 80 && !(tid & 1)) {
        const uint32_t hi = pack2(r, r2);
        sts128(sb + OFF_ST2 + 8 * tid, make_uint4(hi, pack2(mr, mr2), __float_as_uint(0.25f * r), __float_as_uint(0.25f * r2)));
        sts32(sb + OFF_ST2 + 640 + 2 * tid, pack2(r - blo(hi), r2 - bhi(hi)));
      }
      warp_arrive(BAR(B_EP));
    }
    if ((!has2 || wg == 2) && tid == 0) mbar_arrive(BAR(B_DONE));
    if (has2 && wg < 2) {
      float acc[40];
      const uint64_t da0 = make_desc(sb + wg * 8192, 16, 1024, 1), db0 = make_desc(sb + G2_B, 16, 1024, 1);
      const float b20 = 0.5f * ldg_bf16(P.b2 + 128 * dt + 64 * wg + 16 * w4 + g), b21 = 0.5f * ldg_bf16(P.b2 + 128 * dt + 64 * wg + 16 * w4 + g + 8);
      if (threadIdx.x == 0) mbar_arrive(BAR(B_GO));
      mbar_wait(BAR(B_GO), 0);
      const bool lead = tid == 0;
      const int mi = lane >> 3, rr = lane & 7;
      const uint32_t xa = sb + OFF_XT + wg * XT_STEP + ((mi >> 1) * 8 + rr) * 128 + (((2 * w4 + (mi & 1)) ^ rr) << 4);
      const uint32_t ya = sb + OFF_YT + (64 * wg + 16 * w4 + (mi & 1) * 8 + rr) * 160 + (mi >> 1) * 16;
      uint32_t xr[5][4], xn[5][4];
      uint2 rq[10];
      uint32_t va = sb + OFF_MISC + 28, ta = sb + OFF_ST2 + 16 * c, tb = sb + OFF_ST2 + 640 + 4 * c;
      asm volatile("" : "+r"(ta), "+r"(tb));
#pragma unroll
      for (int i = 0; i < 40; i++) acc[i] = 0.f;
#pragma unroll 1
      for (int k0 = 0; k0 < 9; k0++) {
        const int s0 = 3 * (k0 & 1);
        const uint64_t da = da0 + s0 * (G2_STAGE >> 4), db = db0 + s0 * (G2_STAGE >> 4);
        const uint32_t fb = BAR(B_FULL2 + s0);
#pragma unroll
        for (int u = 0; u < 3; u++) {
          if (u == SK2 && k0 == 8 && wg == 1) mbar_wait(BAR(B_SKEW), 0);
          mbar_wait(fb + 8 * u, (k0 >> 1) & 1);
          TZ(threadIdx.x, 64 + 32 + 3 * k0 + u);
          wg_fence();
#pragma unroll
          for (int kk = 0; kk < 4; kk++)
            wgmma_ss_80_10(acc, da + (u * (G2_STAGE >> 4) + kk * (2048 >> 4)), db + (u * (G2_STAGE >> 4) + 2 * kk));
          wg_commit();
          if (SK2 > 2 || k0 < 8) wg_wait<1>();
          if (u) { if (lead) mbar_arrive(fb + 8 * (G2_NST + u - 1)); }
          else if (lead && k0) mbar_arrive(BAR(B_EMPTY2 + 5) - 8 * s0);
        }
      }
      if (SK2 <= 2 && threadIdx.x == 0) mbar_arrive(BAR(B_SKEW));
      if (!CHK && threadIdx.x == 0) { sts32(sb + OFF_MISC + 28, 0); mbar_arrive(BAR(B_VD)); }
      goto tail;
    repeat:
      wg_wait<0>();
#pragma unroll 1
      for (int i = 0, n = 0; i < 4 * 27 && n < 100000;) {
        if (!(i & 3)) {
          asm volatile("bar.sync 9, 256;" ::: "memory");
          if (threadIdx.x == 0) {
            mbar_expect(BAR(B_RT), 26624);
            tma3d(sb, &P.w2, 0, 64 * g2_block(i >> 2), 2 * dt, BAR(B_RT));
            tma2d(sb + G2_B, &P.h_ld, 64 * g2_block(i >> 2), 80 * tj, BAR(B_RT));
          }
          mbar_wait(BAR(B_RT), n++ & 1);
          uint32_t bad = 0;
          ep = lds32(sb + OFF_MISC);
#pragma unroll 1
          for (int q = 0; q < 6; q++) bad |= lds32(h_tag(sb, tj, q >> 1, lane) ^ (i >= 96 && (q & 1) ? 64 : 0)) ^ ep;
          if (__any_sync(0xffffffffu, bad & 1)) continue;
        }
        wg_fence();
        wgmma_ssp_80_10(acc, da0 + (i & 3) * (2048 >> 4), db0 + 2 * (i & 3), i);
        wg_commit();
        wg_wait<0>();
        i++;
      }
      va = sb + OFF_MISC + 24;
    tail:
      mbar_wait(BAR(B_EP), 0);
#pragma unroll
      for (int i = 0; i < 10; i++) {
        if (!(i & 1)) ldsm4t(xa + i * 1024, xr[i >> 1]);
        const uint4 st = lds128(ta + 64 * i);
        const uint32_t lo = MIM & 1 ? lds32(tb + 16 * i) : 0;
        rq[i] = make_uint2(st.z, st.w);
#pragma unroll
        for (int hf = 0; hf < 2; hf++) {
          if (MIM & 1) { const uint32_t d = hadd2(xr[i >> 1][2 * (i & 1) + hf], st.y); xn[i >> 1][2 * (i & 1) + hf] = hfma2v(d, st.x, hmul2(d, lo)); }
          else xn[i >> 1][2 * (i & 1) + hf] = hfma2(xr[i >> 1][2 * (i & 1) + hf], st.x, st.y);
        }
      }
      mbar_wait(BAR(B_VD), 0);
      if (FB && __any_sync(0xffffffffu, lds32(va))) goto repeat;
      wg_wait<0>();
      TZ(tid, 50 + wg);
      mbar_wait(BAR(B_EPY), 0);
      if (tid == 0) mbar_arrive(BAR(B_DONE));
      TZ(tid, 52 + wg);
#pragma unroll
      for (int i = 0; i < 10; i += 2) {
        uint32_t yr[4], ov[4];
        ldsm4(ya + i * 16, yr);
#pragma unroll
        for (int j = 0; j < 2; j++) {
#pragma unroll
          for (int hf = 0; hf < 2; hf++) {
            const float bb2 = hf ? b21 : b20;
            const float z0 = fmaf(acc[4 * (i + j) + 2 * hf], __uint_as_float(rq[i + j].x), bb2), z1 = fmaf(acc[4 * (i + j) + 2 * hf + 1], __uint_as_float(rq[i + j].y), bb2);
            const uint32_t gt = pack2(fmaf(z0, tanh_fast(z0), z0), fmaf(z1, tanh_fast(z1), z1));
            ov[2 * j + hf] = hfma2(hmul2(xn[i >> 1][2 * j + hf], yr[2 * j + hf]), gt, xr[i >> 1][2 * j + hf]);
          }
        }
        if (i == 4 || i == 8) { wfence(8); warp_arrive(BAR(B_HS + 4 * wg + (i == 8))); }
        stsm4t(xa + i * 1024, ov[0], ov[1], ov[2], ov[3]);
      }
      wfence(8);
      warp_arrive(BAR(B_HS + 4 * wg + 2));
      TZ(tid, 6 + wg);
      DBG_END(tid);
    }
  } else {
    asm volatile("setmaxnreg.dec.sync.aligned.u32 %0;" ::"n"(R_P));
    if (warp >= 14) {
      if (has1) {
        {
          float cs[8];
#pragma unroll
          for (int e = 0; e < 8; e++) cs[e] = 0.f;
          const int q = min(2 * rb, 26) + (lane & 1), kr = lane >> 1;
          const uint32_t stp = rb < 8 ? 2048 : 1024;
          const uint32_t a0 = sb + (warp & 1) * 2 * stp + (rb < 8 ? (q >> 3) * 8192 + kr * 128 + (((q & 7) ^ (kr & 7)) << 4)
                                                  : 16384 + ((q - 16) >> 2) * 4096 + kr * 64 + (((q & 3) ^ ((kr >> 1) & 3)) << 4));
#pragma unroll 1
          for (int kb = 0; kb < CS_KB; kb++) {
            const uint32_t a = a0 + (kb & 3) * G1_W;
            mbar_wait(BAR(B_FULL1 + (kb & 3)), kb >> 2);
            const uint4 u = lds128(a), w = lds128(a + stp);
            warp_arrive(BAR(B_EMPTY1 + (kb & 3)) + ((u.x | w.x) & P.zero));
            cs[0] += blo(u.x) + blo(w.x); cs[1] += bhi(u.x) + bhi(w.x); cs[2] += blo(u.y) + blo(w.y); cs[3] += bhi(u.y) + bhi(w.y);
            cs[4] += blo(u.z) + blo(w.z); cs[5] += bhi(u.z) + bhi(w.z); cs[6] += blo(u.w) + blo(w.w); cs[7] += bhi(u.w) + bhi(w.w);
          }
#pragma unroll
          for (int kb = CS_KB; kb < 6; kb++) { mbar_wait(BAR(B_EMPTY1 + (kb & 3)), 0); if (elect()) mbar_arrive(BAR(B_EMPTY1 + (kb & 3))); }
#pragma unroll
          for (int e = 0; e < 4; e++) {
            const bool up = lane & 4;
            const float o = __shfl_xor_sync(0xffffffffu, up ? cs[e] : cs[e + 4], 4);
            cs[e] = (up ? cs[e + 4] : cs[e]) + o;
          }
#pragma unroll
          for (int e = 0; e < 2; e++) {
            const bool up = lane & 2;
            const float o = __shfl_xor_sync(0xffffffffu, up ? cs[e] : cs[e + 2], 2);
            cs[e] = (up ? cs[e + 2] : cs[e]) + o;
            cs[e] += __shfl_xor_sync(0xffffffffu, cs[e], 8);
            cs[e] += __shfl_xor_sync(0xffffffffu, cs[e], 16);
          }
          const uint32_t xa = sb + OFF_ST2 + 8 * (lane & 7);
          if (warp == 15 && lane < 8) { sts32(xa, __float_as_uint(cs[0])); sts32(xa + 4, __float_as_uint(cs[1])); }
          asm volatile("bar.sync 8, 64;" ::: "memory");
          if (warp == 14) {
            const uint2 o = lds64(xa);
            mbar_wait(BAR(B_EPOCH), 0);
            if (lane < 8 && rb < 14 && (rb < 12 || fs < 6))
              tag_store(P.cs + (ext_col(16 * rb, fs) >> 1) + 4 * (lane & 1) + (lane >> 1), cs[0] + __uint_as_float(o.x), cs[1] + __uint_as_float(o.y), lds32(sb + OFF_MISC));
            TZ(lane, 18);
          }
        }
        if (warp == 15) {
#pragma unroll 1
          for (int j = 0; j < 2; j++) {
            const int n0 = 2 * lane + 64 * j, n1 = min(128 + n0, 222);
            const uint32_t b0 = ldg32(P.b1 + ext_col(n0, fs)), b1 = ldg32(P.b1 + ext_col(n1, fs));
            const uint32_t e0 = sb + OFF_EXT + ext_off(n0, 0), e1 = sb + OFF_EXT + ext_off(n1, 0);
#pragma unroll
            for (int k = 3; k < 8; k++) { sts32((e0 + 128 * k) ^ (k << 4), k < 5 ? b0 : 0u); sts32((e1 + 64 * k) ^ ((k >> 1) << 4), k < 5 ? b1 : 0u); }
          }
        }
      }
      mbar_wait(BAR(B_EPOCH), 0);
      const unsigned ep = lds32(sb + OFF_MISC);
      if (has1) {
        const int l2 = tid - 64, n0 = 2 * l2, n1 = min(128 + 2 * l2, 222), f0 = ext_col(n0, fs), f1 = ext_col(n1, fs);
        const uint32_t e0 = sb + OFF_EXT + ext_off(n0, 0), e1 = sb + OFF_EXT + ext_off(n1, 0);
        const uint2* const pc[4] = {P.cs + (f0 >> 1), P.cs + (f1 >> 1), P.cs + CSP + (f0 >> 1), P.cs + CSP + (f1 >> 1)};
        uint2 v[4] = {tag_load(pc[0]), tag_load(pc[1]), tag_load(pc[2]), tag_load(pc[3])};
        tag_wait<4>(pc, v, ep);
#pragma unroll
        for (int i = 0; i < 2; i++) {
          const float x = __uint_as_float(v[i].x) + __uint_as_float(v[i + 2].x), y = __uint_as_float(v[i].y) + __uint_as_float(v[i + 2].y);
          const uint32_t hi = pack2(x, y), lo = pack2(x - blo(hi), y - bhi(hi));
#pragma unroll
          for (int k = 0; k < 3; k++) sts32(i ? (e1 + 64 * k) ^ ((k >> 1) << 4) : (e0 + 128 * k) ^ (k << 4), k < 2 ? hi : lo);
        }
        TZ(lane, 25);
        fence_async_smem();
        warp_arrive(BAR(B_TAB));
      }
      __syncwarp();
      if (elect()) {
        if (warp == 15) {
          if (CHK == 3) for (int s = 0; s < G2_NST; s++) mbar_arrive(BAR(B_EMPTY2 + s));
          if (has1) {
            prefetch_map(&P.h_st); prefetch_map(&P.h_st2);
#pragma unroll
            for (int j = 0; j < 4; j++) {
              mbar_wait(BAR(B_HS + 4 * (j & 1) + (j & 2)), 0); rfence(2);
              if (j & 1) TS(33 + 4 * (j & 2));
              tma2d_st(&P.h_st, 192 * fs + 64 * (j & 2), 128 * rb + 64 * (j & 1), sb + OFF_X + (j & 2) * G1_X + (j & 1) * 8192);
              if (j == 1) {
                bulk_commit();
                bulk_wait_all();
                h_flag(P, rb, 0);
                mbar_arrive(BAR(B_EMPTY2 + 4));
                TS(26);
              }
            }
            if (fs < 6) {
#pragma unroll
              for (int w = 0; w < 2; w++) {
                mbar_wait(BAR(B_HS + 4 * w + 3), 0); rfence(2);
                tma2d_st(&P.h_st2, 1536 + 32 * fs, 128 * rb + 64 * w, sb + OFF_X + 3 * G1_X + w * 4096);
              }
            }
            bulk_commit();
            bulk_wait_all();
            mbar_arrive(BAR(B_EMPTY2 + 5));
            pub_fence(2);
            h_flag(P, rb, 64);
            TS(14);
          }
          if (has2) {
            h_wait(P, tj, 64, ep);
            mbar_arrive(BAR(B_HB));
            TS(17);
          }
        }
      }
      __syncwarp();
      if (warp == 15 && has2) {
        uint32_t ta[3], bad = 0;
#pragma unroll
        for (int q = 0; q < 3; q++) ta[q] = h_tag(sb, tj, q, lane);
        int s = 0, ph = 0;
#pragma unroll 1
        for (int kb = 0; kb < 27; kb++) {
          mbar_wait(BAR(B_FULL2 + s), ph);
          uint32_t t = 0;
#pragma unroll
          for (int q = 0; q < 3; q++) t |= lds32(ta[q] + s * G2_STAGE) ^ ep;
          if (kb >= 24) {
#pragma unroll
            for (int q = 0; q < 3; q++) t |= lds32((ta[q] ^ 64) + s * G2_STAGE) ^ ep;
          }
          bad |= t;
          if (CHK == 3 && lane == 0) mbar_arrive(BAR(B_EMPTY2 + s) + (t & P.zero));
          if (++s == G2_NST) { s = 0; ph ^= 1; }
        }
        bad = __any_sync(0xffffffffu, bad & 1);
        if (lane == 0) { sts32(sb + OFF_MISC + 28, bad); mbar_arrive(BAR(B_VD)); }
      }
      if (elect()) {
        if (warp == 14 && has2) {
          prefetch_map(&P.h_ld);
          h_wait(P, tj, 0, ep);
          TS(16);
#pragma unroll 1
          for (int k0 = 0; k0 < 9; k0++) {
#pragma unroll
            for (int u = 0; u < 3; u++) {
              const int kb = 3 * k0 + u, s = 3 * (k0 & 1) + u;
              if (u == 0 && k0 == 2) {
                if (USE_GO) flag_wait<false>(P.flags + FL_G2 + 32 * mp.z, ep * mp.w * GO_N);
                mbar_arrive(BAR(B_GO));
                TS(20);
              }
              if (u == 2 && k0 == 2) mbar_wait(BAR(B_H1), 0);
              if (u == 1 && k0 == 5) mbar_wait(BAR(B_HB), 0);
              mbar_wait(BAR(B_EMPTY2 + s), (k0 >> 1) & 1);
              TS(64 + 96 + kb);
              mbar_expect(BAR(B_FULL2 + s), 10240);
              tma2d(sb + s * G2_STAGE + G2_B, &P.h_ld, 64 * g2_block(kb), 80 * tj, BAR(B_FULL2 + s));
              if (u == YK % 3 && k0 == YK / 3) mbar_arrive(BAR(B_LATE));
            }
          }
        }
        if (has2) {
          const int w = 15 - warp;
          prefetch_map(&P.out_st);
#pragma unroll
          for (int j = 0; j < 5; j++) {
            if (!(j & 1)) { mbar_wait(BAR(B_HS + 4 * w + (j >> 1)), has1); rfence(8); }
            tma2d_st(&P.out_st, 128 * dt + 64 * w, 80 * tj + 16 * j, sb + OFF_XT + w * XT_STEP + j * 2048);
          }
          bulk_commit();
        }
        mbar_arrive(BAR(B_DONE));
        bulk_wait_read();
        TS(54 + 15 - warp);
        DBG_END(0);
      }
    } else if (warp == 13) {
      unsigned ep;
      asm volatile("ld.relaxed.gpu.global.u32 %0, [%1];" : "=r"(ep) : "l"(P.flags + FL_EPOCH) : "memory");
      if (has1 && lane < 5) sts32(sb + OFF_MISC + 4 + 4 * lane, __float_as_uint(ldg_bf16(P.ssm_D + g1 + 128 * lane)));
      ep += 1;
      __syncwarp();
      if (elect()) {
        sts32(sb + OFF_MISC, ep); sts32(sb + OFF_MISC + 24, 0);
        mbar_arrive(BAR(B_EPOCH));
        if (PFW && has1) bulk_prefetch(P.w1p + 256 * F_ + g1 * (PFW * F_ / 2), PFW * F_);
        flag_add_rlx(P.flags + FL_START, 1);
        if (!has1 && has2) flag_add_rlx(P.flags + FL_G2 + 32 * mp.z, GO_N);
        if (has1) {
          prefetch_map(&P.kvz); prefetch_map(&P.f_ld); prefetch_map(&P.y_st);
#define W(b) mbar_wait_b(BAR(b), 0);
#define KV(r) kv_issue(P, sb + OFF_KV + (r) * KV_SLOT, BAR(B_KV + (r)), r, g1);
#define PUBA rfence(1); kv_out(P, sb + OFF_KVS, 0, g1); kv_out(P, sb + OFF_KV + KV_SLOT + KV_V, 1, g1); bulk_commit(); bulk_wait_read(); \
  kv_issue(P, sb + OFF_KV + KV_SLOT, BAR(B_KV + 1), 3, g1); mbar_arrive(BAR(B_KVR)); bulk_wait_all(); pub_fence(1); flag_add_rlx(P.flags + FL_KV, 1); TS(56);
#define PUBB mbar_wait_b(BAR(B_KVS + 1), 0); rfence(1); kv_out(P, sb + OFF_KVS, 2, g1); kv_out(P, sb + OFF_KV + KV_SLOT + KV_V, 3, g1); bulk_commit(); bulk_wait_read();
#define FLB bulk_wait_all(); pub_fence(1); flag_add_rlx(P.flags + FL_KV + 32, 1); TS(57);
#define PUBC mbar_wait_b(BAR(B_KVS + 2), 0); rfence(1); kv_out(P, sb + OFF_KV + KV_V, 4, g1); bulk_commit(); bulk_wait_read();
#define FLC bulk_wait_all(); pub_fence(1); flag_add_rlx(P.flags + FL_KV + 64, 1); TS(63);
#define KC mbar_expect(BAR(B_DFT), 12288); bulk_g2s(sb + OFF_DFT, P.tab, 12288, BAR(B_DFT));
#define F(c) conv_issue_f(P, conv_tile(sb, c), g1 + 128 * (c), BAR(B_CX + (c)));
#define G(i) flag_wait<true>(P.flags + FL_KV + 32 * (i), ep * 128); fence_async_global(); TS((i) == 2 ? 28 : 23 + 6 * (i));
#define X(c) conv_issue_x(P, conv_tile(sb, c), g1 + 128 * (c), BAR(B_CX + (c)));
#define Y(c) mbar_wait_b(BAR(B_RD + (c)), 0); rfence(4); tma2d_st(&P.y_st, 0, 32 * (g1 + 128 * (c)), (c) ? conv_tile(sb, c) : sb + OFF_Y0); bulk_commit();
#define XE mbar_expect(BAR(B_EP), 20480); tma2d(sb + OFF_XT, &P.x_ep, 128 * dt, 80 * tj, BAR(B_EP)); tma2d(sb + OFF_XT + XT_STEP, &P.x_ep, 128 * dt + 64, 80 * tj, BAR(B_EP));
#define R bulk_wait_read();
#define A(b) mbar_arrive(BAR(b));
#define PF(c) bulk_prefetch(P.ssm_k + (g1 + 128 * (c)) * S_, 4096);
#define PW bulk_prefetch(P.w2p + g1 * (F_ * D_ / 128), F_ * D_ / 64);
          AUX_SEQ
#undef W
#undef PUBA
#undef PUBB
#undef PUBC
#undef FLB
#undef FLC
#undef KC
#undef F
#undef G
#undef X
#undef Y
#undef R
#undef XE
#undef A
#undef PF
#undef PW
          bulk_wait_all(); pub_fence(4);
          flag_add_rlx(P.flags + FL_Y, 1);
          TS(12);
          if (g1 == 0) { flag_wait<true>(P.flags + FL_START, ep * NCTA); P.flags[FL_EPOCH] = ep; }
        }
        if (has2) {
          mbar_expect(BAR(B_EPY), 20480);
          prefetch_map(&P.y_ld);
          if (!has1) {
            mbar_expect(BAR(B_EP), 20480);
            tma2d(sb + OFF_XT, &P.x_ep, 128 * dt, 80 * tj, BAR(B_EP));
            tma2d(sb + OFF_XT + XT_STEP, &P.x_ep, 128 * dt + 64, 80 * tj, BAR(B_EP));
          }
          flag_wait<true>(P.flags + FL_Y, ep * 128);
          fence_async_global();
          mbar_wait_b(BAR(B_LATE), 0);
          TS(13);
          tma2d(sb + OFF_YT, &P.y_ld, 80 * tj, 128 * dt, BAR(B_EPY));
        }
        mbar_wait_b(BAR(B_DONE), 0);
      }
    } else {
      const bool lead = elect();
      if (lead) {
        mbar_init(BAR(B_FULL1), 1);
        fence_async_smem();
        if (has1) g1_issue(P, sb, 0, BAR(B_FULL1), 0, rb, fs);
        else { mbar_expect(BAR(B_FULL1), CS_STAGE); tma3d(sb, &P.w1_cs, 0, 64 * CS_KB, 7 * (g1 - 128), BAR(B_FULL1)); }
#pragma unroll
        for (int b = 1; b < B_FIRST; b++) mbar_init(BAR(b), 1);
        fence_async_smem();
      }
      __syncwarp();
      asm volatile("bar.arrive 0, 512;" ::: "memory");
      if (lead) {
        if (has1) {
#define S(kb) g1_issue(P, sb, kb, BAR(B_FULL1 + (kb)), kb, rb, fs);
#define K(r) kv_issue(P, sb + OFF_KV + (r) * KV_SLOT, BAR(B_KV + (r)), r, g1);
#define T mbar_expect(BAR(B_STAT), 20480); bulk_g2s(sb + OFF_SR, P.x + g1 * 16 * D_, 20480, BAR(B_STAT));
          INIT_SEQ
          TS(64 + 20 + 3);
        } else {
#pragma unroll
          for (int kb = 1; kb < 3; kb++) { mbar_expect(BAR(B_FULL1 + kb), CS_STAGE); tma3d(sb + kb * CS_STAGE, &P.w1_cs, 0, 64 * (CS_KB + kb), 7 * (g1 - 128), BAR(B_FULL1 + kb)); }
        }
      }
      __syncwarp();
      asm volatile("bar.sync 7, 512;" ::: "memory");
      if (lead) {
        if (has1) {
#pragma unroll 1
          for (int kb = G1_NST; kb < 10; kb++) {
            const int s = kb & 3;
            mbar_wait(BAR(B_EMPTY1 + s), ((kb >> 2) - 1) & 1);
            TS(64 + 20 + kb);
            g1_issue(P, sb, s, BAR(B_FULL1 + s), kb, rb, fs);
          }
        }
      }
      __syncwarp();
      if (has1) {
        const uint2* const p0 = P.stats + 128 * rb + lane;
        const uint2* const ps[4] = {p0, p0 + 32, p0 + 64, p0 + 96};
        uint2 sv[4] = {tag_load(ps[0]), tag_load(ps[1]), tag_load(ps[2]), tag_load(ps[3])};
        mbar_wait(BAR(B_EPOCH), 0);
        tag_wait<4>(ps, sv, lds32(sb + OFF_MISC));
#pragma unroll
        for (int j = 0; j < 4; j++) {
          const float mn = -__uint_as_float(sv[j].x), mh = bf_round(mn), sd = rcp_fast(__uint_as_float(sv[j].y)), sh = bf_round(sd);
          sts128(sb + OFF_ST1 + 16 * (lane + 32 * j), make_uint4(pack2(mh, mn - mh), pack2(mh, sh), pack2(sd - sh, 0.f), sv[j].y));
        }
        warp_arrive(BAR(B_TAB));
        TZ(lane, 11);
      }
      if (lead) {
        if (!has1) {
#pragma unroll
          for (int kb = CS_KB + 3; kb < 10; kb++) {
            const int s = kb - CS_KB - 3;
            mbar_wait(BAR(B_EMPTY1 + s), 0);
            mbar_expect(BAR(B_FULL1 + s), CS_STAGE);
            tma3d(sb + s * CS_STAGE, &P.w1_cs, 0, 64 * kb, 7 * (g1 - 128), BAR(B_FULL1 + s));
          }
        }
        auto h_second = [&]() {
#pragma unroll
          for (int w = 0; w < 2; w++) {
            mbar_wait(BAR(B_HS + 4 * w + 1), 0); rfence(2);
            tma2d_st(&P.h_st, 192 * fs + 64, 128 * rb + 64 * w, sb + OFF_X + G1_X + w * 8192);
          }
          TS(37);
          bulk_commit();
          bulk_wait_all();
          mbar_arrive(BAR(B_EMPTY2 + 4)); mbar_arrive(BAR(B_EMPTY2 + 5));
          pub_fence(2);
          h_flag(P, rb, 32);
          TS(27);
        };
        if (has2) {
          prefetch_map(&P.w2);
#pragma unroll 1
          for (int k0 = 0; k0 < 9; k0++) {
#pragma unroll
            for (int u = 0; u < 3; u++) {
              const int kb = 3 * k0 + u, s = 3 * (k0 & 1) + u;
              if (u == 1 && k0 == 1 && has1) h_second();
              if (u == 0 && k0 == 2) { mbar_wait(BAR(B_EPOCH), 0); h_wait(P, tj, 32, lds32(sb + OFF_MISC)); mbar_arrive(BAR(B_H1)); TS(15); }
              mbar_wait(BAR(B_EMPTY2 + s), (k0 >> 1) & 1);
              mbar_expect(BAR(B_FULL2 + s), 16384);
              tma3d(sb + s * G2_STAGE, &P.w2, 0, 64 * g2_block(kb), 2 * dt, BAR(B_FULL2 + s));
            }
          }
        }
        mbar_arrive(BAR(B_DONE));
      }
    }
  }

#undef BAR
}

typedef CUresult (*EncodeFn)(CUtensorMap*, CUtensorMapDataType, cuuint32_t, void*, const cuuint64_t*, const cuuint64_t*, const cuuint32_t*,
                             const cuuint32_t*, CUtensorMapInterleave, CUtensorMapSwizzle, CUtensorMapL2promotion, CUtensorMapFloatOOBfill);

static void enc(EncodeFn f, CUtensorMap* m, const void* base, int rank, const cuuint64_t* dims, const cuuint64_t* strides, const cuuint32_t* box, CUtensorMapSwizzle sw) {
  const cuuint32_t es[5] = {1, 1, 1, 1, 1};
  f(m, CU_TENSOR_MAP_DATA_TYPE_BFLOAT16, rank, const_cast<void*>(base), dims, strides, box, es, CU_TENSOR_MAP_INTERLEAVE_NONE, sw,
    CU_TENSOR_MAP_L2_PROMOTION_L2_128B, CU_TENSOR_MAP_FLOAT_OOB_FILL_NONE);
}
static void enc2(EncodeFn f, CUtensorMap* m, const void* base, uint64_t d0, uint64_t d1, uint32_t b0, uint32_t b1, CUtensorMapSwizzle sw) {
  const cuuint64_t dims[2] = {d0, d1}, strides[1] = {d0 * 2};
  const cuuint32_t box[2] = {b0, b1};
  enc(f, m, base, 2, dims, strides, box, sw);
}

extern "C" void kernel_launch(void* const* d_in, const int* in_sizes, int n_in, void* d_out, int out_size) {
  (void)in_sizes; (void)n_in; (void)out_size;
  static EncodeFn fn = nullptr;
  static void *p_h, *p_kvZ, *p_yT, *p_stats, *p_cs, *p_flags, *p_tab;
  if (!fn) {
    cudaDriverEntryPointQueryResult qr;
    void* f = nullptr;
    cudaGetDriverEntryPoint("cuTensorMapEncodeTiled", &f, cudaEnableDefault, &qr);
    fn = (EncodeFn)f;
    cudaFuncSetAttribute(h3_fused_kernel, cudaFuncAttributeMaxDynamicSharedMemorySize, SMEM_BYTES);
    cudaGetSymbolAddress(&p_h, g_h); cudaGetSymbolAddress(&p_kvZ, g_kvZ); cudaGetSymbolAddress(&p_yT, g_yT);
    cudaGetSymbolAddress(&p_stats, g_stats); cudaGetSymbolAddress(&p_cs, g_cs); cudaGetSymbolAddress(&p_flags, g_flags); cudaGetSymbolAddress(&p_tab, g_tab);
  }
  Params P;
  const bf16 *x = (const bf16*)d_in[0], *k = (const bf16*)d_in[1], *v = (const bf16*)d_in[2];
  const bf16 *w1 = (const bf16*)d_in[7], *w2 = (const bf16*)d_in[9];
  P.x = x; P.shift_k = (const bf16*)d_in[3]; P.ssm_k = (const bf16*)d_in[4]; P.ssm_D = (const bf16*)d_in[5];
  P.b1 = (const bf16*)d_in[8]; P.b2 = (const bf16*)d_in[10]; P.w2p = w2; P.w1p = w1;
  P.zero = 0; P.kvZ = (bf16*)p_kvZ; P.tab = (const uint32_t*)p_tab; P.stats = (uint2*)p_stats; P.cs = (uint2*)p_cs; P.flags = (unsigned*)p_flags;
  enc2(fn, &P.x_g1, x, D_, S_, 64, 128, CU_TENSOR_MAP_SWIZZLE_128B);
  {
    const cuuint64_t dims[3] = {64, D_, 27}, strides[2] = {F_ * 2, 128};
    const cuuint32_t box[3] = {64, 64, 2};
    enc(fn, &P.w1_a, w1, 3, dims, strides, box, CU_TENSOR_MAP_SWIZZLE_128B);
    const cuuint32_t box7[3] = {64, 64, 7};
    enc(fn, &P.w1_cs, w1, 3, dims, strides, box7, CU_TENSOR_MAP_SWIZZLE_128B);
    const cuuint64_t dims2[3] = {32, D_, 54}, strides2[2] = {F_ * 2, 64};
    const cuuint32_t box2[3] = {32, 64, 2}, box1[3] = {32, 64, 1};
    enc(fn, &P.w1_b2, w1, 3, dims2, strides2, box2, CU_TENSOR_MAP_SWIZZLE_64B);
    enc(fn, &P.w1_b1, w1, 3, dims2, strides2, box1, CU_TENSOR_MAP_SWIZZLE_64B);
  }
  enc2(fn, &P.h_ld, p_h, F_, S_, 64, 80, CU_TENSOR_MAP_SWIZZLE_128B);
  {
    const cuuint64_t dims[3] = {64, F_, 10}, strides[2] = {D_ * 2, 128};
    const cuuint32_t box[3] = {64, 64, 2};
    enc(fn, &P.w2, w2, 3, dims, strides, box, CU_TENSOR_MAP_SWIZZLE_128B);
  }
  enc2(fn, &P.h_st, p_h, F_, S_, 64, 64, CU_TENSOR_MAP_SWIZZLE_128B);
  enc2(fn, &P.h_st2, p_h, F_, S_, 32, 64, CU_TENSOR_MAP_SWIZZLE_64B);
  enc2(fn, &P.k, k, D_, S_, 128, 19, CU_TENSOR_MAP_SWIZZLE_NONE);
  enc2(fn, &P.v, v, D_, S_, 128, 16, CU_TENSOR_MAP_SWIZZLE_NONE);
  {
    const cuuint64_t dims[3] = {D_ * 16, 32, 4}, strides[2] = {D_ * 128, D_ * 32};
    const cuuint32_t box[3] = {16, 32, 4};
    enc(fn, &P.kvz, p_kvZ, 3, dims, strides, box, CU_TENSOR_MAP_SWIZZLE_32B);
  }
  enc2(fn, &P.f_ld, P.ssm_k, 64, D_ * 32, 64, 32, CU_TENSOR_MAP_SWIZZLE_128B);
  enc2(fn, &P.y_st, p_yT, 64, D_ * 32, 64, 32, CU_TENSOR_MAP_SWIZZLE_128B);
  enc2(fn, &P.y_ld, p_yT, S_, D_, 80, 128, CU_TENSOR_MAP_SWIZZLE_NONE);
  enc2(fn, &P.x_ep, x, D_, S_, 64, 80, CU_TENSOR_MAP_SWIZZLE_128B);
  enc2(fn, &P.out_st, d_out, D_, S_, 64, 16, CU_TENSOR_MAP_SWIZZLE_128B);
  for (int b = 0; b < 64; b++) P.cnt[b] = 1;
  for (int b = 0; b < 5; b++) { P.cnt[B_CX + b] = 2; P.cnt[B_RD + b] = 4; }
  for (int b = 0; b < 4; b++) P.cnt[B_EMPTY1 + b] = 4;
  for (int b = 0; b < 2 * G2_NST; b++) P.cnt[B_FULL2 + b] = CHK == 3 && b >= G2_NST ? 3 : 2;
  P.cnt[B_DBG] = 4;
  P.cnt[B_G1FREE] = P.cnt[B_GO] = 2; P.cnt[B_TAB] = 3; P.cnt[B_EP] = 5; P.cnt[B_DONE] = 6;
  for (int b = 0; b < 8; b++) P.cnt[B_HS + b] = 4;
  P.cnt[B_KVS] = P.cnt[B_KVS + 1] = P.cnt[B_STATFREE] = 4; P.cnt[B_KVS + 2] = 2;
  {
    int mem[9][18], cnt[9] = {0};
    for (int b = 0; b < NCTA; b++) {
      const int tpc = b >> 1;
      const int gp = tpc < 32 ? tpc % 8 : tpc < 60 ? 1 + (tpc - 32) % 7 : tpc < 62 ? tpc - 54 : 8;
      mem[gp][cnt[gp]++] = b;
      P.map[b] = make_uchar4(255, 255, gp, 0);
    }
    const int bi[8] = {0, 0, 0, 1, 1, 2, 3, 2}, bj[8] = {0, 0, 1, 0, 1, 0, 0, 1};
    for (int gp = 1; gp < 8; gp++)
      for (int i = 0; i < 16; i++) P.map[mem[gp][i]].x = (4 * bi[gp] + (i & 3)) * 8 + 4 * bj[gp] + (i >> 2);
    for (int i = 0; i < 8; i++) P.map[mem[0][i]].x = (12 + (i & 3)) * 8 + 4 + (i >> 2);
    for (int i = 0; i < 2; i++) { P.map[mem[6][16 + i]].x = (12 + i) * 8 + 6; P.map[mem[7][16 + i]].x = (14 + i) * 8 + 6; }
    for (int i = 0; i < 4; i++) { P.map[mem[8][i]].x = (12 + i) * 8 + 7; P.map[mem[8][4 + i]].x = 128 + i; }
    const int ord[9] = {6, 1, 2, 0, 8, 7, 3, 4, 5};
    int n = 0;
    for (int q = 0; q < 9; q++)
      for (int i = 0; i < (ord[q] == 8 ? 6 : cnt[ord[q]]); i++, n++) { P.map[mem[ord[q]][i]].y = n / 5 * 8 + n % 5; P.map[mem[ord[q]][i]].w = ord[q] == 8 ? 6 : cnt[ord[q]]; }
  }
  h3_fused_kernel<<<NCTA, 512, SMEM_BYTES, cudaStreamPerThread>>>(P);
}
```

```cpp
#include <cuda_runtime.h>
#include <cuda_bf16.h>
#include <cuda.h>
#include <stdint.h>
#include <stdlib.h>

#define K4E 0
#define INIT_SEQ S(1) S(2) S(3) K(0) K(1) T
#define AUX_PRE
#define AUX_SEQ AUX_PRE W(B_KVS) PUBA W(B_STATFREE) KC F(0) PF(1) G(0) X(0) PF(2) PF(3) PUBB X(1) F(1) FLB PF(4) PW PUBC A(B_KVC) F(2) FLC W(B_G1FREE) F(3) G(1) X(3) X(2) G(2) W(B_RD) X(4) F(4) AUX_END
#define G1V 2
#define G2MAP "BBBBB BBBBB BBBBB BCCCC CCCCC CCCCC CCDDD DDDDD DDDDD DDDGG GGGGG GGGGG GGGGG HHHHH HHHHH HHHHH HHEEE EEEEE EEEEE EEssE AAAAA AAAAA AAttF FFFFF FFFFF FFFFF"
#define GOMAP "0123456745"
#define SP_D0 0
#define SP_D1 0
#define PRE 0
#define RM (PRE == 1)
#define AUX_END Y(0) Y(1) Y(2) Y(3) R XE Y(4)
#define SPEC 1
#define NCH 5
#define TAB_AT 0
#define NORM_AT 1
#define GO5 1
#define XE_AT 1
#define YPRE 0
#define B1E 1
#define STE 10
#define NOW 10
#define CH_W0 0xf2
#define CH_W1 0xf3
#define CH_W2 0xf410
#define CS_KB 5
#define CHK 3
#define MIM 1
#define KVCHK 1
#define FB 1
#define DFT_EARLY 3
#define GO_WG 4
#define EREL 0
#define PFW 0
#define SK2 2
#define YK 26
#define DFT_AT 16
#define USE_GO 1
#define GO_AT 2
#define HS_LAG 0
#define LOOKAHEAD 2
#define SPLIT9 0
#define GELU_BF16 4
#define R_G 160
#define R_P 32
#define DBG_TIME 0

namespace {

constexpr int GO_N = (GO_WG & 1) + ((GO_WG >> 1) & 1) + (GO_WG >> 2);
constexpr int S_ = 2048, D_ = 640, F_ = 1728;
constexpr int NCTA = 132;
typedef __nv_bfloat16 bf16;

__device__ __align__(1024) bf16 g_h[S_ * F_];
__device__ __align__(1024) bf16 g_kvZ[D_ * S_];
__device__ __align__(1024) bf16 g_yT[D_ * S_];
__device__ __align__(128) uint2 g_stats[S_];
constexpr int CSP = F_ / 2 + 32;
__device__ __align__(128) uint2 g_cs[2 * CSP];
constexpr int FL_EPOCH = 0, FL_START = 32, FL_KV = 64  , FL_Y = FL_KV + 3 * 32, FL_H = FL_Y + 32  , FL_G2 = FL_H + 96 * 32  , FL_COUNT = FL_G2 + 9 * 32;
__device__ __align__(128) unsigned g_flags[FL_COUNT];
__device__ __align__(128) const uint32_t g_tab[6144] = {
0x3f803f80,0x3f803f80,0x3f803f80,0x3f803f80,0x3f803f80,0x3f803f80,0x3f803f80,0x3f803f80,0x3f803f80,0x3f803f80,0x3f803f80,0x3f803f80,0x3f803f80,0x3f803f80,0x3f803f80,0x3f803f80,
0x0,0x0,0x0,0x0,0x0,0x0,0x0,0x0,0x0,0x0,0x0,0x0,0x0,0x0,0x0,0x0,
0x3f183f2c,0x3edb3f04,0x3e793eac,0x3d493e16,0x3f7d3f80,0x3f713f78,0x3f5c3f67,0x3f3e3f4e,0xbf4ebf3e,0xbf67bf5c,0xbf78bf71,0xbf80bf7d,0xbe16bd49,0xbeacbe79,0xbf04bedb,0xbf2cbf18,
0x3f4e3f3e,0x3f673f5c,0x3f783f71,0x3f803f7d,0x3e163d49,0x3eac3e79,0x3f043edb,0x3f2c3f18,0x3f183f2c,0x3edb3f04,0x3e793eac,0x3d493e16,0x3f7d3f80,0x3f713f78,0x3f5c3f67,0x3f3e3f4e,
0xbf75bf7f,0xbf46bf62,0xbef1bf22,0xbdc9be95,0x3e953dc9,0x3f223ef1,0x3f623f46,0x3f7f3f75,0x3f753f7f,0x3f463f62,0x3ef13f22,0x3dc93e95,0xbe95bdc9,0xbf22bef1,0xbf62bf46,0xbf7fbf75,
0xbe95bdc9,0xbf22bef1,0xbf62bf46,0xbf7fbf75,0xbf75bf7f,0xbf46bf62,0xbef1bf22,0xbdc9be95,0x3e953dc9,0x3f223ef1,0x3f623f46,0x3f7f3f75,0x3f753f7f,0x3f463f62,0x3ef13f22,0x3dc93e95,
0x3eac3f18,0xbe793d49,0xbf3ebf04,0xbf7dbf67,0x3edb3e16,0x3f5c3f2c,0x3f803f78,0x3f4e3f71,0xbf71bf4e,0xbf78bf80,0xbf2cbf5c,0xbe16bedb,0x3f673f7d,0x3f043f3e,0xbd493e79,0xbf18beac,
0x3f713f4e,0x3f783f80,0x3f2c3f5c,0x3e163edb,0xbf67bf7d,0xbf04bf3e,0x3d49be79,0x3f183eac,0x3eac3f18,0xbe793d49,0xbf3ebf04,0xbf7dbf67,0x3edb3e16,0x3f5c3f2c,0x3f803f78,0x3f4e3f71,
0x3f0e3e48,0x3f7b3f55,0x3f553f7b,0x3e483f0e,0xbf0ebe48,0xbf7bbf55,0xbf55bf7b,0xbe48bf0e,0x3f0e3e48,0x3f7b3f55,0x3f553f7b,0x3e483f0e,0xbf0ebe48,0xbf7bbf55,0xbf55bf7b,0xbe48bf0e,
0x3f553f7b,0x3e483f0e,0xbf0ebe48,0xbf7bbf55,0xbf55bf7b,0xbe48bf0e,0x3f0e3e48,0x3f7b3f55,0x3f553f7b,0x3e483f0e,0xbf0ebe48,0xbf7bbf55,0xbf55bf7b,0xbe48bf0e,0x3f0e3e48,0x3f7b3f55,
0xbf80bf5c,0xbf18bf67,0x3eacbe16,0x3f783f3e,0x3f2c3e79,0x3f7d3f71,0x3edb3f4e,0xbf04bd49,0xbd49bf04,0x3f4e3edb,0x3f713f7d,0x3e793f2c,0x3f3e3f78,0xbe163eac,0xbf67bf18,0xbf5cbf80,
0xbd49bf04,0x3f4e3edb,0x3f713f7d,0x3e793f2c,0x3f3e3f78,0xbe163eac,0xbf67bf18,0xbf5cbf80,0x3f803f5c,0x3f183f67,0xbeac3e16,0xbf78bf3e,0xbf2cbe79,0xbf7dbf71,0xbedbbf4e,0x3f043d49,
0xbf46be95,0xbf62bf7f,0x3dc9bef1,0x3f753f22,0x3f223f75,0xbef13dc9,0xbf7fbf62,0xbe95bf46,0x3f463e95,0x3f623f7f,0xbdc93ef1,0xbf75bf22,0xbf22bf75,0x3ef1bdc9,0x3f7f3f62,0x3e953f46,
0xbf22bf75,0x3ef1bdc9,0x3f7f3f62,0x3e953f46,0xbf46be95,0xbf62bf7f,0x3dc9bef1,0x3f753f22,0x3f223f75,0xbef13dc9,0xbf7fbf62,0xbe95bf46,0x3f463e95,0x3f623f7f,0xbdc93ef1,0xbf75bf22,
0xbf78bf67,0x3d49bf18,0x3f7d3f2c,0x3eac3f5c,0xbf04bf71,0x3f3e3e16,0x3f4e3f80,0xbedb3e79,0x3e79bedb,0x3f803f4e,0x3e163f3e,0xbf71bf04,0x3f5c3eac,0x3f2c3f7d,0xbf183d49,0xbf67bf78,
0x3e79bedb,0x3f803f4e,0x3e163f3e,0xbf71bf04,0x3f5c3eac,0x3f2c3f7d,0xbf183d49,0xbf67bf78,0x3f783f67,0xbd493f18,0xbf7dbf2c,0xbeacbf5c,0x3f043f71,0xbf3ebe16,0xbf4ebf80,0x3edbbe79,
0x3ec43f6d,0xbf6dbec4,0xbec4bf6d,0x3f6d3ec4,0x3ec43f6d,0xbf6dbec4,0xbec4bf6d,0x3f6d3ec4,0x3ec43f6d,0xbf6dbec4,0xbec4bf6d,0x3f6d3ec4,0x3ec43f6d,0xbf6dbec4,0xbec4bf6d,0x3f6d3ec4,
0x3f6d3ec4,0x3ec43f6d,0xbf6dbec4,0xbec4bf6d,0x3f6d3ec4,0x3ec43f6d,0xbf6dbec4,0xbec4bf6d,0x3f6d3ec4,0x3ec43f6d,0xbf6dbec4,0xbec4bf6d,0x3f6d3ec4,0x3ec43f6d,0xbf6dbec4,0xbec4bf6d,
0xbf043eac,0xbf3ebf7d,0x3f4e3d49,0x3edb3f78,0x3e793f67,0xbf80bf18,0x3e16bf2c,0x3f713f5c,0xbf5cbf71,0x3f2cbe16,0x3f183f80,0xbf67be79,0xbf78bedb,0xbd49bf4e,0x3f7d3f3e,0xbeac3f04,
0x3f5c3f71,0xbf2c3e16,0xbf18bf80,0x3f673e79,0x3f783edb,0x3d493f4e,0xbf7dbf3e,0x3eacbf04,0xbf043eac,0xbf3ebf7d,0x3f4e3d49,0x3edb3f78,0x3e793f67,0xbf80bf18,0x3e16bf2c,0x3f713f5c,
0xbdc9bf62,0x3f753f46,0xbf223e95,0xbef1bf7f,0x3f7f3ef1,0xbe953f22,0xbf46bf75,0x3f623dc9,0x3dc93f62,0xbf75bf46,0x3f22be95,0x3ef13f7f,0xbf7fbef1,0x3e95bf22,0x3f463f75,0xbf62bdc9,
0xbf7fbef1,0x3e95bf22,0x3f463f75,0xbf62bdc9,0xbdc9bf62,0x3f753f46,0xbf223e95,0xbef1bf7f,0x3f7f3ef1,0xbe953f22,0xbf46bf75,0x3f623dc9,0x3dc93f62,0xbf75bf46,0x3f22be95,0x3ef13f7f,
0xbf3e3e79,0xbe16bf71,0x3f673f4e,0xbf5c3d49,0x3f803f04,0xbf183edb,0xbeacbf7d,0x3f783f2c,0xbf2cbf78,0x3f7d3eac,0xbedb3f18,0xbf04bf80,0xbd493f5c,0xbf4ebf67,0x3f713e16,0xbe793f3e,
0x3f2c3f78,0xbf7dbeac,0x3edbbf18,0x3f043f80,0x3d49bf5c,0x3f4e3f67,0xbf71be16,0x3e79bf3e,0xbf3e3e79,0xbe16bf71,0x3f673f4e,0xbf5c3d49,0x3f803f04,0xbf183edb,0xbeacbf7d,0x3f783f2c,
0x3f7b3f0e,0xbf553e48,0x3e48bf55,0x3f0e3f7b,0xbf7bbf0e,0x3f55be48,0xbe483f55,0xbf0ebf7b,0x3f7b3f0e,0xbf553e48,0x3e48bf55,0x3f0e3f7b,0xbf7bbf0e,0x3f55be48,0xbe483f55,0xbf0ebf7b,
0xbe483f55,0xbf0ebf7b,0x3f7b3f0e,0xbf553e48,0x3e48bf55,0x3f0e3f7b,0xbf7bbf0e,0x3f55be48,0xbe483f55,0xbf0ebf7b,0x3f7b3f0e,0xbf553e48,0x3e48bf55,0x3f0e3f7b,0xbf7bbf0e,0x3f55be48,
0xbedbbf7d,0x3f5c3f3e,0xbf80be79,0x3f4ebeac,0x3f713f18,0xbf78bd49,0x3f2cbf04,0xbe163f67,0x3f67be16,0xbf043f2c,0xbd49bf78,0x3f183f71,0xbeac3f4e,0xbe79bf80,0x3f3e3f5c,0xbf7dbedb,
0x3f67be16,0xbf043f2c,0xbd49bf78,0x3f183f71,0xbeac3f4e,0xbe79bf80,0x3f3e3f5c,0xbf7dbedb,0x3edb3f7d,0xbf5cbf3e,0x3f803e79,0xbf4e3eac,0xbf71bf18,0x3f783d49,0xbf2c3f04,0x3e16bf67,
0xbf62bf22,0x3f7f3e95,0xbf753dc9,0x3f46bef1,0xbef13f46,0x3dc9bf75,0x3e953f7f,0xbf22bf62,0x3f623f22,0xbf7fbe95,0x3f75bdc9,0xbf463ef1,0x3ef1bf46,0xbdc93f75,0xbe95bf7f,0x3f223f62,
0x3ef1bf46,0xbdc93f75,0xbe95bf7f,0x3f223f62,0xbf62bf22,0x3f7f3e95,0xbf753dc9,0x3f46bef1,0xbef13f46,0x3dc9bf75,0x3e953f7f,0xbf22bf62,0x3f623f22,0xbf7fbe95,0x3f75bdc9,0xbf463ef1,
0xbe16bf80,0x3eac3f78,0xbf04bf67,0x3f2c3f4e,0x3f18bf3e,0xbedb3f5c,0x3e79bf71,0xbd493f7d,0x3f7dbd49,0xbf713e79,0x3f5cbedb,0xbf3e3f18,0x3f4e3f2c,0xbf67bf04,0x3f783eac,0xbf80be16,
0x3f7dbd49,0xbf713e79,0x3f5cbedb,0xbf3e3f18,0x3f4e3f2c,0xbf67bf04,0x3f783eac,0xbf80be16,0x3e163f80,0xbeacbf78,0x3f043f67,0xbf2cbf4e,0xbf183f3e,0x3edbbf5c,0xbe793f71,0x3d49bf7d,
0xbf353f35,0x3f35bf35,0xbf353f35,0x3f35bf35,0xbf353f35,0x3f35bf35,0xbf353f35,0x3f35bf35,0xbf353f35,0x3f35bf35,0xbf353f35,0x3f35bf35,0xbf353f35,0x3f35bf35,0xbf353f35,0x3f35bf35,
0x3f353f35,0xbf35bf35,0x3f353f35,0xbf35bf35,0x3f353f35,0xbf35bf35,0x3f353f35,0xbf35bf35,0x3f353f35,0xbf35bf35,0x3f353f35,0xbf35bf35,0x3f353f35,0xbf35bf35,0x3f353f35,0xbf35bf35,
0xbf7dbd49,0x3f713e79,0xbf5cbedb,0x3f3e3f18,0xbf4e3f2c,0x3f67bf04,0xbf783eac,0x3f80be16,0x3e16bf80,0xbeac3f78,0x3f04bf67,0xbf2c3f4e,0xbf18bf3e,0x3edb3f5c,0xbe79bf71,0x3d493f7d,
0xbe163f80,0x3eacbf78,0xbf043f67,0x3f2cbf4e,0x3f183f3e,0xbedbbf5c,0x3e793f71,0xbd49bf7d,0xbf7dbd49,0x3f713e79,0xbf5cbedb,0x3f3e3f18,0xbf4e3f2c,0x3f67bf04,0xbf783eac,0x3f80be16,
0x3f62bf22,0xbf7f3e95,0x3f753dc9,0xbf46bef1,0x3ef13f46,0xbdc9bf75,0xbe953f7f,0x3f22bf62,0xbf623f22,0x3f7fbe95,0xbf75bdc9,0x3f463ef1,0xbef1bf46,0x3dc93f75,0x3e95bf7f,0xbf223f62,
0xbef1bf46,0x3dc93f75,0x3e95bf7f,0xbf223f62,0x3f62bf22,0xbf7f3e95,0x3f753dc9,0xbf46bef1,0x3ef13f46,0xbdc9bf75,0xbe953f7f,0x3f22bf62,0xbf623f22,0x3f7fbe95,0xbf75bdc9,0x3f463ef1,
0xbf67be16,0x3f043f2c,0x3d49bf78,0xbf183f71,0x3eac3f4e,0x3e79bf80,0xbf3e3f5c,0x3f7dbedb,0x3edbbf7d,0xbf5c3f3e,0x3f80be79,0xbf4ebeac,0xbf713f18,0x3f78bd49,0xbf2cbf04,0x3e163f67,
0xbedb3f7d,0x3f5cbf3e,0xbf803e79,0x3f4e3eac,0x3f71bf18,0xbf783d49,0x3f2c3f04,0xbe16bf67,0xbf67be16,0x3f043f2c,0x3d49bf78,0xbf183f71,0x3eac3f4e,0x3e79bf80,0xbf3e3f5c,0x3f7dbedb,
0x3e483f55,0x3f0ebf7b,0xbf7b3f0e,0x3f553e48,0xbe48bf55,0xbf0e3f7b,0x3f7bbf0e,0xbf55be48,0x3e483f55,0x3f0ebf7b,0xbf7b3f0e,0x3f553e48,0xbe48bf55,0xbf0e3f7b,0x3f7bbf0e,0xbf55be48,
0xbf7b3f0e,0x3f553e48,0xbe48bf55,0xbf0e3f7b,0x3f7bbf0e,0xbf55be48,0x3e483f55,0x3f0ebf7b,0xbf7b3f0e,0x3f553e48,0xbe48bf55,0xbf0e3f7b,0x3f7bbf0e,0xbf55be48,0x3e483f55,0x3f0ebf7b,
0x3f2cbf78,0xbf7d3eac,0x3edb3f18,0x3f04bf80,0x3d493f5c,0x3f4ebf67,0xbf713e16,0x3e793f3e,0x3f3e3e79,0x3e16bf71,0xbf673f4e,0x3f5c3d49,0xbf803f04,0x3f183edb,0x3eacbf7d,0xbf783f2c,
0x3f3e3e79,0x3e16bf71,0xbf673f4e,0x3f5c3d49,0xbf803f04,0x3f183edb,0x3eacbf7d,0xbf783f2c,0xbf2c3f78,0x3f7dbeac,0xbedbbf18,0xbf043f80,0xbd49bf5c,0xbf4e3f67,0x3f71be16,0xbe79bf3e,
0x3dc9bf62,0xbf753f46,0x3f223e95,0x3ef1bf7f,0xbf7f3ef1,0x3e953f22,0x3f46bf75,0xbf623dc9,0xbdc93f62,0x3f75bf46,0xbf22be95,0xbef13f7f,0x3f7fbef1,0xbe95bf22,0xbf463f75,0x3f62bdc9,
0x3f7fbef1,0xbe95bf22,0xbf463f75,0x3f62bdc9,0x3dc9bf62,0xbf753f46,0x3f223e95,0x3ef1bf7f,0xbf7f3ef1,0x3e953f22,0x3f46bf75,0xbf623dc9,0xbdc93f62,0x3f75bf46,0xbf22be95,0xbef13f7f,
0x3f5cbf71,0xbf2cbe16,0xbf183f80,0x3f67be79,0x3f78bedb,0x3d49bf4e,0xbf7d3f3e,0x3eac3f04,0x3f043eac,0x3f3ebf7d,0xbf4e3d49,0xbedb3f78,0xbe793f67,0x3f80bf18,0xbe16bf2c,0xbf713f5c,
0x3f043eac,0x3f3ebf7d,0xbf4e3d49,0xbedb3f78,0xbe793f67,0x3f80bf18,0xbe16bf2c,0xbf713f5c,0xbf5c3f71,0x3f2c3e16,0x3f18bf80,0xbf673e79,0xbf783edb,0xbd493f4e,0x3f7dbf3e,0xbeacbf04,
0xbf6d3ec4,0xbec43f6d,0x3f6dbec4,0x3ec4bf6d,0xbf6d3ec4,0xbec43f6d,0x3f6dbec4,0x3ec4bf6d,0xbf6d3ec4,0xbec43f6d,0x3f6dbec4,0x3ec4bf6d,0xbf6d3ec4,0xbec43f6d,0x3f6dbec4,0x3ec4bf6d,
0xbec43f6d,0x3f6dbec4,0x3ec4bf6d,0xbf6d3ec4,0xbec43f6d,0x3f6dbec4,0x3ec4bf6d,0xbf6d3ec4,0xbec43f6d,0x3f6dbec4,0x3ec4bf6d,0xbf6d3ec4,0xbec43f6d,0x3f6dbec4,0x3ec4bf6d,0xbf6d3ec4,
0xbe79bedb,0xbf803f4e,0xbe163f3e,0x3f71bf04,0xbf5c3eac,0xbf2c3f7d,0x3f183d49,0x3f67bf78,0x3f78bf67,0xbd49bf18,0xbf7d3f2c,0xbeac3f5c,0x3f04bf71,0xbf3e3e16,0xbf4e3f80,0x3edb3e79,
0xbf783f67,0x3d493f18,0x3f7dbf2c,0x3eacbf5c,0xbf043f71,0x3f3ebe16,0x3f4ebf80,0xbedbbe79,0xbe79bedb,0xbf803f4e,0xbe163f3e,0x3f71bf04,0xbf5c3eac,0xbf2c3f7d,0x3f183d49,0x3f67bf78,
0x3f46be95,0x3f62bf7f,0xbdc9bef1,0xbf753f22,0xbf223f75,0x3ef13dc9,0x3f7fbf62,0x3e95bf46,0xbf463e95,0xbf623f7f,0x3dc93ef1,0x3f75bf22,0x3f22bf75,0xbef1bdc9,0xbf7f3f62,0xbe953f46,
0x3f22bf75,0xbef1bdc9,0xbf7f3f62,0xbe953f46,0x3f46be95,0x3f62bf7f,0xbdc9bef1,0xbf753f22,0xbf223f75,0x3ef13dc9,0x3f7fbf62,0x3e95bf46,0xbf463e95,0xbf623f7f,0x3dc93ef1,0x3f75bf22,
0x3d49bf04,0xbf4e3edb,0xbf713f7d,0xbe793f2c,0xbf3e3f78,0x3e163eac,0x3f67bf18,0x3f5cbf80,0x3f80bf5c,0x3f18bf67,0xbeacbe16,0xbf783f3e,0xbf2c3e79,0xbf7d3f71,0xbedb3f4e,0x3f04bd49,
0xbf803f5c,0xbf183f67,0x3eac3e16,0x3f78bf3e,0x3f2cbe79,0x3f7dbf71,0x3edbbf4e,0xbf043d49,0x3d49bf04,0xbf4e3edb,0xbf713f7d,0xbe793f2c,0xbf3e3f78,0x3e163eac,0x3f67bf18,0x3f5cbf80,
0xbf553f7b,0xbe483f0e,0x3f0ebe48,0x3f7bbf55,0x3f55bf7b,0x3e48bf0e,0xbf0e3e48,0xbf7b3f55,0xbf553f7b,0xbe483f0e,0x3f0ebe48,0x3f7bbf55,0x3f55bf7b,0x3e48bf0e,0xbf0e3e48,0xbf7b3f55,
0xbf0e3e48,0xbf7b3f55,0xbf553f7b,0xbe483f0e,0x3f0ebe48,0x3f7bbf55,0x3f55bf7b,0x3e48bf0e,0xbf0e3e48,0xbf7b3f55,0xbf553f7b,0xbe483f0e,0x3f0ebe48,0x3f7bbf55,0x3f55bf7b,0x3e48bf0e,
0x3f71bf4e,0x3f78bf80,0x3f2cbf5c,0x3e16bedb,0xbf673f7d,0xbf043f3e,0x3d493e79,0x3f18beac,0xbeac3f18,0x3e793d49,0x3f3ebf04,0x3f7dbf67,0xbedb3e16,0xbf5c3f2c,0xbf803f78,0xbf4e3f71,
0xbeac3f18,0x3e793d49,0x3f3ebf04,0x3f7dbf67,0xbedb3e16,0xbf5c3f2c,0xbf803f78,0xbf4e3f71,0xbf713f4e,0xbf783f80,0xbf2c3f5c,0xbe163edb,0x3f67bf7d,0x3f04bf3e,0xbd49be79,0xbf183eac,
0x3f75bf7f,0x3f46bf62,0x3ef1bf22,0x3dc9be95,0xbe953dc9,0xbf223ef1,0xbf623f46,0xbf7f3f75,0xbf753f7f,0xbf463f62,0xbef13f22,0xbdc93e95,0x3e95bdc9,0x3f22bef1,0x3f62bf46,0x3f7fbf75,
0x3e95bdc9,0x3f22bef1,0x3f62bf46,0x3f7fbf75,0x3f75bf7f,0x3f46bf62,0x3ef1bf22,0x3dc9be95,0xbe953dc9,0xbf223ef1,0xbf623f46,0xbf7f3f75,0xbf753f7f,0xbf463f62,0xbef13f22,0xbdc93e95,
0x3f4ebf3e,0x3f67bf5c,0x3f78bf71,0x3f80bf7d,0x3e16bd49,0x3eacbe79,0x3f04bedb,0x3f2cbf18,0xbf183f2c,0xbedb3f04,0xbe793eac,0xbd493e16,0xbf7d3f80,0xbf713f78,0xbf5c3f67,0xbf3e3f4e,
0xbf183f2c,0xbedb3f04,0xbe793eac,0xbd493e16,0xbf7d3f80,0xbf713f78,0xbf5c3f67,0xbf3e3f4e,0xbf4e3f3e,0xbf673f5c,0xbf783f71,0xbf803f7d,0xbe163d49,0xbeac3e79,0xbf043edb,0xbf2c3f18,
0xa554248d,0xa5f725b0,0xa731261f,0xa742a68d,0xa754a654,0xa765a60d,0xa777a58e,0xa784a137,0xa78d258d,0xa796260d,0xa79f280d,0x2731268d,0xa7b12816,0x270d26d4,0xa7c2281f,0x26d4270d,
0xbf803f80,0xbf803f80,0xbf803f80,0xbf803f80,0xbf803f80,0xbf803f80,0xbf803f80,0xbf803f80,0xbf803f80,0xbf803f80,0xbf803f80,0xbf803f80,0xbf803f80,0xbf803f80,0xbf803f80,0xbf803f80,
0x3f4ebf3e,0x3f67bf5c,0x3f78bf71,0x3f80bf7d,0x3e16bd49,0x3eacbe79,0x3f04bedb,0x3f2cbf18,0x3f18bf2c,0x3edbbf04,0x3e79beac,0x3d49be16,0x3f7dbf80,0x3f71bf78,0x3f5cbf67,0x3f3ebf4e,
0xbf183f2c,0xbedb3f04,0xbe793eac,0xbd493e16,0xbf7d3f80,0xbf713f78,0xbf5c3f67,0xbf3e3f4e,0x3f4ebf3e,0x3f67bf5c,0x3f78bf71,0x3f80bf7d,0x3e16bd49,0x3eacbe79,0x3f04bedb,0x3f2cbf18,
0xbe953dc9,0xbf223ef1,0xbf623f46,0xbf7f3f75,0xbf753f7f,0xbf463f62,0xbef13f22,0xbdc93e95,0x3e95bdc9,0x3f22bef1,0x3f62bf46,0x3f7fbf75,0x3f75bf7f,0x3f46bf62,0x3ef1bf22,0x3dc9be95,
0x3f75bf7f,0x3f46bf62,0x3ef1bf22,0x3dc9be95,0xbe953dc9,0xbf223ef1,0xbf623f46,0xbf7f3f75,0xbf753f7f,0xbf463f62,0xbef13f22,0xbdc93e95,0x3e95bdc9,0x3f22bef1,0x3f62bf46,0x3f7fbf75,
0x3f71bf4e,0x3f78bf80,0x3f2cbf5c,0x3e16bedb,0xbf673f7d,0xbf043f3e,0x3d493e79,0x3f18beac,0x3eacbf18,0xbe79bd49,0xbf3e3f04,0xbf7d3f67,0x3edbbe16,0x3f5cbf2c,0x3f80bf78,0x3f4ebf71,
0xbeac3f18,0x3e793d49,0x3f3ebf04,0x3f7dbf67,0xbedb3e16,0xbf5c3f2c,0xbf803f78,0xbf4e3f71,0x3f71bf4e,0x3f78bf80,0x3f2cbf5c,0x3e16bedb,0xbf673f7d,0xbf043f3e,0x3d493e79,0x3f18beac,
0xbf553f7b,0xbe483f0e,0x3f0ebe48,0x3f7bbf55,0x3f55bf7b,0x3e48bf0e,0xbf0e3e48,0xbf7b3f55,0xbf553f7b,0xbe483f0e,0x3f0ebe48,0x3f7bbf55,0x3f55bf7b,0x3e48bf0e,0xbf0e3e48,0xbf7b3f55,
0x3f0ebe48,0x3f7bbf55,0x3f55bf7b,0x3e48bf0e,0xbf0e3e48,0xbf7b3f55,0xbf553f7b,0xbe483f0e,0x3f0ebe48,0x3f7bbf55,0x3f55bf7b,0x3e48bf0e,0xbf0e3e48,0xbf7b3f55,0xbf553f7b,0xbe483f0e,
0x3d49bf04,0xbf4e3edb,0xbf713f7d,0xbe793f2c,0xbf3e3f78,0x3e163eac,0x3f67bf18,0x3f5cbf80,0xbf803f5c,0xbf183f67,0x3eac3e16,0x3f78bf3e,0x3f2cbe79,0x3f7dbf71,0x3edbbf4e,0xbf043d49,
0xbf803f5c,0xbf183f67,0x3eac3e16,0x3f78bf3e,0x3f2cbe79,0x3f7dbf71,0x3edbbf4e,0xbf043d49,0xbd493f04,0x3f4ebedb,0x3f71bf7d,0x3e79bf2c,0x3f3ebf78,0xbe16beac,0xbf673f18,0xbf5c3f80,
0x3f22bf75,0xbef1bdc9,0xbf7f3f62,0xbe953f46,0x3f46be95,0x3f62bf7f,0xbdc9bef1,0xbf753f22,0xbf223f75,0x3ef13dc9,0x3f7fbf62,0x3e95bf46,0xbf463e95,0xbf623f7f,0x3dc93ef1,0x3f75bf22,
0xbf463e95,0xbf623f7f,0x3dc93ef1,0x3f75bf22,0x3f22bf75,0xbef1bdc9,0xbf7f3f62,0xbe953f46,0x3f46be95,0x3f62bf7f,0xbdc9bef1,0xbf753f22,0xbf223f75,0x3ef13dc9,0x3f7fbf62,0x3e95bf46,
0xbe79bedb,0xbf803f4e,0xbe163f3e,0x3f71bf04,0xbf5c3eac,0xbf2c3f7d,0x3f183d49,0x3f67bf78,0xbf783f67,0x3d493f18,0x3f7dbf2c,0x3eacbf5c,0xbf043f71,0x3f3ebe16,0x3f4ebf80,0xbedbbe79,
0xbf783f67,0x3d493f18,0x3f7dbf2c,0x3eacbf5c,0xbf043f71,0x3f3ebe16,0x3f4ebf80,0xbedbbe79,0x3e793edb,0x3f80bf4e,0x3e16bf3e,0xbf713f04,0x3f5cbeac,0x3f2cbf7d,0xbf18bd49,0xbf673f78,
0x3f6dbec4,0x3ec4bf6d,0xbf6d3ec4,0xbec43f6d,0x3f6dbec4,0x3ec4bf6d,0xbf6d3ec4,0xbec43f6d,0x3f6dbec4,0x3ec4bf6d,0xbf6d3ec4,0xbec43f6d,0x3f6dbec4,0x3ec4bf6d,0xbf6d3ec4,0xbec43f6d,
0xbec43f6d,0x3f6dbec4,0x3ec4bf6d,0xbf6d3ec4,0xbec43f6d,0x3f6dbec4,0x3ec4bf6d,0xbf6d3ec4,0xbec43f6d,0x3f6dbec4,0x3ec4bf6d,0xbf6d3ec4,0xbec43f6d,0x3f6dbec4,0x3ec4bf6d,0xbf6d3ec4,
0x3f5cbf71,0xbf2cbe16,0xbf183f80,0x3f67be79,0x3f78bedb,0x3d49bf4e,0xbf7d3f3e,0x3eac3f04,0xbf04beac,0xbf3e3f7d,0x3f4ebd49,0x3edbbf78,0x3e79bf67,0xbf803f18,0x3e163f2c,0x3f71bf5c,
0x3f043eac,0x3f3ebf7d,0xbf4e3d49,0xbedb3f78,0xbe793f67,0x3f80bf18,0xbe16bf2c,0xbf713f5c,0x3f5cbf71,0xbf2cbe16,0xbf183f80,0x3f67be79,0x3f78bedb,0x3d49bf4e,0xbf7d3f3e,0x3eac3f04,
0xbf7f3ef1,0x3e953f22,0x3f46bf75,0xbf623dc9,0xbdc93f62,0x3f75bf46,0xbf22be95,0xbef13f7f,0x3f7fbef1,0xbe95bf22,0xbf463f75,0x3f62bdc9,0x3dc9bf62,0xbf753f46,0x3f223e95,0x3ef1bf7f,
0x3dc9bf62,0xbf753f46,0x3f223e95,0x3ef1bf7f,0xbf7f3ef1,0x3e953f22,0x3f46bf75,0xbf623dc9,0xbdc93f62,0x3f75bf46,0xbf22be95,0xbef13f7f,0x3f7fbef1,0xbe95bf22,0xbf463f75,0x3f62bdc9,
0x3f2cbf78,0xbf7d3eac,0x3edb3f18,0x3f04bf80,0x3d493f5c,0x3f4ebf67,0xbf713e16,0x3e793f3e,0xbf3ebe79,0xbe163f71,0x3f67bf4e,0xbf5cbd49,0x3f80bf04,0xbf18bedb,0xbeac3f7d,0x3f78bf2c,
0x3f3e3e79,0x3e16bf71,0xbf673f4e,0x3f5c3d49,0xbf803f04,0x3f183edb,0x3eacbf7d,0xbf783f2c,0x3f2cbf78,0xbf7d3eac,0x3edb3f18,0x3f04bf80,0x3d493f5c,0x3f4ebf67,0xbf713e16,0x3e793f3e,
0x3e483f55,0x3f0ebf7b,0xbf7b3f0e,0x3f553e48,0xbe48bf55,0xbf0e3f7b,0x3f7bbf0e,0xbf55be48,0x3e483f55,0x3f0ebf7b,0xbf7b3f0e,0x3f553e48,0xbe48bf55,0xbf0e3f7b,0x3f7bbf0e,0xbf55be48,
0x3f7bbf0e,0xbf55be48,0x3e483f55,0x3f0ebf7b,0xbf7b3f0e,0x3f553e48,0xbe48bf55,0xbf0e3f7b,0x3f7bbf0e,0xbf55be48,0x3e483f55,0x3f0ebf7b,0xbf7b3f0e,0x3f553e48,0xbe48bf55,0xbf0e3f7b,
0xbf67be16,0x3f043f2c,0x3d49bf78,0xbf183f71,0x3eac3f4e,0x3e79bf80,0xbf3e3f5c,0x3f7dbedb,0xbedb3f7d,0x3f5cbf3e,0xbf803e79,0x3f4e3eac,0x3f71bf18,0xbf783d49,0x3f2c3f04,0xbe16bf67,
0xbedb3f7d,0x3f5cbf3e,0xbf803e79,0x3f4e3eac,0x3f71bf18,0xbf783d49,0x3f2c3f04,0xbe16bf67,0x3f673e16,0xbf04bf2c,0xbd493f78,0x3f18bf71,0xbeacbf4e,0xbe793f80,0x3f3ebf5c,0xbf7d3edb,
0xbef1bf46,0x3dc93f75,0x3e95bf7f,0xbf223f62,0x3f62bf22,0xbf7f3e95,0x3f753dc9,0xbf46bef1,0x3ef13f46,0xbdc9bf75,0xbe953f7f,0x3f22bf62,0xbf623f22,0x3f7fbe95,0xbf75bdc9,0x3f463ef1,
0xbf623f22,0x3f7fbe95,0xbf75bdc9,0x3f463ef1,0xbef1bf46,0x3dc93f75,0x3e95bf7f,0xbf223f62,0x3f62bf22,0xbf7f3e95,0x3f753dc9,0xbf46bef1,0x3ef13f46,0xbdc9bf75,0xbe953f7f,0x3f22bf62,
0xbf7dbd49,0x3f713e79,0xbf5cbedb,0x3f3e3f18,0xbf4e3f2c,0x3f67bf04,0xbf783eac,0x3f80be16,0xbe163f80,0x3eacbf78,0xbf043f67,0x3f2cbf4e,0x3f183f3e,0xbedbbf5c,0x3e793f71,0xbd49bf7d,
0xbe163f80,0x3eacbf78,0xbf043f67,0x3f2cbf4e,0x3f183f3e,0xbedbbf5c,0x3e793f71,0xbd49bf7d,0x3f7d3d49,0xbf71be79,0x3f5c3edb,0xbf3ebf18,0x3f4ebf2c,0xbf673f04,0x3f78beac,0xbf803e16,
0x3f35bf35,0xbf353f35,0x3f35bf35,0xbf353f35,0x3f35bf35,0xbf353f35,0x3f35bf35,0xbf353f35,0x3f35bf35,0xbf353f35,0x3f35bf35,0xbf353f35,0x3f35bf35,0xbf353f35,0x3f35bf35,0xbf353f35,
0x3f353f35,0xbf35bf35,0x3f353f35,0xbf35bf35,0x3f353f35,0xbf35bf35,0x3f353f35,0xbf35bf35,0x3f353f35,0xbf35bf35,0x3f353f35,0xbf35bf35,0x3f353f35,0xbf35bf35,0x3f353f35,0xbf35bf35,
0xbe16bf80,0x3eac3f78,0xbf04bf67,0x3f2c3f4e,0x3f18bf3e,0xbedb3f5c,0x3e79bf71,0xbd493f7d,0xbf7d3d49,0x3f71be79,0xbf5c3edb,0x3f3ebf18,0xbf4ebf2c,0x3f673f04,0xbf78beac,0x3f803e16,
0x3f7dbd49,0xbf713e79,0x3f5cbedb,0xbf3e3f18,0x3f4e3f2c,0xbf67bf04,0x3f783eac,0xbf80be16,0xbe16bf80,0x3eac3f78,0xbf04bf67,0x3f2c3f4e,0x3f18bf3e,0xbedb3f5c,0x3e79bf71,0xbd493f7d,
0xbef13f46,0x3dc9bf75,0x3e953f7f,0xbf22bf62,0x3f623f22,0xbf7fbe95,0x3f75bdc9,0xbf463ef1,0x3ef1bf46,0xbdc93f75,0xbe95bf7f,0x3f223f62,0xbf62bf22,0x3f7f3e95,0xbf753dc9,0x3f46bef1,
0xbf62bf22,0x3f7f3e95,0xbf753dc9,0x3f46bef1,0xbef13f46,0x3dc9bf75,0x3e953f7f,0xbf22bf62,0x3f623f22,0xbf7fbe95,0x3f75bdc9,0xbf463ef1,0x3ef1bf46,0xbdc93f75,0xbe95bf7f,0x3f223f62,
0xbedbbf7d,0x3f5c3f3e,0xbf80be79,0x3f4ebeac,0x3f713f18,0xbf78bd49,0x3f2cbf04,0xbe163f67,0xbf673e16,0x3f04bf2c,0x3d493f78,0xbf18bf71,0x3eacbf4e,0x3e793f80,0xbf3ebf5c,0x3f7d3edb,
0x3f67be16,0xbf043f2c,0xbd49bf78,0x3f183f71,0xbeac3f4e,0xbe79bf80,0x3f3e3f5c,0xbf7dbedb,0xbedbbf7d,0x3f5c3f3e,0xbf80be79,0x3f4ebeac,0x3f713f18,0xbf78bd49,0x3f2cbf04,0xbe163f67,
0x3f7b3f0e,0xbf553e48,0x3e48bf55,0x3f0e3f7b,0xbf7bbf0e,0x3f55be48,0xbe483f55,0xbf0ebf7b,0x3f7b3f0e,0xbf553e48,0x3e48bf55,0x3f0e3f7b,0xbf7bbf0e,0x3f55be48,0xbe483f55,0xbf0ebf7b,
0x3e48bf55,0x3f0e3f7b,0xbf7bbf0e,0x3f55be48,0xbe483f55,0xbf0ebf7b,0x3f7b3f0e,0xbf553e48,0x3e48bf55,0x3f0e3f7b,0xbf7bbf0e,0x3f55be48,0xbe483f55,0xbf0ebf7b,0x3f7b3f0e,0xbf553e48,
0xbf3e3e79,0xbe16bf71,0x3f673f4e,0xbf5c3d49,0x3f803f04,0xbf183edb,0xbeacbf7d,0x3f783f2c,0x3f2c3f78,0xbf7dbeac,0x3edbbf18,0x3f043f80,0x3d49bf5c,0x3f4e3f67,0xbf71be16,0x3e79bf3e,
0x3f2c3f78,0xbf7dbeac,0x3edbbf18,0x3f043f80,0x3d49bf5c,0x3f4e3f67,0xbf71be16,0x3e79bf3e,0x3f3ebe79,0x3e163f71,0xbf67bf4e,0x3f5cbd49,0xbf80bf04,0x3f18bedb,0x3eac3f7d,0xbf78bf2c,
0xbf7fbef1,0x3e95bf22,0x3f463f75,0xbf62bdc9,0xbdc9bf62,0x3f753f46,0xbf223e95,0xbef1bf7f,0x3f7f3ef1,0xbe953f22,0xbf46bf75,0x3f623dc9,0x3dc93f62,0xbf75bf46,0x3f22be95,0x3ef13f7f,
0x3dc93f62,0xbf75bf46,0x3f22be95,0x3ef13f7f,0xbf7fbef1,0x3e95bf22,0x3f463f75,0xbf62bdc9,0xbdc9bf62,0x3f753f46,0xbf223e95,0xbef1bf7f,0x3f7f3ef1,0xbe953f22,0xbf46bf75,0x3f623dc9,
0xbf043eac,0xbf3ebf7d,0x3f4e3d49,0x3edb3f78,0x3e793f67,0xbf80bf18,0x3e16bf2c,0x3f713f5c,0x3f5c3f71,0xbf2c3e16,0xbf18bf80,0x3f673e79,0x3f783edb,0x3d493f4e,0xbf7dbf3e,0x3eacbf04,
0x3f5c3f71,0xbf2c3e16,0xbf18bf80,0x3f673e79,0x3f783edb,0x3d493f4e,0xbf7dbf3e,0x3eacbf04,0x3f04beac,0x3f3e3f7d,0xbf4ebd49,0xbedbbf78,0xbe79bf67,0x3f803f18,0xbe163f2c,0xbf71bf5c,
0xbec4bf6d,0x3f6d3ec4,0x3ec43f6d,0xbf6dbec4,0xbec4bf6d,0x3f6d3ec4,0x3ec43f6d,0xbf6dbec4,0xbec4bf6d,0x3f6d3ec4,0x3ec43f6d,0xbf6dbec4,0xbec4bf6d,0x3f6d3ec4,0x3ec43f6d,0xbf6dbec4,
0x3f6d3ec4,0x3ec43f6d,0xbf6dbec4,0xbec4bf6d,0x3f6d3ec4,0x3ec43f6d,0xbf6dbec4,0xbec4bf6d,0x3f6d3ec4,0x3ec43f6d,0xbf6dbec4,0xbec4bf6d,0x3f6d3ec4,0x3ec43f6d,0xbf6dbec4,0xbec4bf6d,
0xbf78bf67,0x3d49bf18,0x3f7d3f2c,0x3eac3f5c,0xbf04bf71,0x3f3e3e16,0x3f4e3f80,0xbedb3e79,0xbe793edb,0xbf80bf4e,0xbe16bf3e,0x3f713f04,0xbf5cbeac,0xbf2cbf7d,0x3f18bd49,0x3f673f78,
0x3e79bedb,0x3f803f4e,0x3e163f3e,0xbf71bf04,0x3f5c3eac,0x3f2c3f7d,0xbf183d49,0xbf67bf78,0xbf78bf67,0x3d49bf18,0x3f7d3f2c,0x3eac3f5c,0xbf04bf71,0x3f3e3e16,0x3f4e3f80,0xbedb3e79,
0x3f223f75,0xbef13dc9,0xbf7fbf62,0xbe95bf46,0x3f463e95,0x3f623f7f,0xbdc93ef1,0xbf75bf22,0xbf22bf75,0x3ef1bdc9,0x3f7f3f62,0x3e953f46,0xbf46be95,0xbf62bf7f,0x3dc9bef1,0x3f753f22,
0xbf46be95,0xbf62bf7f,0x3dc9bef1,0x3f753f22,0x3f223f75,0xbef13dc9,0xbf7fbf62,0xbe95bf46,0x3f463e95,0x3f623f7f,0xbdc93ef1,0xbf75bf22,0xbf22bf75,0x3ef1bdc9,0x3f7f3f62,0x3e953f46,
0xbf80bf5c,0xbf18bf67,0x3eacbe16,0x3f783f3e,0x3f2c3e79,0x3f7d3f71,0x3edb3f4e,0xbf04bd49,0x3d493f04,0xbf4ebedb,0xbf71bf7d,0xbe79bf2c,0xbf3ebf78,0x3e16beac,0x3f673f18,0x3f5c3f80,
0xbd49bf04,0x3f4e3edb,0x3f713f7d,0x3e793f2c,0x3f3e3f78,0xbe163eac,0xbf67bf18,0xbf5cbf80,0xbf80bf5c,0xbf18bf67,0x3eacbe16,0x3f783f3e,0x3f2c3e79,0x3f7d3f71,0x3edb3f4e,0xbf04bd49,
0x3f0e3e48,0x3f7b3f55,0x3f553f7b,0x3e483f0e,0xbf0ebe48,0xbf7bbf55,0xbf55bf7b,0xbe48bf0e,0x3f0e3e48,0x3f7b3f55,0x3f553f7b,0x3e483f0e,0xbf0ebe48,0xbf7bbf55,0xbf55bf7b,0xbe48bf0e,
0xbf55bf7b,0xbe48bf0e,0x3f0e3e48,0x3f7b3f55,0x3f553f7b,0x3e483f0e,0xbf0ebe48,0xbf7bbf55,0xbf55bf7b,0xbe48bf0e,0x3f0e3e48,0x3f7b3f55,0x3f553f7b,0x3e483f0e,0xbf0ebe48,0xbf7bbf55,
0x3eac3f18,0xbe793d49,0xbf3ebf04,0xbf7dbf67,0x3edb3e16,0x3f5c3f2c,0x3f803f78,0x3f4e3f71,0x3f713f4e,0x3f783f80,0x3f2c3f5c,0x3e163edb,0xbf67bf7d,0xbf04bf3e,0x3d49be79,0x3f183eac,
0x3f713f4e,0x3f783f80,0x3f2c3f5c,0x3e163edb,0xbf67bf7d,0xbf04bf3e,0x3d49be79,0x3f183eac,0xbeacbf18,0x3e79bd49,0x3f3e3f04,0x3f7d3f67,0xbedbbe16,0xbf5cbf2c,0xbf80bf78,0xbf4ebf71,
0xbe95bdc9,0xbf22bef1,0xbf62bf46,0xbf7fbf75,0xbf75bf7f,0xbf46bf62,0xbef1bf22,0xbdc9be95,0x3e953dc9,0x3f223ef1,0x3f623f46,0x3f7f3f75,0x3f753f7f,0x3f463f62,0x3ef13f22,0x3dc93e95,
0x3f753f7f,0x3f463f62,0x3ef13f22,0x3dc93e95,0xbe95bdc9,0xbf22bef1,0xbf62bf46,0xbf7fbf75,0xbf75bf7f,0xbf46bf62,0xbef1bf22,0xbdc9be95,0x3e953dc9,0x3f223ef1,0x3f623f46,0x3f7f3f75,
0x3f183f2c,0x3edb3f04,0x3e793eac,0x3d493e16,0x3f7d3f80,0x3f713f78,0x3f5c3f67,0x3f3e3f4e,0x3f4e3f3e,0x3f673f5c,0x3f783f71,0x3f803f7d,0x3e163d49,0x3eac3e79,0x3f043edb,0x3f2c3f18,
0x3f4e3f3e,0x3f673f5c,0x3f783f71,0x3f803f7d,0x3e163d49,0x3eac3e79,0x3f043edb,0x3f2c3f18,0xbf18bf2c,0xbedbbf04,0xbe79beac,0xbd49be16,0xbf7dbf80,0xbf71bf78,0xbf5cbf67,0xbf3ebf4e,
0x38fb37c9,0x39a13960,0x39fc39cf,0x3a273a13,0xba7eba80,0xba73ba7a,0xba5fba6a,0xba42ba51,0x3a4a3a39,0x3a653a58,0x3a773a6f,0x3a7f3a7c,0xba1dba31,0xb9e6ba09,0xb989b9b8,0xb897b92f,
0x3a7e3a80,0x3a733a7a,0x3a5f3a6a,0x3a423a51,0x38fb37c9,0x39a13960,0x39fc39cf,0x3a273a13,0x3a1d3a31,0x39e63a09,0x398939b8,0x3897392f,0x3a4a3a39,0x3a653a58,0x3a773a6f,0x3a7f3a7c,
0xba6fba7f,0xba13ba4a,0xb7c9b9a1,0x3a093989,0x39b83897,0x3a513a1d,0x3a803a73,0x3a583a77,0x3a6a3a42,0x3a7c3a7e,0x3a393a65,0x396039fc,0x39cf3a27,0xb92f38fb,0xba31b9e6,0xba7aba5f,
0xb9b8b897,0xba51ba1d,0xba80ba73,0xba58ba77,0xba6fba7f,0xba13ba4a,0xb7c9b9a1,0x3a093989,0xb9cfba27,0x392fb8fb,0x3a3139e6,0x3a7a3a5f,0x3a6a3a42,0x3a7c3a7e,0x3a393a65,0x396039fc,
0xba7cba4a,0xba31ba73,0x3960b989,0x3a6f3a27,0x392f3a1d,0xba39b9a1,0xba7aba77,0xb9b8ba42,0x3a1338fb,0x3a803a65,0x3a093a5f,0xb9cf3897,0xba51ba7e,0x37c9b9e6,0x3a5839fc,0x3a6a3a7f,
0xb92fba1d,0x3a3939a1,0x3a7a3a77,0x39b83a42,0xba7cba4a,0xba31ba73,0x3960b989,0x3a6f3a27,0x3a513a7e,0xb7c939e6,0xba58b9fc,0xba6aba7f,0x3a1338fb,0x3a803a65,0x3a093a5f,0xb9cf3897,
0xba7fba51,0xb8fbba39,0x3a733a09,0x39fc3a6f,0x3897ba13,0x3a7e3a31,0x39a13a58,0xba5fb9b8,0xba27ba7c,0x3a1db7c9,0x3a653a7a,0xb98939cf,0x3a42392f,0x3a4a3a80,0xb9e63960,0xba77ba6a,
0xb8973a13,0xba7eba31,0xb9a1ba58,0x3a5f39b8,0xba7fba51,0xb8fbba39,0x3a733a09,0x39fc3a6f,0xba42b92f,0xba4aba80,0x39e6b960,0x3a773a6a,0xba27ba7c,0x3a1db7c9,0x3a653a7a,0xb98939cf,
0x39e63a7a,0xba77b9cf,0xb897ba51,0x3a7e3a39,0x3a653960,0x39893a6a,0xba7fba13,0x38fbba31,0xb9a13a09,0xba5fba6f,0x3a27b92f,0x3a1d3a80,0x3a733a58,0xb9fc39b8,0xba42ba7c,0x3a4a37c9,
0x3a653960,0x39893a6a,0xba7fba13,0x38fbba31,0xb9e6ba7a,0x3a7739cf,0x38973a51,0xba7eba39,0x3a733a58,0xb9fc39b8,0xba42ba7c,0x3a4a37c9,0x39a1ba09,0x3a5f3a6f,0xba27392f,0xba1dba80,
0xba7ab989,0x39b8ba27,0x3a133a7e,0xba80b9e6,0xb960ba77,0x3a6f3a42,0xba5138fb,0xb7c9ba65,0x3a09b9fc,0x39cf3a7f,0xba7cba1d,0x3a31b9a1,0x3a583a5f,0xba6ab897,0x392fba4a,0x3a393a73,
0xb960ba77,0x3a6f3a42,0xba5138fb,0xb7c9ba65,0x3a7a3989,0xb9b83a27,0xba13ba7e,0x3a8039e6,0x3a583a5f,0xba6ab897,0x392fba4a,0x3a393a73,0xba0939fc,0xb9cfba7f,0x3a7c3a1d,0xba3139a1,
0x3a39b9e6,0xb9603a5f,0xb9b8ba7f,0x3a513a4a,0xba31ba65,0x3a7a39fc,0xba6f3897,0x3a13ba1d,0xb7c93a73,0xba09ba77,0x3a6a3a27,0xba7cb8fb,0x3a8039a1,0xba583989,0x39cfba42,0x392f3a7e,
0xba31ba65,0x3a7a39fc,0xba6f3897,0x3a13ba1d,0xba3939e6,0x3960ba5f,0x39b83a7f,0xba51ba4a,0x3a8039a1,0xba583989,0x39cfba42,0x392f3a7e,0x37c9ba73,0x3a093a77,0xba6aba27,0x3a7c38fb,
0xba5f39cf,0x3a42ba13,0xba1d3a39,0x39e6ba58,0xb9fcba6a,0x3a273a51,0xba4aba31,0x3a653a09,0xba77b9b8,0x3a7f392f,0xba7e37c9,0x3a73b960,0x3989ba6f,0xb8973a7c,0xb8fbba80,0x39a13a7a,
0xb9fcba6a,0x3a273a51,0xba4aba31,0x3a653a09,0x3a5fb9cf,0xba423a13,0x3a1dba39,0xb9e63a58,0x3989ba6f,0xb8973a7c,0xb8fbba80,0x39a13a7a,0x3a7739b8,0xba7fb92f,0x3a7eb7c9,0xba733960,
0x3a5f39cf,0xba42ba13,0x3a1d3a39,0xb9e6ba58,0x39fcba6a,0xba273a51,0x3a4aba31,0xba653a09,0x39893a6f,0xb897ba7c,0xb8fb3a80,0x39a1ba7a,0x3a77b9b8,0xba7f392f,0x3a7e37c9,0xba73b960,
0xb9fc3a6a,0x3a27ba51,0xba4a3a31,0x3a65ba09,0x3a5f39cf,0xba42ba13,0x3a1d3a39,0xb9e6ba58,0xba7739b8,0x3a7fb92f,0xba7eb7c9,0x3a733960,0x39893a6f,0xb897ba7c,0xb8fb3a80,0x39a1ba7a,
0x3a31ba65,0xba7a39fc,0x3a6f3897,0xba13ba1d,0x3a3939e6,0xb960ba5f,0xb9b83a7f,0x3a51ba4a,0x37c93a73,0x3a09ba77,0xba6a3a27,0x3a7cb8fb,0xba8039a1,0x3a583989,0xb9cfba42,0xb92f3a7e,
0xba39b9e6,0x39603a5f,0x39b8ba7f,0xba513a4a,0x3a31ba65,0xba7a39fc,0x3a6f3897,0xba13ba1d,0x3a80b9a1,0xba58b989,0x39cf3a42,0x392fba7e,0x37c93a73,0x3a09ba77,0xba6a3a27,0x3a7cb8fb,
0x3960ba77,0xba6f3a42,0x3a5138fb,0x37c9ba65,0xba7a3989,0x39b83a27,0x3a13ba7e,0xba8039e6,0x3a0939fc,0x39cfba7f,0xba7c3a1d,0x3a3139a1,0x3a58ba5f,0xba6a3897,0x392f3a4a,0x3a39ba73,
0x3a7ab989,0xb9b8ba27,0xba133a7e,0x3a80b9e6,0x3960ba77,0xba6f3a42,0x3a5138fb,0x37c9ba65,0xba583a5f,0x3a6ab897,0xb92fba4a,0xba393a73,0x3a0939fc,0x39cfba7f,0xba7c3a1d,0x3a3139a1,
0x39e6ba7a,0xba7739cf,0xb8973a51,0x3a7eba39,0x3a65b960,0x3989ba6a,0xba7f3a13,0x38fb3a31,0x3a73ba58,0xb9fcb9b8,0xba423a7c,0x3a4ab7c9,0x39a13a09,0x3a5fba6f,0xba27b92f,0xba1d3a80,
0xba653960,0xb9893a6a,0x3a7fba13,0xb8fbba31,0x39e6ba7a,0xba7739cf,0xb8973a51,0x3a7eba39,0xb9a1ba09,0xba5f3a6f,0x3a27392f,0x3a1dba80,0x3a73ba58,0xb9fcb9b8,0xba423a7c,0x3a4ab7c9,
0xba7f3a51,0xb8fb3a39,0x3a73ba09,0x39fcba6f,0x38973a13,0x3a7eba31,0x39a1ba58,0xba5f39b8,0xba42392f,0xba4a3a80,0x39e63960,0x3a77ba6a,0xba273a7c,0x3a1d37c9,0x3a65ba7a,0xb989b9cf,
0x38973a13,0x3a7eba31,0x39a1ba58,0xba5f39b8,0x3a7fba51,0x38fbba39,0xba733a09,0xb9fc3a6f,0xba273a7c,0x3a1d37c9,0x3a65ba7a,0xb989b9cf,0x3a42b92f,0x3a4aba80,0xb9e6b960,0xba773a6a,
0x392fba1d,0xba3939a1,0xba7a3a77,0xb9b83a42,0x3a7cba4a,0x3a31ba73,0xb960b989,0xba6f3a27,0x3a13b8fb,0x3a80ba65,0x3a09ba5f,0xb9cfb897,0xba513a7e,0x37c939e6,0x3a58b9fc,0x3a6aba7f,
0x3a7cba4a,0x3a31ba73,0xb960b989,0xba6f3a27,0xb92f3a1d,0x3a39b9a1,0x3a7aba77,0x39b8ba42,0xba513a7e,0x37c939e6,0x3a58b9fc,0x3a6aba7f,0xba1338fb,0xba803a65,0xba093a5f,0x39cf3897,
0x39b8b897,0x3a51ba1d,0x3a80ba73,0x3a58ba77,0x3a6fba7f,0x3a13ba4a,0x37c9b9a1,0xba093989,0xba6a3a42,0xba7c3a7e,0xba393a65,0xb96039fc,0xb9cf3a27,0x392f38fb,0x3a31b9e6,0x3a7aba5f,
0x3a6fba7f,0x3a13ba4a,0x37c9b9a1,0xba093989,0xb9b83897,0xba513a1d,0xba803a73,0xba583a77,0xb9cf3a27,0x392f38fb,0x3a31b9e6,0x3a7aba5f,0x3a6aba42,0x3a7cba7e,0x3a39ba65,0x3960b9fc,
0xb8fb37c9,0xb9a13960,0xb9fc39cf,0xba273a13,0x3a7eba80,0x3a73ba7a,0x3a5fba6a,0x3a42ba51,0x3a1dba31,0x39e6ba09,0x3989b9b8,0x3897b92f,0x3a4aba39,0x3a65ba58,0x3a77ba6f,0x3a7fba7c,
0x3a7eba80,0x3a73ba7a,0x3a5fba6a,0x3a42ba51,0x38fbb7c9,0x39a1b960,0x39fcb9cf,0x3a27ba13,0x3a4aba39,0x3a65ba58,0x3a77ba6f,0x3a7fba7c,0xba1d3a31,0xb9e63a09,0xb98939b8,0xb897392f,
0xba4a3a39,0xba653a58,0xba773a6f,0xba7f3a7c,0x3a1dba31,0x39e6ba09,0x3989b9b8,0x3897b92f,0xba7e3a80,0xba733a7a,0xba5f3a6a,0xba423a51,0xb8fb37c9,0xb9a13960,0xb9fc39cf,0xba273a13,
0xba1d3a31,0xb9e63a09,0xb98939b8,0xb897392f,0xba4a3a39,0xba653a58,0xba773a6f,0xba7f3a7c,0x38fbb7c9,0x39a1b960,0x39fcb9cf,0x3a27ba13,0xba7e3a80,0xba733a7a,0xba5f3a6a,0xba423a51,
0x39cfba27,0xb92fb8fb,0xba3139e6,0xba7a3a5f,0xba6a3a42,0xba7c3a7e,0xba393a65,0xb96039fc,0xba6f3a7f,0xba133a4a,0xb7c939a1,0x3a09b989,0x39b8b897,0x3a51ba1d,0x3a80ba73,0x3a58ba77,
0x3a6aba42,0x3a7cba7e,0x3a39ba65,0x3960b9fc,0x39cfba27,0xb92fb8fb,0xba3139e6,0xba7a3a5f,0xb9b83897,0xba513a1d,0xba803a73,0xba583a77,0xba6f3a7f,0xba133a4a,0xb7c939a1,0x3a09b989,
0x3a51ba7e,0xb7c9b9e6,0xba5839fc,0xba6a3a7f,0x3a13b8fb,0x3a80ba65,0x3a09ba5f,0xb9cfb897,0xba7c3a4a,0xba313a73,0x39603989,0x3a6fba27,0x392fba1d,0xba3939a1,0xba7a3a77,0xb9b83a42,
0xba1338fb,0xba803a65,0xba093a5f,0x39cf3897,0x3a51ba7e,0xb7c9b9e6,0xba5839fc,0xba6a3a7f,0xb92f3a1d,0x3a39b9a1,0x3a7aba77,0x39b8ba42,0xba7c3a4a,0xba313a73,0x39603989,0x3a6fba27,
0x3a27ba7c,0xba1db7c9,0xba653a7a,0x398939cf,0xba42392f,0xba4a3a80,0x39e63960,0x3a77ba6a,0xb897ba13,0xba7e3a31,0xb9a13a58,0x3a5fb9b8,0xba7f3a51,0xb8fb3a39,0x3a73ba09,0x39fcba6f,
0x3a42b92f,0x3a4aba80,0xb9e6b960,0xba773a6a,0x3a27ba7c,0xba1db7c9,0xba653a7a,0x398939cf,0x3a7fba51,0x38fbba39,0xba733a09,0xb9fc3a6f,0xb897ba13,0xba7e3a31,0xb9a13a58,0x3a5fb9b8,
0x39a13a09,0x3a5fba6f,0xba27b92f,0xba1d3a80,0xba733a58,0x39fc39b8,0x3a42ba7c,0xba4a37c9,0x3a65b960,0x3989ba6a,0xba7f3a13,0x38fb3a31,0xb9e63a7a,0x3a77b9cf,0x3897ba51,0xba7e3a39,
0xba733a58,0x39fc39b8,0x3a42ba7c,0xba4a37c9,0xb9a1ba09,0xba5f3a6f,0x3a27392f,0x3a1dba80,0xb9e63a7a,0x3a77b9cf,0x3897ba51,0xba7e3a39,0xba653960,0xb9893a6a,0x3a7fba13,0xb8fbba31,
0x3a58ba5f,0xba6a3897,0x392f3a4a,0x3a39ba73,0xba09b9fc,0xb9cf3a7f,0x3a7cba1d,0xba31b9a1,0xba7a3989,0x39b83a27,0x3a13ba7e,0xba8039e6,0xb9603a77,0x3a6fba42,0xba51b8fb,0xb7c93a65,
0xba09b9fc,0xb9cf3a7f,0x3a7cba1d,0xba31b9a1,0xba583a5f,0x3a6ab897,0xb92fba4a,0xba393a73,0xb9603a77,0x3a6fba42,0xba51b8fb,0xb7c93a65,0x3a7ab989,0xb9b8ba27,0xba133a7e,0x3a80b9e6,
0xba8039a1,0x3a583989,0xb9cfba42,0xb92f3a7e,0xb7c9ba73,0xba093a77,0x3a6aba27,0xba7c38fb,0x3a3939e6,0xb960ba5f,0xb9b83a7f,0x3a51ba4a,0xba313a65,0x3a7ab9fc,0xba6fb897,0x3a133a1d,
0xb7c9ba73,0xba093a77,0x3a6aba27,0xba7c38fb,0x3a80b9a1,0xba58b989,0x39cf3a42,0x392fba7e,0xba313a65,0x3a7ab9fc,0xba6fb897,0x3a133a1d,0xba39b9e6,0x39603a5f,0x39b8ba7f,0xba513a4a,
0x3a77b9b8,0xba7f392f,0x3a7e37c9,0xba73b960,0xb989ba6f,0x38973a7c,0x38fbba80,0xb9a13a7a,0x39fcba6a,0xba273a51,0x3a4aba31,0xba653a09,0xba5fb9cf,0x3a423a13,0xba1dba39,0x39e63a58,
0xb989ba6f,0x38973a7c,0x38fbba80,0xb9a13a7a,0xba7739b8,0x3a7fb92f,0xba7eb7c9,0x3a733960,0xba5fb9cf,0x3a423a13,0xba1dba39,0x39e63a58,0xb9fc3a6a,0x3a27ba51,0xba4a3a31,0x3a65ba09,
0xb9893a6f,0x3897ba7c,0x38fb3a80,0xb9a1ba7a,0xba77b9b8,0x3a7f392f,0xba7e37c9,0x3a73b960,0x39fc3a6a,0xba27ba51,0x3a4a3a31,0xba65ba09,0xba5f39cf,0x3a42ba13,0xba1d3a39,0x39e6ba58,
0x3a7739b8,0xba7fb92f,0x3a7eb7c9,0xba733960,0xb9893a6f,0x3897ba7c,0x38fb3a80,0xb9a1ba7a,0x3a5fb9cf,0xba423a13,0x3a1dba39,0xb9e63a58,0x39fc3a6a,0xba27ba51,0x3a4a3a31,0xba65ba09,
0xba80b9a1,0x3a58b989,0xb9cf3a42,0xb92fba7e,0xb7c93a73,0xba09ba77,0x3a6a3a27,0xba7cb8fb,0x3a313a65,0xba7ab9fc,0x3a6fb897,0xba133a1d,0x3a39b9e6,0xb9603a5f,0xb9b8ba7f,0x3a513a4a,
0x37c9ba73,0x3a093a77,0xba6aba27,0x3a7c38fb,0xba80b9a1,0x3a58b989,0xb9cf3a42,0xb92fba7e,0xba3939e6,0x3960ba5f,0x39b83a7f,0xba51ba4a,0x3a313a65,0xba7ab9fc,0x3a6fb897,0xba133a1d,
0xba58ba5f,0x3a6a3897,0xb92f3a4a,0xba39ba73,0x3a09b9fc,0x39cf3a7f,0xba7cba1d,0x3a31b9a1,0x39603a77,0xba6fba42,0x3a51b8fb,0x37c93a65,0xba7ab989,0x39b8ba27,0x3a133a7e,0xba80b9e6,
0xba0939fc,0xb9cfba7f,0x3a7c3a1d,0xba3139a1,0xba58ba5f,0x3a6a3897,0xb92f3a4a,0xba39ba73,0x3a7a3989,0xb9b83a27,0xba13ba7e,0x3a8039e6,0x39603a77,0xba6fba42,0x3a51b8fb,0x37c93a65,
0xba73ba58,0x39fcb9b8,0x3a423a7c,0xba4ab7c9,0xb9a13a09,0xba5fba6f,0x3a27b92f,0x3a1d3a80,0xba65b960,0xb989ba6a,0x3a7f3a13,0xb8fb3a31,0x39e63a7a,0xba77b9cf,0xb897ba51,0x3a7e3a39,
0x39a1ba09,0x3a5f3a6f,0xba27392f,0xba1dba80,0xba73ba58,0x39fcb9b8,0x3a423a7c,0xba4ab7c9,0xb9e6ba7a,0x3a7739cf,0x38973a51,0xba7eba39,0xba65b960,0xb989ba6a,0x3a7f3a13,0xb8fb3a31,
0x3a42392f,0x3a4a3a80,0xb9e63960,0xba77ba6a,0x3a273a7c,0xba1d37c9,0xba65ba7a,0x3989b9cf,0x3897ba13,0x3a7e3a31,0x39a13a58,0xba5fb9b8,0x3a7f3a51,0x38fb3a39,0xba73ba09,0xb9fcba6f,
0x3a273a7c,0xba1d37c9,0xba65ba7a,0x3989b9cf,0xba42b92f,0xba4aba80,0x39e6b960,0x3a773a6a,0x3a7f3a51,0x38fb3a39,0xba73ba09,0xb9fcba6f,0xb8973a13,0xba7eba31,0xb9a1ba58,0x3a5f39b8,
0xba51ba7e,0x37c9b9e6,0x3a5839fc,0x3a6a3a7f,0xba13b8fb,0xba80ba65,0xba09ba5f,0x39cfb897,0x392f3a1d,0xba39b9a1,0xba7aba77,0xb9b8ba42,0x3a7c3a4a,0x3a313a73,0xb9603989,0xba6fba27,
0xba13b8fb,0xba80ba65,0xba09ba5f,0x39cfb897,0x3a513a7e,0xb7c939e6,0xba58b9fc,0xba6aba7f,0x3a7c3a4a,0x3a313a73,0xb9603989,0xba6fba27,0xb92fba1d,0x3a3939a1,0x3a7a3a77,0x39b83a42,
0x39cf3a27,0xb92f38fb,0xba31b9e6,0xba7aba5f,0xba6aba42,0xba7cba7e,0xba39ba65,0xb960b9fc,0x39b83897,0x3a513a1d,0x3a803a73,0x3a583a77,0x3a6f3a7f,0x3a133a4a,0x37c939a1,0xba09b989,
0xba6aba42,0xba7cba7e,0xba39ba65,0xb960b9fc,0xb9cfba27,0x392fb8fb,0x3a3139e6,0x3a7a3a5f,0x3a6f3a7f,0x3a133a4a,0x37c939a1,0xba09b989,0xb9b8b897,0xba51ba1d,0xba80ba73,0xba58ba77,
0xba1dba31,0xb9e6ba09,0xb989b9b8,0xb897b92f,0xba4aba39,0xba65ba58,0xba77ba6f,0xba7fba7c,0xba7eba80,0xba73ba7a,0xba5fba6a,0xba42ba51,0xb8fbb7c9,0xb9a1b960,0xb9fcb9cf,0xba27ba13,
0xba4aba39,0xba65ba58,0xba77ba6f,0xba7fba7c,0x3a1d3a31,0x39e63a09,0x398939b8,0x3897392f,0xb8fbb7c9,0xb9a1b960,0xb9fcb9cf,0xba27ba13,0x3a7e3a80,0x3a733a7a,0x3a5f3a6a,0x3a423a51,
0x3d973cc9,0xbf7fbf80,0x3ee63ecf,0xbf65bf6a,0x3e2f3dfb,0xbf7cbf7e,0x3f093efc,0xbf58bf5f,0x3e893e60,0xbf77bf7a,0x3f1d3f13,0xbf4abf51,0x3eb83ea1,0xbf6fbf73,0x3f313f27,0xbf39bf42,
0x3eb83dfb,0xbf6fbf7e,0x3f393f5f,0x3f313efc,0x3f423f13,0xbf27bf51,0x3ea13f09,0x3f733f58,0x3f7a3f65,0xbe60bee6,0xbe2f3d97,0x3f7c3f7f,0x3f773f80,0x3e893cc9,0xbf1dbecf,0x3f4a3f6a,
0x3f1d3e60,0xbf4abf7a,0xbf5fbf13,0x3efc3f51,0x3f803f65,0xbcc9bee6,0xbf6fbf7f,0xbeb83d97,0x3f273f6a,0x3f423ecf,0xbea1bf31,0xbf73bf39,0xbe2f3e89,0x3f7c3f77,0x3f093dfb,0xbf58bf7e,
0x3f513ea1,0xbf13bf73,0xbe60bf42,0xbf7abf27,0x3f4a3f80,0x3f1d3cc9,0x3f5f3ecf,0xbefcbf6a,0xbeb83e89,0x3f6f3f77,0x3f393f7e,0x3f313dfb,0xbf7fbf58,0xbd973f09,0xbee63e2f,0x3f653f7c,
0x3f733ecf,0xbea1bf6a,0x3f7f3f39,0x3d97bf31,0x3e603f5f,0x3f7a3efc,0xbe2f3f1d,0x3f7c3f4a,0xbf7ebf13,0x3dfb3f51,0xbf77bf58,0xbe893f09,0xbcc9bf42,0xbf80bf27,0x3eb8bee6,0xbf6fbf65,
0x3f803efc,0xbcc9bf5f,0xbeb83f1d,0x3f6f3f4a,0xbee63f09,0x3f653f58,0xbf27bf7c,0xbf423e2f,0xbf13bf7f,0xbf513d97,0x3f7a3ea1,0xbe60bf73,0x3f7e3ecf,0xbdfbbf6a,0xbe893f31,0x3f773f39,
0x3f773f13,0x3e89bf51,0xbf4abf58,0xbf1d3f09,0xbf6a3d97,0x3ecf3f7f,0x3f803ea1,0xbcc9bf73,0x3ee6bf31,0xbf65bf39,0xbf423eb8,0x3f273f6f,0x3e603f7e,0x3f7a3dfb,0x3e2fbf5f,0xbf7cbefc,
0x3f583f27,0x3f09bf42,0x3f51bee6,0xbf13bf65,0xbf77becf,0xbe893f6a,0xbf1d3f31,0x3f4a3f39,0x3f803dfb,0xbcc9bf7e,0x3eb8bf5f,0xbf6fbefc,0xbf733e2f,0x3ea13f7c,0xbd973f7a,0x3f7f3e60,
0x3f273f39,0x3f42bf31,0x3ea13f6f,0x3f73beb8,0xbf13bf4a,0xbf513f1d,0xbe60bf77,0xbf7a3e89,0x3efc3f58,0x3f5fbf09,0x3dfb3f7c,0x3f7ebe2f,0xbecfbf65,0xbf6a3ee6,0xbcc9bf7f,0xbf803d97,
0x3ecf3f4a,0x3f6abf1d,0xbf803e89,0x3cc93f77,0x3d97bf7c,0xbf7f3e2f,0x3f653e60,0x3ee6bf7a,0xbf093f73,0x3f583ea1,0xbf13bf27,0xbf513f42,0x3f5fbf31,0xbefcbf39,0x3dfb3f6f,0x3f7ebeb8,
0x3dfb3f58,0x3f7ebf09,0x3e89bf7c,0xbf773e2f,0x3f31bf73,0xbf39bea1,0xbf6a3f42,0x3ecf3f27,0xbf7f3eb8,0xbd973f6f,0x3f653cc9,0x3ee6bf80,0x3f133efc,0x3f51bf5f,0xbe60bf4a,0xbf7a3f1d,
0xbe2f3f65,0x3f7cbee6,0x3f58bd97,0x3f09bf7f,0x3f7ebf31,0xbdfbbf39,0x3e89bf6f,0xbf773eb8,0xbecfbefc,0xbf6a3f5f,0xbf803f1d,0x3cc93f4a,0xbf423f7a,0x3f273e60,0x3ea13f13,0x3f73bf51,
0xbee63f6f,0x3f65beb8,0xbf423f80,0x3f273cc9,0x3f58be89,0x3f09bf77,0x3f133dfb,0x3f51bf7e,0x3f1dbf7c,0xbf4a3e2f,0x3f5fbf7a,0xbefcbe60,0xbf393d97,0xbf313f7f,0xbecfbea1,0xbf6a3f73,
0xbf313f77,0x3f39be89,0xbecfbdfb,0xbf6a3f7e,0x3ea13e60,0x3f73bf7a,0xbf7f3f51,0xbd973f13,0x3f7cbf42,0x3e2fbf27,0xbf093f65,0x3f58bee6,0x3f1dbf6f,0xbf4a3eb8,0x3efc3cc9,0x3f5fbf80,
0xbf5f3f7c,0x3efcbe2f,0x3f7ebf7a,0xbdfbbe60,0xbeb83f27,0x3f6fbf42,0x3f31bf65,0xbf393ee6,0x3ea13cc9,0x3f73bf80,0x3d97becf,0xbf7f3f6a,0x3f58bf1d,0x3f09bf4a,0xbf133e89,0xbf513f77,
0xbf7a3f7f,0x3e60bd97,0xbe2f3ea1,0x3f7cbf73,0xbf5f3f6f,0x3efcbeb8,0x3dfb3cc9,0x3f7ebf80,0xbf313f4a,0x3f39bf1d,0x3ecfbe89,0x3f6abf77,0xbee63f13,0x3f65bf51,0x3f27bf09,0x3f42bf58,
0xbf7f3f80,0xbd973cc9,0xbf653f6a,0xbee63ecf,0xbf7c3f7e,0xbe2f3dfb,0xbf583f5f,0xbf093efc,0xbf773f7a,0xbe893e60,0xbf4a3f51,0xbf1d3f13,0xbf6f3f73,0xbeb83ea1,0xbf393f42,0xbf313f27,
0xbf6f3f7e,0xbeb83dfb,0x3f31befc,0xbf393f5f,0xbf273f51,0xbf423f13,0x3f73bf58,0xbea13f09,0xbe603ee6,0xbf7a3f65,0x3f7cbf7f,0x3e2f3d97,0x3e89bcc9,0xbf773f80,0x3f4abf6a,0x3f1dbecf,
0xbf4a3f7a,0xbf1d3e60,0x3efcbf51,0x3f5fbf13,0xbcc93ee6,0xbf803f65,0xbeb8bd97,0x3f6fbf7f,0x3f42becf,0xbf273f6a,0xbf733f39,0x3ea1bf31,0x3f7cbf77,0x3e2f3e89,0xbf583f7e,0xbf093dfb,
0xbf133f73,0xbf513ea1,0xbf7a3f27,0x3e60bf42,0x3f1dbcc9,0xbf4a3f80,0xbefc3f6a,0xbf5f3ecf,0x3f6fbf77,0x3eb83e89,0x3f31bdfb,0xbf393f7e,0xbd97bf09,0x3f7fbf58,0x3f65bf7c,0x3ee63e2f,
0xbea13f6a,0xbf733ecf,0x3d973f31,0xbf7f3f39,0x3f7abefc,0xbe603f5f,0x3f7cbf4a,0x3e2f3f1d,0x3dfbbf51,0x3f7ebf13,0xbe89bf09,0x3f77bf58,0xbf803f27,0x3cc9bf42,0xbf6f3f65,0xbeb8bee6,
0xbcc93f5f,0xbf803efc,0x3f6fbf4a,0x3eb83f1d,0x3f65bf58,0x3ee63f09,0xbf42be2f,0x3f27bf7c,0xbf51bd97,0x3f13bf7f,0xbe603f73,0xbf7a3ea1,0xbdfb3f6a,0xbf7e3ecf,0x3f77bf39,0x3e893f31,
0x3e893f51,0xbf773f13,0xbf1dbf09,0x3f4abf58,0x3ecfbf7f,0x3f6a3d97,0xbcc93f73,0xbf803ea1,0xbf653f39,0xbee6bf31,0x3f27bf6f,0x3f423eb8,0x3f7abdfb,0xbe603f7e,0xbf7c3efc,0xbe2fbf5f,
0x3f093f42,0xbf583f27,0xbf133f65,0xbf51bee6,0xbe89bf6a,0x3f77becf,0x3f4abf39,0x3f1d3f31,0xbcc93f7e,0xbf803dfb,0xbf6f3efc,0xbeb8bf5f,0x3ea1bf7c,0x3f733e2f,0x3f7fbe60,0x3d973f7a,
0x3f423f31,0xbf273f39,0x3f733eb8,0xbea13f6f,0xbf51bf1d,0x3f13bf4a,0xbf7abe89,0x3e60bf77,0x3f5f3f09,0xbefc3f58,0x3f7e3e2f,0xbdfb3f7c,0xbf6abee6,0x3ecfbf65,0xbf80bd97,0x3cc9bf7f,
0x3f6a3f1d,0xbecf3f4a,0x3cc9bf77,0x3f803e89,0xbf7fbe2f,0xbd97bf7c,0x3ee63f7a,0xbf653e60,0x3f58bea1,0x3f093f73,0xbf51bf42,0x3f13bf27,0xbefc3f39,0xbf5fbf31,0x3f7e3eb8,0xbdfb3f6f,
0x3f7e3f09,0xbdfb3f58,0xbf77be2f,0xbe89bf7c,0xbf393ea1,0xbf31bf73,0x3ecfbf27,0x3f6a3f42,0xbd97bf6f,0x3f7f3eb8,0x3ee63f80,0xbf653cc9,0x3f513f5f,0xbf133efc,0xbf7abf1d,0x3e60bf4a,
0x3f7c3ee6,0x3e2f3f65,0x3f093f7f,0xbf58bd97,0xbdfb3f39,0xbf7ebf31,0xbf77beb8,0xbe89bf6f,0xbf6abf5f,0x3ecfbefc,0x3cc9bf4a,0x3f803f1d,0x3f27be60,0x3f423f7a,0x3f733f51,0xbea13f13,
0x3f653eb8,0x3ee63f6f,0x3f27bcc9,0x3f423f80,0x3f093f77,0xbf58be89,0x3f513f7e,0xbf133dfb,0xbf4abe2f,0xbf1dbf7c,0xbefc3e60,0xbf5fbf7a,0xbf31bf7f,0x3f393d97,0xbf6abf73,0x3ecfbea1,
0x3f393e89,0x3f313f77,0xbf6abf7e,0x3ecfbdfb,0x3f733f7a,0xbea13e60,0xbd97bf13,0x3f7f3f51,0x3e2f3f27,0xbf7cbf42,0x3f583ee6,0x3f093f65,0xbf4abeb8,0xbf1dbf6f,0x3f5f3f80,0xbefc3cc9,
0x3efc3e2f,0x3f5f3f7c,0xbdfb3e60,0xbf7ebf7a,0x3f6f3f42,0x3eb83f27,0xbf39bee6,0xbf31bf65,0x3f733f80,0xbea13cc9,0xbf7fbf6a,0xbd97becf,0x3f093f4a,0xbf58bf1d,0xbf51bf77,0x3f133e89,
0x3e603d97,0x3f7a3f7f,0x3f7c3f73,0x3e2f3ea1,0x3efc3eb8,0x3f5f3f6f,0x3f7e3f80,0xbdfb3cc9,0x3f393f1d,0x3f313f4a,0x3f6a3f77,0xbecfbe89,0x3f653f51,0x3ee63f13,0x3f423f58,0xbf27bf09,
0x3f423f39,0xbf27bf31,0x3f733f6f,0xbea1beb8,0x3f513f4a,0xbf13bf1d,0x3f7a3f77,0xbe60be89,0x3f5f3f58,0xbefcbf09,0x3f7e3f7c,0xbdfbbe2f,0x3f6a3f65,0xbecfbee6,0x3f803f7f,0xbcc9bd97,
0xbf6abf4a,0x3ecf3f1d,0xbcc9be89,0xbf80bf77,0xbf7fbf7c,0xbd973e2f,0x3ee63e60,0xbf65bf7a,0xbf58bf73,0xbf09bea1,0x3f513f27,0xbf13bf42,0xbefcbf31,0xbf5fbf39,0x3f7e3f6f,0xbdfbbeb8,
0x3f7e3f58,0xbdfbbf09,0xbf77bf7c,0xbe893e2f,0x3f393f73,0x3f313ea1,0xbecfbf42,0xbf6abf27,0xbd973eb8,0x3f7f3f6f,0x3ee63cc9,0xbf65bf80,0xbf51befc,0x3f133f5f,0x3f7a3f4a,0xbe60bf1d,
0xbf7cbf65,0xbe2f3ee6,0xbf093d97,0x3f583f7f,0xbdfbbf31,0xbf7ebf39,0xbf77bf6f,0xbe893eb8,0x3f6a3efc,0xbecfbf5f,0xbcc9bf1d,0xbf80bf4a,0x3f273f7a,0x3f423e60,0x3f733f13,0xbea1bf51,
0x3f653f6f,0x3ee6beb8,0x3f273f80,0x3f423cc9,0xbf093e89,0x3f583f77,0xbf51bdfb,0x3f133f7e,0xbf4abf7c,0xbf1d3e2f,0xbefcbf7a,0xbf5fbe60,0x3f31bd97,0xbf39bf7f,0x3f6a3ea1,0xbecfbf73,
0xbf39bf77,0xbf313e89,0x3f6a3dfb,0xbecfbf7e,0x3f733e60,0xbea1bf7a,0xbd973f51,0x3f7f3f13,0xbe2f3f42,0x3f7c3f27,0xbf58bf65,0xbf093ee6,0xbf4abf6f,0xbf1d3eb8,0x3f5f3cc9,0xbefcbf80,
0x3efc3f7c,0x3f5fbe2f,0xbdfbbf7a,0xbf7ebe60,0xbf6fbf27,0xbeb83f42,0x3f393f65,0x3f31bee6,0x3f733cc9,0xbea1bf80,0xbf7fbecf,0xbd973f6a,0xbf093f1d,0x3f583f4a,0x3f51be89,0xbf13bf77,
0xbe60bf7f,0xbf7a3d97,0xbf7cbea1,0xbe2f3f73,0x3efc3f6f,0x3f5fbeb8,0x3f7e3cc9,0xbdfbbf80,0xbf39bf4a,0xbf313f1d,0xbf6a3e89,0x3ecf3f77,0x3f653f13,0x3ee6bf51,0x3f42bf09,0xbf27bf58,
0xbd973f80,0x3f7f3cc9,0xbee63f6a,0x3f653ecf,0x3e2fbf7e,0xbf7cbdfb,0x3f09bf5f,0xbf58befc,0xbe893f7a,0x3f773e60,0xbf1d3f51,0x3f4a3f13,0x3eb8bf73,0xbf6fbea1,0x3f31bf42,0xbf39bf27,
0x3eb8bf7e,0xbf6fbdfb,0x3f393efc,0x3f31bf5f,0xbf423f51,0x3f273f13,0xbea1bf58,0xbf733f09,0x3f7abee6,0xbe60bf65,0xbe2f3f7f,0x3f7cbd97,0xbf77bcc9,0xbe893f80,0x3f1dbf6a,0xbf4abecf,
0xbf1d3f7a,0x3f4a3e60,0x3f5fbf51,0xbefcbf13,0x3f80bee6,0xbcc9bf65,0xbf6f3d97,0xbeb83f7f,0xbf27becf,0xbf423f6a,0x3ea13f39,0x3f73bf31,0xbe2f3f77,0x3f7cbe89,0x3f09bf7e,0xbf58bdfb,
0x3f51bf73,0xbf13bea1,0xbe60bf27,0xbf7a3f42,0xbf4abcc9,0xbf1d3f80,0xbf5f3f6a,0x3efc3ecf,0xbeb83f77,0x3f6fbe89,0x3f393dfb,0x3f31bf7e,0x3f7fbf09,0x3d97bf58,0x3ee6bf7c,0xbf653e2f,
0xbf733f6a,0x3ea13ecf,0xbf7f3f31,0xbd973f39,0x3e603efc,0x3f7abf5f,0xbe2f3f4a,0x3f7cbf1d,0x3f7ebf51,0xbdfbbf13,0x3f77bf09,0x3e89bf58,0xbcc9bf27,0xbf803f42,0x3eb8bf65,0xbf6f3ee6,
0x3f80bf5f,0xbcc9befc,0xbeb83f4a,0x3f6fbf1d,0x3ee6bf58,0xbf653f09,0x3f27be2f,0x3f42bf7c,0xbf133d97,0xbf513f7f,0x3f7abf73,0xbe60bea1,0xbf7e3f6a,0x3dfb3ecf,0x3e89bf39,0xbf773f31,
0xbf773f51,0xbe893f13,0x3f4abf09,0x3f1dbf58,0xbf6a3f7f,0x3ecfbd97,0x3f80bf73,0xbcc9bea1,0xbee63f39,0x3f65bf31,0x3f42bf6f,0xbf273eb8,0x3e603dfb,0x3f7abf7e,0x3e2fbefc,0xbf7c3f5f,
0x3f58bf42,0x3f09bf27,0x3f51bf65,0xbf133ee6,0x3f77bf6a,0x3e89becf,0x3f1dbf39,0xbf4a3f31,0x3f80bf7e,0xbcc9bdfb,0x3eb8befc,0xbf6f3f5f,0x3f73bf7c,0xbea13e2f,0x3d97be60,0xbf7f3f7a,
0xbf273f31,0xbf423f39,0xbea13eb8,0xbf733f6f,0xbf133f1d,0xbf513f4a,0xbe603e89,0xbf7a3f77,0xbefc3f09,0xbf5f3f58,0xbdfb3e2f,0xbf7e3f7c,0xbecf3ee6,0xbf6a3f65,0xbcc93d97,0xbf803f7f,
0x3ecfbf1d,0x3f6abf4a,0xbf803f77,0x3cc9be89,0xbd97be2f,0x3f7fbf7c,0xbf653f7a,0xbee63e60,0xbf093ea1,0x3f58bf73,0xbf133f42,0xbf513f27,0xbf5f3f39,0x3efcbf31,0xbdfb3eb8,0xbf7e3f6f,
0xbdfb3f09,0xbf7e3f58,0xbe89be2f,0x3f77bf7c,0x3f31bea1,0xbf393f73,0xbf6a3f27,0x3ecfbf42,0x3f7fbf6f,0x3d973eb8,0xbf653f80,0xbee63cc9,0x3f13bf5f,0x3f51befc,0xbe603f1d,0xbf7a3f4a,
0xbe2fbee6,0x3f7cbf65,0x3f58bf7f,0x3f093d97,0xbf7e3f39,0x3dfbbf31,0xbe89beb8,0x3f77bf6f,0xbecf3f5f,0xbf6a3efc,0xbf803f4a,0x3cc9bf1d,0x3f42be60,0xbf273f7a,0xbea13f51,0xbf733f13,
0x3ee63eb8,0xbf653f6f,0x3f42bcc9,0xbf273f80,0x3f58bf77,0x3f093e89,0x3f13bf7e,0x3f51bdfb,0xbf1dbe2f,0x3f4abf7c,0xbf5f3e60,0x3efcbf7a,0xbf393f7f,0xbf31bd97,0xbecf3f73,0xbf6a3ea1,
0xbf31be89,0x3f39bf77,0xbecf3f7e,0xbf6a3dfb,0xbea13f7a,0xbf733e60,0x3f7fbf13,0x3d973f51,0x3f7cbf27,0x3e2f3f42,0xbf09bee6,0x3f58bf65,0xbf1dbeb8,0x3f4abf6f,0xbefc3f80,0xbf5f3cc9,
0x3f5f3e2f,0xbefc3f7c,0xbf7e3e60,0x3dfbbf7a,0xbeb8bf42,0x3f6fbf27,0x3f313ee6,0xbf393f65,0xbea13f80,0xbf733cc9,0xbd97bf6a,0x3f7fbecf,0x3f58bf4a,0x3f093f1d,0xbf133f77,0xbf51be89,
0xbf7abd97,0x3e60bf7f,0xbe2fbf73,0x3f7cbea1,0x3f5f3eb8,0xbefc3f6f,0xbdfb3f80,0xbf7e3cc9,0xbf31bf1d,0x3f39bf4a,0x3ecfbf77,0x3f6a3e89,0x3ee63f51,0xbf653f13,0xbf273f58,0xbf42bf09,
0x3f7fbcc9,0x3d973f80,0x3f65becf,0x3ee63f6a,0xbf7c3dfb,0xbe2fbf7e,0xbf583efc,0xbf09bf5f,0x3f77be60,0x3e893f7a,0x3f4abf13,0x3f1d3f51,0xbf6f3ea1,0xbeb8bf73,0xbf393f27,0xbf31bf42,
0xbf6f3dfb,0xbeb8bf7e,0x3f313f5f,0xbf393efc,0x3f27bf13,0x3f423f51,0xbf73bf09,0x3ea1bf58,0xbe603f65,0xbf7abee6,0x3f7c3d97,0x3e2f3f7f,0xbe89bf80,0x3f77bcc9,0xbf4a3ecf,0xbf1dbf6a,
0x3f4abe60,0x3f1d3f7a,0xbefc3f13,0xbf5fbf51,0xbcc93f65,0xbf80bee6,0xbeb8bf7f,0x3f6f3d97,0xbf42bf6a,0x3f27becf,0x3f733f31,0xbea13f39,0x3f7c3e89,0x3e2f3f77,0xbf583dfb,0xbf09bf7e,
0xbf133ea1,0xbf51bf73,0xbf7abf42,0x3e60bf27,0xbf1dbf80,0x3f4abcc9,0x3efcbecf,0x3f5f3f6a,0x3f6f3e89,0x3eb83f77,0x3f313f7e,0xbf393dfb,0x3d973f58,0xbf7fbf09,0xbf65be2f,0xbee6bf7c,
0x3ea1becf,0x3f733f6a,0xbd97bf39,0x3f7f3f31,0x3f7a3f5f,0xbe603efc,0x3f7c3f1d,0x3e2f3f4a,0xbdfb3f13,0xbf7ebf51,0x3e893f58,0xbf77bf09,0xbf80bf42,0x3cc9bf27,0xbf6fbee6,0xbeb8bf65,
0xbcc93efc,0xbf80bf5f,0x3f6f3f1d,0x3eb83f4a,0xbf65bf09,0xbee6bf58,0x3f423f7c,0xbf27be2f,0xbf51bf7f,0x3f133d97,0xbe603ea1,0xbf7abf73,0x3dfbbecf,0x3f7e3f6a,0xbf77bf31,0xbe89bf39,
0xbe89bf13,0x3f773f51,0x3f1d3f58,0xbf4abf09,0x3ecf3d97,0x3f6a3f7f,0xbcc93ea1,0xbf80bf73,0x3f653f31,0x3ee63f39,0xbf27beb8,0xbf42bf6f,0x3f7a3f7e,0xbe603dfb,0xbf7cbf5f,0xbe2fbefc,
0x3f093f27,0xbf58bf42,0xbf13bee6,0xbf51bf65,0x3e893ecf,0xbf77bf6a,0xbf4abf31,0xbf1dbf39,0xbcc93dfb,0xbf80bf7e,0xbf6fbf5f,0xbeb8befc,0xbea1be2f,0xbf73bf7c,0xbf7fbf7a,0xbd97be60,
0x3f6e3f7a,0x3f1f3f28,0x3ec23ed0,0x3e2f3e48,0x3f583f63,0x3f0e3f17,0x3ea63eb4,0x3df93e15,0x3f443f4e,0x3efd3f06,0x3e8b3e99,0x3d953dc7,0x3f313f3a,0x3edf3eee,0x3e623e7c,0x3cc63d46,
0x3f583f62,0x3f133f1b,0x3eb53ec2,0x3e243e3b,0x3f453f4f,0x3f043f0b,0x3e9b3ea8,0x3de93e0c,0x3f333f3c,0x3eeb3ef9,0x3e823e8f,0x3d8b3dba,0x3f233f2b,0x3ecf3edd,0x3e533e6c,0x3cb93d39,
0x3f443f4d,0x3f073f0e,0x3ea83eb4,0x3e183e2e,0x3f343f3c,0x3ef33f00,0x3e903e9c,0x3dd93e02,0x3f243f2c,0x3ed93ee6,0x3e723e84,0x3d823dad,0x3f153f1c,0x3ec03ecc,0x3e453e5b,0x3cad3d2d,
0x3f323f39,0x3ef73f02,0x3e9b3ea6,0x3e0d3e22,0x3f233f2a,0x3edf3eeb,0x3e853e90,0x3dc93df1,0x3f153f1c,0x3ec83ed3,0x3e603e75,0x3d713da1,0x3f083f0f,0x3eb13ebc,0x3e363e4b,0x3ca03d20,
0x3f203f27,0x3ee13eec,0x3e8e3e98,0x3e023e15,0x3f133f1a,0x3ecc3ed6,0x3e743e84,0x3db93dde,0x3f073f0d,0x3eb73ec1,0x3e4e3e61,0x3d5e3d94,0x3ef83f02,0x3ea23eac,0x3e283e3b,0x3c943d14,
0x3f103f15,0x3ecc3ed6,0x3e813e8a,0x3ded3e08,0x3f053f0a,0x3eb93ec2,0x3e5f3e71,0x3da93dcb,0x3ef43eff,0x3ea63eaf,0x3e3c3e4d,0x3d4b3d87,0x3ee03eea,0x3e933e9d,0x3e193e2a,0x3c873d07,
0x3f003f05,0x3eb73ec0,0x3e6a3e7a,0x3dd73df6,0x3eed3ef6,0x3ea63eaf,0x3e4a3e5a,0x3d993db8,0x3edb3ee4,0x3e963e9e,0x3e2a3e3a,0x3d383d75,0x3ec93ed2,0x3e853e8d,0x3e0b3e1a,0x3c753cf5,
0x3ee23eeb,0x3ea33eab,0x3e513e5f,0x3dc13ddd,0x3ed23eda,0x3e943e9c,0x3e353e43,0x3d8a3da5,0x3ec23eca,0x3e853e8d,0x3e183e26,0x3d253d5c,0x3eb33eba,0x3e6e3e7c,0x3df93e0a,0x3c5c3cdc,
0x3ec63ecd,0x3e903e96,0x3e393e45,0x3dab3dc3,0x3eb83ebf,0x3e833e89,0x3e203e2c,0x3d743d92,0x3eaa3eb1,0x3e6b3e78,0x3e073e13,0x3d123d43,0x3e9d3ea3,0x3e523e5f,0x3ddc3df5,0x3c433cc3,
0x3eaa3eb0,0x3e793e82,0x3e203e2b,0x3d953daa,0x3e9f3ea4,0x3e623e6d,0x3e0b3e15,0x3d543d7f,0x3e933e99,0x3e4c3e57,0x3dea3e00,0x3cff3d2a,0x3e883e8d,0x3e363e41,0x3dbf3dd5,0x3c2a3caa,
0x3e903e94,0x3e533e5c,0x3e083e11,0x3d7d3d91,0x3e863e8b,0x3e403e49,0x3dec3dfe,0x3d353d59,0x3e793e81,0x3e2d3e37,0x3dc73dda,0x3cd93d11,0x3e663e6f,0x3e1b3e24,0x3da33db5,0x3c113c91,
0x3e6b3e73,0x3e2d3e35,0x3de13df0,0x3d513d6f,0x3e5c3e63,0x3e1e3e26,0x3dc33dd2,0x3d153d33,0x3e4c3e54,0x3e0f3e16,0x3da53db4,0x3cb33cef,0x3e3d3e44,0x3dff3e07,0x3d863d95,0x3bef3c6f,
0x3e393e3f,0x3e083e0e,0x3db13dbd,0x3d253d3d,0x3e2c3e32,0x3df93e02,0x3d993da5,0x3cec3d0d,0x3e203e26,0x3de13ded,0x3d823d8e,0x3c8d3cbd,0x3e143e1a,0x3dc93dd5,0x3d543d6c,0x3bbc3c3d,
0x3e073e0b,0x3dc73dd0,0x3d823d8a,0x3cf23d0a,0x3dfc3e02,0x3db63dbf,0x3d613d72,0x3cad3ccf,0x3dea3df3,0x3da53dad,0x3d3e3d50,0x3c4f3c8a,0x3dd93de2,0x3d933d9c,0x3d1c3d2d,0x3b8a3c0a,
0x3dab3db0,0x3d7d3d84,0x3d253d30,0x3c9a3cb0,0x3da03da5,0x3d673d72,0x3d0f3d1a,0x3c5c3c84,0x3d953d9a,0x3d513d5c,0x3cf23d04,0x3c043c30,0x3d8a3d8f,0x3d3b3d46,0x3cc63cdc,0x3b303bb0,
0x3d123d17,0x3cd93ce2,0x3c8d3c97,0x3c043c17,0x3d093d0d,0x3cc63ccf,0x3c753c84,0x3bbc3be2,0x3cff3d04,0x3cb33cbd,0x3c4f3c62,0x3b623b97,0x3cec3cf5,0x3ca03caa,0x3c2a3c3d,0x3a973b17,
0xbc43bc49,0xbc11bc17,0xbbbcbbc9,0xbb30bb49,0xbc36bc3d,0xbc04bc0a,0xbba3bbb0,0xbafbbb17,0xbc2abc30,0xbbefbbfb,0xbb8abb97,0xba97bac9,0xbc1dbc23,0xbbd6bbe2,0xbb62bb7b,0xb9c9ba49,
0xbd74bd7c,0xbd35bd3d,0xbcecbcfb,0xbc5cbc7b,0xbd64bd6c,0xbd25bd2d,0xbcccbcdc,0xbc1dbc3d,0xbd54bd5c,0xbd15bd1d,0xbcadbcbd,0xbbbcbbfb,0xbd45bd4c,0xbd06bd0d,0xbc8dbc9d,0xbafbbb7b,
0xbddcbde3,0xbda3bdaa,0xbd54bd62,0xbcc6bce2,0xbdcebdd5,0xbd95bd9c,0xbd38bd46,0xbc8dbcaa,0xbdbfbdc7,0xbd86bd8e,0xbd1cbd2a,0xbc2abc62,0xbdb1bdb8,0xbd71bd7f,0xbcffbd0d,0xbb62bbe2,
0xbe20be25,0xbdecbdf6,0xbd99bda4,0xbd0fbd23,0xbe15be1a,0xbdd7bde2,0xbd85bd8f,0xbcccbcf5,0xbe0bbe10,0xbdc3bdcd,0xbd61bd75,0xbc75bca3,0xbe00be05,0xbdaebdb8,0xbd38bd4c,0xbba3bc23,
0xbe52be59,0xbe1bbe22,0xbdc9bdd6,0xbd3bbd56,0xbe44be4b,0xbe0dbe14,0xbdaebdbb,0xbd06bd20,0xbe36be3d,0xbdffbe06,0xbd93bda1,0xbca0bcd6,0xbe28be2f,0xbde4bdf1,0xbd71bd86,0xbbd6bc56,
0xbe83be87,0xbe40be48,0xbdf9be05,0xbd67bd84,0xbe74be7c,0xbe2fbe37,0xbdd7bde8,0xbd25bd46,0xbe62be6b,0xbe1ebe26,0xbdb6bdc7,0xbcc6bd04,0xbe51be5a,0xbe0dbe15,0xbd95bda5,0xbc04bc84,
0xbe9dbea2,0xbe66be70,0xbe14be1e,0xbd8abd9d,0xbe92be97,0xbe51be5b,0xbe00be0a,0xbd45bd6c,0xbe88be8d,0xbe3dbe47,0xbdd9bded,0xbcecbd1d,0xbe7abe82,0xbe28be32,0xbdb1bdc5,0xbc1dbc9d,
0xbeb8bebe,0xbe86be8c,0xbe2cbe38,0xbda0bdb7,0xbeabbeb1,0xbe74be80,0xbe15be21,0xbd64bd89,0xbe9fbea5,0xbe5cbe68,0xbdfcbe09,0xbd09bd36,0xbe92be98,0xbe44be50,0xbdcebde5,0xbc36bcb6,
0xbed4bedb,0xbe99bea0,0xbe45be52,0xbdb6bdd0,0xbec5becc,0xbe8bbe92,0xbe2abe37,0xbd82bd9c,0xbeb6bebd,0xbe7bbe84,0xbe0fbe1d,0xbd1cbd50,0xbea8beaf,0xbe60be6d,0xbdeabe02,0xbc4fbccf,
0xbef1befa,0xbeadbeb5,0xbe5dbe6d,0xbdccbde9,0xbedfbee8,0xbe9dbea5,0xbe3fbe4e,0xbd92bdaf,0xbecebed7,0xbe8dbe95,0xbe21be30,0xbd2ebd69,0xbebebec6,0xbe7cbe86,0xbe03be12,0xbc68bce9,
0xbf08bf0d,0xbec2becb,0xbe76be84,0xbde2be01,0xbefbbf03,0xbeafbeb9,0xbe54be65,0xbda1bdc2,0xbee7bef1,0xbe9ebea7,0xbe33be44,0xbd41bd81,0xbed4bede,0xbe8cbe95,0xbe12be22,0xbc81bd01,
0xbf18bf1e,0xbed7bee1,0xbe88be91,0xbdf9be0e,0xbf0cbf12,0xbec2becc,0xbe6abe7c,0xbdb1bdd5,0xbf01bf06,0xbeaebeb8,0xbe45be57,0xbd54bd8e,0xbeecbef6,0xbe9bbea4,0xbe20be32,0xbc8dbd0d,
0xbf29bf30,0xbeecbef8,0xbe94be9f,0xbe07be1b,0xbf1bbf22,0xbed5bee1,0xbe7fbe8a,0xbdc1bde8,0xbf0ebf15,0xbebfbeca,0xbe57be6b,0xbd67bd9a,0xbf02bf08,0xbea9beb4,0xbe2fbe43,0xbc9abd1a,
0xbf3bbf43,0xbf01bf08,0xbea1bead,0xbe13be28,0xbf2bbf33,0xbee9bef6,0xbe8bbe96,0xbdd1bdfb,0xbf1dbf24,0xbed0bedc,0xbe69be7f,0xbd7abda7,0xbf0fbf15,0xbeb8bec4,0xbe3dbe53,0xbca7bd27,
0xbf4ebf57,0xbf0dbf14,0xbeaebebb,0xbe1ebe35,0xbf3cbf45,0xbefdbf06,0xbe96bea2,0xbde1be07,0xbf2bbf34,0xbee2beef,0xbe7bbe89,0xbd86bdb4,0xbf1cbf23,0xbec8bed5,0xbe4cbe63,0xbcb3bd33,
0xbf63bf6e,0xbf19bf21,0xbebbbec9,0xbe29be42,0xbf4ebf58,0xbf09bf11,0xbea1beae,0xbdf1be11,0xbf3bbf45,0xbef4bf01,0xbe87be94,0xbd90bdc0,0xbf29bf32,0xbed7bee5,0xbe5bbe74,0xbcc0bd40,
0xbcc68000,0xbe62be48,0xbedfbed0,0xbf31bf28,0xbd95bd46,0xbe8bbe7c,0xbefdbeee,0xbf44bf3a,0xbdf9bdc7,0xbea6be99,0xbf0ebf06,0xbf58bf4e,0xbe2fbe15,0xbec2beb4,0xbf1fbf17,0xbf6ebf63,
0xbcb98000,0xbe53be3b,0xbecfbec2,0xbf23bf1b,0xbd8bbd39,0xbe82be6c,0xbeebbedd,0xbf33bf2b,0xbde9bdba,0xbe9bbe8f,0xbf04bef9,0xbf45bf3c,0xbe24be0c,0xbeb5bea8,0xbf13bf0b,0xbf58bf4f,
0xbcad8000,0xbe45be2e,0xbec0beb4,0xbf15bf0e,0xbd82bd2d,0xbe72be5b,0xbed9becc,0xbf24bf1c,0xbdd9bdad,0xbe90be84,0xbef3bee6,0xbf34bf2c,0xbe18be02,0xbea8be9c,0xbf07bf00,0xbf44bf3c,
0xbca08000,0xbe36be22,0xbeb1bea6,0xbf08bf02,0xbd71bd20,0xbe60be4b,0xbec8bebc,0xbf15bf0f,0xbdc9bda1,0xbe85be75,0xbedfbed3,0xbf23bf1c,0xbe0dbdf1,0xbe9bbe90,0xbef7beeb,0xbf32bf2a,
0xbc948000,0xbe28be15,0xbea2be98,0xbef8beec,0xbd5ebd14,0xbe4ebe3b,0xbeb7beac,0xbf07bf02,0xbdb9bd94,0xbe74be61,0xbeccbec1,0xbf13bf0d,0xbe02bdde,0xbe8ebe84,0xbee1bed6,0xbf20bf1a,
0xbc878000,0xbe19be08,0xbe93be8a,0xbee0bed6,0xbd4bbd07,0xbe3cbe2a,0xbea6be9d,0xbef4beea,0xbda9bd87,0xbe5fbe4d,0xbeb9beaf,0xbf05beff,0xbdedbdcb,0xbe81be71,0xbeccbec2,0xbf10bf0a,
0xbc758000,0xbe0bbdf6,0xbe85be7a,0xbec9bec0,0xbd38bcf5,0xbe2abe1a,0xbe96be8d,0xbedbbed2,0xbd99bd75,0xbe4abe3a,0xbea6be9e,0xbeedbee4,0xbdd7bdb8,0xbe6abe5a,0xbeb7beaf,0xbf00bef6,
0xbc5c8000,0xbdf9bddd,0xbe6ebe5f,0xbeb3beab,0xbd25bcdc,0xbe18be0a,0xbe85be7c,0xbec2beba,0xbd8abd5c,0xbe35be26,0xbe94be8d,0xbed2beca,0xbdc1bda5,0xbe51be43,0xbea3be9c,0xbee2beda,
0xbc438000,0xbddcbdc3,0xbe52be45,0xbe9dbe96,0xbd12bcc3,0xbe07bdf5,0xbe6bbe5f,0xbeaabea3,0xbd74bd43,0xbe20be13,0xbe83be78,0xbeb8beb1,0xbdabbd92,0xbe39be2c,0xbe90be89,0xbec6bebf,
0xbc2a8000,0xbdbfbdaa,0xbe36be2b,0xbe88be82,0xbcffbcaa,0xbdeabdd5,0xbe4cbe41,0xbe93be8d,0xbd54bd2a,0xbe0bbe00,0xbe62be57,0xbe9fbe99,0xbd95bd7f,0xbe20be15,0xbe79be6d,0xbeaabea4,
0xbc118000,0xbda3bd91,0xbe1bbe11,0xbe66be5c,0xbcd9bc91,0xbdc7bdb5,0xbe2dbe24,0xbe79be6f,0xbd35bd11,0xbdecbdda,0xbe40be37,0xbe86be81,0xbd7dbd59,0xbe08bdfe,0xbe53be49,0xbe90be8b,
0xbbef8000,0xbd86bd6f,0xbdffbdf0,0xbe3dbe35,0xbcb3bc6f,0xbda5bd95,0xbe0fbe07,0xbe4cbe44,0xbd15bcef,0xbdc3bdb4,0xbe1ebe16,0xbe5cbe54,0xbd51bd33,0xbde1bdd2,0xbe2dbe26,0xbe6bbe63,
0xbbbc8000,0xbd54bd3d,0xbdc9bdbd,0xbe14be0e,0xbc8dbc3d,0xbd82bd6c,0xbde1bdd5,0xbe20be1a,0xbcecbcbd,0xbd99bd8e,0xbdf9bded,0xbe2cbe26,0xbd25bd0d,0xbdb1bda5,0xbe08be02,0xbe39be32,
0xbb8a8000,0xbd1cbd0a,0xbd93bd8a,0xbdd9bdd0,0xbc4fbc0a,0xbd3ebd2d,0xbda5bd9c,0xbdeabde2,0xbcadbc8a,0xbd61bd50,0xbdb6bdad,0xbdfcbdf3,0xbcf2bccf,0xbd82bd72,0xbdc7bdbf,0xbe07be02,
0xbb308000,0xbcc6bcb0,0xbd3bbd30,0xbd8abd84,0xbc04bbb0,0xbcf2bcdc,0xbd51bd46,0xbd95bd8f,0xbc5cbc30,0xbd0fbd04,0xbd67bd5c,0xbda0bd9a,0xbc9abc84,0xbd25bd1a,0xbd7dbd72,0xbdabbda5,
0xba978000,0xbc2abc17,0xbca0bc97,0xbcecbce2,0xbb62bb17,0xbc4fbc3d,0xbcb3bcaa,0xbcffbcf5,0xbbbcbb97,0xbc75bc62,0xbcc6bcbd,0xbd09bd04,0xbc04bbe2,0xbc8dbc84,0xbcd9bccf,0xbd12bd0d,
0x39c90000,0x3b623b49,0x3bd63bc9,0x3c1d3c17,0x3a973a49,0x3b8a3b7b,0x3bef3be2,0x3c2a3c23,0x3afb3ac9,0x3ba33b97,0x3c043bfb,0x3c363c30,0x3b303b17,0x3bbc3bb0,0x3c113c0a,0x3c433c3d,
0x3afb0000,0x3c8d3c7b,0x3d063cfb,0x3d453d3d,0x3bbc3b7b,0x3cad3c9d,0x3d153d0d,0x3d543d4c,0x3c1d3bfb,0x3ccc3cbd,0x3d253d1d,0x3d643d5c,0x3c5c3c3d,0x3cec3cdc,0x3d353d2d,0x3d743d6c,
0x3b620000,0x3cff3ce2,0x3d713d62,0x3db13daa,0x3c2a3be2,0x3d1c3d0d,0x3d863d7f,0x3dbf3db8,0x3c8d3c62,0x3d383d2a,0x3d953d8e,0x3dce3dc7,0x3cc63caa,0x3d543d46,0x3da33d9c,0x3ddc3dd5,
0x3ba30000,0x3d383d23,0x3dae3da4,0x3e003df6,0x3c753c23,0x3d613d4c,0x3dc33db8,0x3e0b3e05,0x3ccc3ca3,0x3d853d75,0x3dd73dcd,0x3e153e10,0x3d0f3cf5,0x3d993d8f,0x3dec3de2,0x3e203e1a,
0x3bd60000,0x3d713d56,0x3de43dd6,0x3e283e22,0x3ca03c56,0x3d933d86,0x3dff3df1,0x3e363e2f,0x3d063cd6,0x3dae3da1,0x3e0d3e06,0x3e443e3d,0x3d3b3d20,0x3dc93dbb,0x3e1b3e14,0x3e523e4b,
0x3c040000,0x3d953d84,0x3e0d3e05,0x3e513e48,0x3cc63c84,0x3db63da5,0x3e1e3e15,0x3e623e5a,0x3d253d04,0x3dd73dc7,0x3e2f3e26,0x3e743e6b,0x3d673d46,0x3df93de8,0x3e403e37,0x3e833e7c,
0x3c1d0000,0x3db13d9d,0x3e283e1e,0x3e7a3e70,0x3cec3c9d,0x3dd93dc5,0x3e3d3e32,0x3e883e82,0x3d453d1d,0x3e003ded,0x3e513e47,0x3e923e8d,0x3d8a3d6c,0x3e143e0a,0x3e663e5b,0x3e9d3e97,
0x3c360000,0x3dce3db7,0x3e443e38,0x3e923e8c,0x3d093cb6,0x3dfc3de5,0x3e5c3e50,0x3e9f3e98,0x3d643d36,0x3e153e09,0x3e743e68,0x3eab3ea5,0x3da03d89,0x3e2c3e21,0x3e863e80,0x3eb83eb1,
0x3c4f0000,0x3dea3dd0,0x3e603e52,0x3ea83ea0,0x3d1c3ccf,0x3e0f3e02,0x3e7b3e6d,0x3eb63eaf,0x3d823d50,0x3e2a3e1d,0x3e8b3e84,0x3ec53ebd,0x3db63d9c,0x3e453e37,0x3e993e92,0x3ed43ecc,
0x3c680000,0x3e033de9,0x3e7c3e6d,0x3ebe3eb5,0x3d2e3ce9,0x3e213e12,0x3e8d3e86,0x3ece3ec6,0x3d923d69,0x3e3f3e30,0x3e9d3e95,0x3edf3ed7,0x3dcc3daf,0x3e5d3e4e,0x3ead3ea5,0x3ef13ee8,
0x3c810000,0x3e123e01,0x3e8c3e84,0x3ed43ecb,0x3d413d01,0x3e333e22,0x3e9e3e95,0x3ee73ede,0x3da13d81,0x3e543e44,0x3eaf3ea7,0x3efb3ef1,0x3de23dc2,0x3e763e65,0x3ec23eb9,0x3f083f03,
0x3c8d0000,0x3e203e0e,0x3e9b3e91,0x3eec3ee1,0x3d543d0d,0x3e453e32,0x3eae3ea4,0x3f013ef6,0x3db13d8e,0x3e6a3e57,0x3ec23eb8,0x3f0c3f06,0x3df93dd5,0x3e883e7c,0x3ed73ecc,0x3f183f12,
0x3c9a0000,0x3e2f3e1b,0x3ea93e9f,0x3f023ef8,0x3d673d1a,0x3e573e43,0x3ebf3eb4,0x3f0e3f08,0x3dc13d9a,0x3e7f3e6b,0x3ed53eca,0x3f1b3f15,0x3e073de8,0x3e943e8a,0x3eec3ee1,0x3f293f22,
0x3ca70000,0x3e3d3e28,0x3eb83ead,0x3f0f3f08,0x3d7a3d27,0x3e693e53,0x3ed03ec4,0x3f1d3f15,0x3dd13da7,0x3e8b3e7f,0x3ee93edc,0x3f2b3f24,0x3e133dfb,0x3ea13e96,0x3f013ef6,0x3f3b3f33,
0x3cb30000,0x3e4c3e35,0x3ec83ebb,0x3f1c3f14,0x3d863d33,0x3e7b3e63,0x3ee23ed5,0x3f2b3f23,0x3de13db4,0x3e963e89,0x3efd3eef,0x3f3c3f34,0x3e1e3e07,0x3eae3ea2,0x3f0d3f06,0x3f4e3f45,
0x3cc00000,0x3e5b3e42,0x3ed73ec9,0x3f293f21,0x3d903d40,0x3e873e74,0x3ef43ee5,0x3f3b3f32,0x3df13dc0,0x3ea13e94,0x3f093f01,0x3f4e3f45,0x3e293e11,0x3ebb3eae,0x3f193f11,0x3f633f58,
0x3f7f3f80,0x3f653f6b,0x3f2a3f33,0x3eaa3ec1,0x3f7c3f7e,0x3f593f60,0x3f163f20,0x3e753e92,0x3f773f7a,0x3f4b3f53,0x3f023f0c,0x3e143e45,0x3f6f3f73,0x3f3b3f44,0x3ed83eee,0x3d463dc6,
0x3f7c3f7e,0x3f5d3f63,0x3f213f2a,0x3e9f3eb5,0x3f773f7a,0x3f503f57,0x3f0e3f18,0x3e663e89,0x3f713f74,0x3f423f49,0x3ef43f04,0x3e0b3e38,0x3f683f6c,0x3f323f3a,0x3ecb3ee0,0x3d393db9,
0x3f773f7a,0x3f533f59,0x3f173f20,0x3e953eaa,0x3f713f74,0x3f463f4d,0x3f053f0f,0x3e563e80,0x3f693f6d,0x3f383f3f,0x3ee53ef8,0x3e013e2c,0x3f5f3f64,0x3f283f30,0x3ebe3ed2,0x3d2d3dad,
0x3f703f73,0x3f483f4f,0x3f0e3f16,0x3e8a3e9e,0x3f683f6c,0x3f3b3f42,0x3ef93f05,0x3e473e6e,0x3f5f3f64,0x3f2d3f34,0x3ed63ee8,0x3df03e20,0x3f543f5a,0x3f1e3f26,0x3eb13ec3,0x3d203da0,
0x3f663f6a,0x3f3d3f43,0x3f043f0c,0x3e803e92,0x3f5d3f62,0x3f303f36,0x3ee73ef8,0x3e383e5c,0x3f543f59,0x3f223f29,0x3ec63ed7,0x3ddd3e13,0x3f493f4e,0x3f133f1b,0x3ea33eb5,0x3d143d94,
0x3f5a3f5f,0x3f303f36,0x3ef33f01,0x3e6a3e86,0x3f513f56,0x3f233f2a,0x3ed53ee4,0x3e283e49,0x3f473f4c,0x3f163f1d,0x3eb63ec5,0x3dca3e07,0x3f3c3f42,0x3f083f0f,0x3e963ea6,0x3d073d87,
0x3f4d3f51,0x3f233f28,0x3ede3eec,0x3e553e73,0x3f433f48,0x3f163f1d,0x3ec23ed0,0x3e193e37,0x3f393f3e,0x3f0a3f10,0x3ea53eb4,0x3db83df4,0x3f2e3f34,0x3ef93f03,0x3e883e97,0x3cf53d75,
0x3f3d3f42,0x3f143f1a,0x3ec93ed5,0x3e3f3e5a,0x3f343f39,0x3f093f0f,0x3eaf3ebc,0x3e093e24,0x3f2a3f2f,0x3efa3f03,0x3e953ea2,0x3da53ddb,0x3f1f3f25,0x3ee23eee,0x3e753e88,0x3cdc3d5c,
0x3f2c3f31,0x3f053f0a,0x3eb33ebe,0x3e2a3e42,0x3f233f28,0x3ef53f00,0x3e9c3ea7,0x3df33e12,0x3f193f1e,0x3ee03eea,0x3e843e90,0x3d923dc2,0x3f0f3f14,0x3ec93ed4,0x3e593e71,0x3cc33d43,
0x3f193f1d,0x3eeb3ef4,0x3e9c3ea7,0x3e143e29,0x3f113f15,0x3ed83ee1,0x3e883e92,0x3dd43dfe,0x3f083f0c,0x3ec43ece,0x3e673e7c,0x3d7e3da9,0x3efd3f03,0x3eb13eba,0x3e3e3e53,0x3caa3d2a,
0x3f053f09,0x3eca3ed2,0x3e863e8f,0x3dfc3e10,0x3efb3f01,0x3eb93ec2,0x3e693e7a,0x3db43dd8,0x3eeb3ef3,0x3ea83eb1,0x3e453e57,0x3d593d90,0x3edb3ee3,0x3e973ea0,0x3e223e34,0x3c913d10,
0x3ee03ee6,0x3ea83eaf,0x3e5e3e6d,0x3dd13dee,0x3ed23ed9,0x3e9a3ea1,0x3e413e4f,0x3d953db3,0x3ec43ecb,0x3e8c3e93,0x3e233e32,0x3d333d6f,0x3eb63ebd,0x3e7b3e85,0x3e063e15,0x3c6f3cef,
0x3eb33eb8,0x3e863e8c,0x3e303e3b,0x3da53dbc,0x3ea83ead,0x3e753e80,0x3e193e24,0x3d6b3d8d,0x3e9c3ea2,0x3e5e3e6a,0x3e013e0d,0x3d0d3d3c,0x3e913e97,0x3e473e53,0x3dd43deb,0x3c3c3cbc,
0x3e843e89,0x3e453e4e,0x3e013e0a,0x3d723d8a,0x3e783e80,0x3e343e3d,0x3de03df1,0x3d2d3d4f,0x3e673e70,0x3e233e2c,0x3dbe3dcf,0x3ccf3d0a,0x3e563e5f,0x3e123e1b,0x3d9b3dad,0x3c0a3c8a,
0x3e2a3e2f,0x3dfc3e04,0x3da53db0,0x3d1a3d30,0x3e1f3e24,0x3de63df1,0x3d8f3d9a,0x3cdc3d04,0x3e143e19,0x3dd13ddb,0x3d723d84,0x3c843cb0,0x3e093e0e,0x3dbb3dc6,0x3d463d5c,0x3bb03c30,
0x3d923d97,0x3d593d62,0x3d0d3d17,0x3c843c97,0x3d893d8d,0x3d463d4f,0x3cf53d04,0x3c3c3c62,0x3d7e3d84,0x3d333d3c,0x3ccf3ce2,0x3be23c17,0x3d6b3d75,0x3d203d2a,0x3caa3cbc,0x3b173b97,
0xbcc3bcc9,0xbc91bc97,0xbc3cbc49,0xbbb0bbc9,0xbcb6bcbc,0xbc84bc8a,0xbc23bc30,0xbb7bbb97,0xbcaabcb0,0xbc6fbc7b,0xbc0abc17,0xbb17bb49,0xbc9dbca3,0xbc56bc62,0xbbe2bbfb,0xba49bac9,
0xbdf3bdfb,0xbdb4bdbc,0xbd6bbd7b,0xbcdcbcfb,0xbde3bdeb,0xbda5bdad,0xbd4cbd5c,0xbc9dbcbc,0xbdd4bddb,0xbd95bd9d,0xbd2dbd3c,0xbc3cbc7b,0xbdc4bdcc,0xbd85bd8d,0xbd0dbd1d,0xbb7bbbfb,
0xbe59be60,0xbe22be29,0xbdd4bde2,0xbd46bd62,0xbe4cbe53,0xbe14be1b,0xbdb8bdc6,0xbd0dbd2a,0xbe3ebe45,0xbe06be0d,0xbd9bbda9,0xbcaabce2,0xbe30be37,0xbdf0bdfe,0xbd7ebd8d,0xbbe2bc62,
0xbe9cbea1,0xbe69be73,0xbe19be23,0xbd8fbda3,0xbe92be97,0xbe55be5f,0xbe04be0e,0xbd4cbd75,0xbe88be8d,0xbe41be4b,0xbde0bdf4,0xbcf5bd23,0xbe7dbe83,0xbe2dbe37,0xbdb8bdcc,0xbc23bca3,
0xbec9becf,0xbe97be9e,0xbe47be54,0xbdbbbdd5,0xbebdbec3,0xbe8abe91,0xbe2dbe3a,0xbd85bda0,0xbeb1beb7,0xbe7bbe84,0xbe12be20,0xbd20bd56,0xbea4beaa,0xbe61be6e,0xbdf0be05,0xbc56bcd6,
0xbef5befc,0xbeb9bec1,0xbe75be82,0xbde6be04,0xbee7beee,0xbeaabeb2,0xbe55be65,0xbda5bdc6,0xbed8bedf,0xbe9abea2,0xbe34be45,0xbd46bd84,0xbec9bed0,0xbe8abe92,0xbe14be24,0xbc84bd04,
0xbf0fbf13,0xbedbbee3,0xbe91be9b,0xbe09be1c,0xbf07bf0b,0xbec9bed2,0xbe7dbe88,0xbdc4bdeb,0xbefdbf03,0xbeb6bec0,0xbe56be6a,0xbd6bbd9d,0xbeecbef5,0xbea4bead,0xbe30be43,0xbc9dbd1d,
0xbf23bf27,0xbefbbf02,0xbea8beb2,0xbe1fbe35,0xbf1abf1e,0xbee7bef1,0xbe92be9d,0xbde3be08,0xbf11bf15,0xbed2bedc,0xbe78be87,0xbd89bdb6,0xbf07bf0c,0xbebdbec8,0xbe4cbe62,0xbcb6bd36,
0xbf35bf39,0xbf0dbf12,0xbebebeca,0xbe34be4e,0xbf2bbf30,0xbf02bf07,0xbea5beb2,0xbe01be1b,0xbf22bf27,0xbeedbef8,0xbe8dbe99,0xbd9bbdcf,0xbf17bf1d,0xbed6bee1,0xbe67be80,0xbccfbd4f,
0xbf45bf4a,0xbf1bbf21,0xbed3bee1,0xbe4abe66,0xbf3cbf41,0xbf10bf16,0xbeb9bec6,0xbe11be2e,0xbf32bf37,0xbf03bf0a,0xbe9dbeab,0xbdaebde8,0xbf27bf2c,0xbeeebefa,0xbe81be8f,0xbce8bd68,
0xbf54bf58,0xbf29bf2f,0xbee9bef7,0xbe60be7f,0xbf4abf4f,0xbf1dbf23,0xbeccbeda,0xbe20be40,0xbf40bf45,0xbf10bf17,0xbeaebebd,0xbdc1be00,0xbf35bf3b,0xbf02bf09,0xbe8fbe9e,0xbd01bd81,
0xbf61bf65,0xbf37bf3d,0xbefdbf06,0xbe75be8c,0xbf58bf5c,0xbf2abf30,0xbedebeee,0xbe30be53,0xbf4ebf53,0xbf1cbf23,0xbebebece,0xbdd4be0d,0xbf42bf48,0xbf0ebf15,0xbe9cbead,0xbd0dbd8d,
0xbf6bbf6f,0xbf43bf49,0xbf09bf11,0xbe85be98,0xbf63bf67,0xbf36bf3c,0xbef0bf01,0xbe3fbe65,0xbf59bf5e,0xbf28bf2f,0xbecebedf,0xbde6be19,0xbf4fbf54,0xbf19bf20,0xbeaabebc,0xbd1abd9a,
0xbf74bf77,0xbf4ebf54,0xbf13bf1b,0xbe90bea4,0xbf6dbf70,0xbf41bf48,0xbf01bf0a,0xbe4fbe77,0xbf64bf68,0xbf33bf3a,0xbeddbef0,0xbdf9be26,0xbf5abf5f,0xbf23bf2b,0xbeb7beca,0xbd26bda6,
0xbf7abf7c,0xbf58bf5e,0xbf1cbf25,0xbe9abeaf,0xbf74bf77,0xbf4bbf52,0xbf0abf13,0xbe5ebe85,0xbf6dbf71,0xbf3dbf44,0xbeedbf00,0xbe06be32,0xbf63bf68,0xbf2dbf35,0xbec4bed9,0xbd33bdb3,
0xbf7ebf7f,0xbf61bf67,0xbf25bf2e,0xbea5bebb,0xbf7abf7c,0xbf55bf5b,0xbf12bf1c,0xbe6dbe8e,0xbf74bf77,0xbf47bf4e,0xbefcbf08,0xbe0fbe3f,0xbf6cbf70,0xbf37bf3f,0xbed1bee7,0xbd40bdbf,
0xbd468000,0xbed8bec1,0xbf3bbf33,0xbf6fbf6b,0xbe14bdc6,0xbf02beee,0xbf4bbf44,0xbf77bf73,0xbe75be45,0xbf16bf0c,0xbf59bf53,0xbf7cbf7a,0xbeaabe92,0xbf2abf20,0xbf65bf60,0xbf7fbf7e,
0xbd398000,0xbecbbeb5,0xbf32bf2a,0xbf68bf63,0xbe0bbdb9,0xbef4bee0,0xbf42bf3a,0xbf71bf6c,0xbe66be38,0xbf0ebf04,0xbf50bf49,0xbf77bf74,0xbe9fbe89,0xbf21bf18,0xbf5dbf57,0xbf7cbf7a,
0xbd2d8000,0xbebebeaa,0xbf28bf20,0xbf5fbf59,0xbe01bdad,0xbee5bed2,0xbf38bf30,0xbf69bf64,0xbe56be2c,0xbf05bef8,0xbf46bf3f,0xbf71bf6d,0xbe95be80,0xbf17bf0f,0xbf53bf4d,0xbf77bf74,
0xbd208000,0xbeb1be9e,0xbf1ebf16,0xbf54bf4f,0xbdf0bda0,0xbed6bec3,0xbf2dbf26,0xbf5fbf5a,0xbe47be20,0xbef9bee8,0xbf3bbf34,0xbf68bf64,0xbe8abe6e,0xbf0ebf05,0xbf48bf42,0xbf70bf6c,
0xbd148000,0xbea3be92,0xbf13bf0c,0xbf49bf43,0xbdddbd94,0xbec6beb5,0xbf22bf1b,0xbf54bf4e,0xbe38be13,0xbee7bed7,0xbf30bf29,0xbf5dbf59,0xbe80be5c,0xbf04bef8,0xbf3dbf36,0xbf66bf62,
0xbd078000,0xbe96be86,0xbf08bf01,0xbf3cbf36,0xbdcabd87,0xbeb6bea6,0xbf16bf0f,0xbf47bf42,0xbe28be07,0xbed5bec5,0xbf23bf1d,0xbf51bf4c,0xbe6abe49,0xbef3bee4,0xbf30bf2a,0xbf5abf56,
0xbcf58000,0xbe88be73,0xbef9beec,0xbf2ebf28,0xbdb8bd75,0xbea5be97,0xbf0abf03,0xbf39bf34,0xbe19bdf4,0xbec2beb4,0xbf16bf10,0xbf43bf3e,0xbe55be37,0xbedebed0,0xbf23bf1d,0xbf4dbf48,
0xbcdc8000,0xbe75be5a,0xbee2bed5,0xbf1fbf1a,0xbda5bd5c,0xbe95be88,0xbefabeee,0xbf2abf25,0xbe09bddb,0xbeafbea2,0xbf09bf03,0xbf34bf2f,0xbe3fbe24,0xbec9bebc,0xbf14bf0f,0xbf3dbf39,
0xbcc38000,0xbe59be42,0xbec9bebe,0xbf0fbf0a,0xbd92bd43,0xbe84be71,0xbee0bed4,0xbf19bf14,0xbdf3bdc2,0xbe9cbe90,0xbef5beea,0xbf23bf1e,0xbe2abe12,0xbeb3bea7,0xbf05bf00,0xbf2cbf28,
0xbcaa8000,0xbe3ebe29,0xbeb1bea7,0xbefdbef4,0xbd7ebd2a,0xbe67be53,0xbec4beba,0xbf08bf03,0xbdd4bda9,0xbe88be7c,0xbed8bece,0xbf11bf0c,0xbe14bdfe,0xbe9cbe92,0xbeebbee1,0xbf19bf15,
0xbc918000,0xbe22be10,0xbe97be8f,0xbedbbed2,0xbd59bd10,0xbe45be34,0xbea8bea0,0xbeebbee3,0xbdb4bd90,0xbe69be57,0xbeb9beb1,0xbefbbef3,0xbdfcbdd8,0xbe86be7a,0xbecabec2,0xbf05bf01,
0xbc6f8000,0xbe06bdee,0xbe7bbe6d,0xbeb6beaf,0xbd33bcef,0xbe23be15,0xbe8cbe85,0xbec4bebd,0xbd95bd6f,0xbe41be32,0xbe9abe93,0xbed2becb,0xbdd1bdb3,0xbe5ebe4f,0xbea8bea1,0xbee0bed9,
0xbc3c8000,0xbdd4bdbc,0xbe47be3b,0xbe91be8c,0xbd0dbcbc,0xbe01bdeb,0xbe5ebe53,0xbe9cbe97,0xbd6bbd3c,0xbe19be0d,0xbe75be6a,0xbea8bea2,0xbda5bd8d,0xbe30be24,0xbe86be80,0xbeb3bead,
0xbc0a8000,0xbd9bbd8a,0xbe12be0a,0xbe56be4e,0xbccfbc8a,0xbdbebdad,0xbe23be1b,0xbe67be5f,0xbd2dbd0a,0xbde0bdcf,0xbe34be2c,0xbe78be70,0xbd72bd4f,0xbe01bdf1,0xbe45be3d,0xbe84be80,
0xbbb08000,0xbd46bd30,0xbdbbbdb0,0xbe09be04,0xbc84bc30,0xbd72bd5c,0xbdd1bdc6,0xbe14be0e,0xbcdcbcb0,0xbd8fbd84,0xbde6bddb,0xbe1fbe19,0xbd1abd04,0xbda5bd9a,0xbdfcbdf1,0xbe2abe24,
0xbb178000,0xbcaabc97,0xbd20bd17,0xbd6bbd62,0xbbe2bb97,0xbccfbcbc,0xbd33bd2a,0xbd7ebd75,0xbc3cbc17,0xbcf5bce2,0xbd46bd3c,0xbd89bd84,0xbc84bc62,0xbd0dbd04,0xbd59bd4f,0xbd92bd8d,
0x3a490000,0x3be23bc9,0x3c563c49,0x3c9d3c97,0x3b173ac9,0x3c0a3bfb,0x3c6f3c62,0x3caa3ca3,0x3b7b3b49,0x3c233c17,0x3c843c7b,0x3cb63cb0,0x3bb03b97,0x3c3c3c30,0x3c913c8a,0x3cc33cbc,
0x3b7b0000,0x3d0d3cfb,0x3d853d7b,0x3dc43dbc,0x3c3c3bfb,0x3d2d3d1d,0x3d953d8d,0x3dd43dcc,0x3c9d3c7b,0x3d4c3d3c,0x3da53d9d,0x3de33ddb,0x3cdc3cbc,0x3d6b3d5c,0x3db43dad,0x3df33deb,
0x3be20000,0x3d7e3d62,0x3df03de2,0x3e303e29,0x3caa3c62,0x3d9b3d8d,0x3e063dfe,0x3e3e3e37,0x3d0d3ce2,0x3db83da9,0x3e143e0d,0x3e4c3e45,0x3d463d2a,0x3dd43dc6,0x3e223e1b,0x3e593e53,
0x3c230000,0x3db83da3,0x3e2d3e23,0x3e7d3e73,0x3cf53ca3,0x3de03dcc,0x3e413e37,0x3e883e83,0x3d4c3d23,0x3e043df4,0x3e553e4b,0x3e923e8d,0x3d8f3d75,0x3e193e0e,0x3e693e5f,0x3e9c3e97,
0x3c560000,0x3df03dd5,0x3e613e54,0x3ea43e9e,0x3d203cd6,0x3e123e05,0x3e7b3e6e,0x3eb13eaa,0x3d853d56,0x3e2d3e20,0x3e8a3e84,0x3ebd3eb7,0x3dbb3da0,0x3e473e3a,0x3e973e91,0x3ec93ec3,
0x3c840000,0x3e143e04,0x3e8a3e82,0x3ec93ec1,0x3d463d04,0x3e343e24,0x3e9a3e92,0x3ed83ed0,0x3da53d84,0x3e553e45,0x3eaa3ea2,0x3ee73edf,0x3de63dc6,0x3e753e65,0x3eb93eb2,0x3ef53eee,
0x3c9d0000,0x3e303e1c,0x3ea43e9b,0x3eec3ee3,0x3d6b3d1d,0x3e563e43,0x3eb63ead,0x3efd3ef5,0x3dc43d9d,0x3e7d3e6a,0x3ec93ec0,0x3f073f03,0x3e093deb,0x3e913e88,0x3edb3ed2,0x3f0f3f0b,
0x3cb60000,0x3e4c3e35,0x3ebd3eb2,0x3f073f02,0x3d893d36,0x3e783e62,0x3ed23ec8,0x3f113f0c,0x3de33db6,0x3e923e87,0x3ee73edc,0x3f1a3f15,0x3e1f3e08,0x3ea83e9d,0x3efb3ef1,0x3f233f1e,
0x3ccf0000,0x3e673e4e,0x3ed63eca,0x3f173f12,0x3d9b3d4f,0x3e8d3e80,0x3eed3ee1,0x3f223f1d,0x3e013dcf,0x3ea53e99,0x3f023ef8,0x3f2b3f27,0x3e343e1b,0x3ebe3eb2,0x3f0d3f07,0x3f353f30,
0x3ce80000,0x3e813e66,0x3eee3ee1,0x3f273f21,0x3dae3d68,0x3e9d3e8f,0x3f033efa,0x3f323f2c,0x3e113de8,0x3eb93eab,0x3f103f0a,0x3f3c3f37,0x3e4a3e2e,0x3ed33ec6,0x3f1b3f16,0x3f453f41,
0x3d010000,0x3e8f3e7f,0x3f023ef7,0x3f353f2f,0x3dc13d81,0x3eae3e9e,0x3f103f09,0x3f403f3b,0x3e203e00,0x3ecc3ebd,0x3f1d3f17,0x3f4a3f45,0x3e603e40,0x3ee93eda,0x3f293f23,0x3f543f4f,
0x3d0d0000,0x3e9c3e8c,0x3f0e3f06,0x3f423f3d,0x3dd43d8d,0x3ebe3ead,0x3f1c3f15,0x3f4e3f48,0x3e303e0d,0x3ede3ece,0x3f2a3f23,0x3f583f53,0x3e753e53,0x3efd3eee,0x3f373f30,0x3f613f5c,
0x3d1a0000,0x3eaa3e98,0x3f193f11,0x3f4f3f49,0x3de63d9a,0x3ece3ebc,0x3f283f20,0x3f593f54,0x3e3f3e19,0x3ef03edf,0x3f363f2f,0x3f633f5e,0x3e853e65,0x3f093f01,0x3f433f3c,0x3f6b3f67,
0x3d260000,0x3eb73ea4,0x3f233f1b,0x3f5a3f54,0x3df93da6,0x3edd3eca,0x3f333f2b,0x3f643f5f,0x3e4f3e26,0x3f013ef0,0x3f413f3a,0x3f6d3f68,0x3e903e77,0x3f133f0a,0x3f4e3f48,0x3f743f70,
0x3d330000,0x3ec43eaf,0x3f2d3f25,0x3f633f5e,0x3e063db3,0x3eed3ed9,0x3f3d3f35,0x3f6d3f68,0x3e5e3e32,0x3f0a3f00,0x3f4b3f44,0x3f743f71,0x3e9a3e85,0x3f1c3f13,0x3f583f52,0x3f7a3f77,
0x3d400000,0x3ed13ebb,0x3f373f2e,0x3f6c3f67,0x3e0f3dbf,0x3efc3ee7,0x3f473f3f,0x3f743f70,0x3e6d3e3f,0x3f123f08,0x3f553f4e,0x3f7a3f77,0x3ea53e8e,0x3f253f1c,0x3f613f5b,0x3f7e3f7c
};
#define DBG_END(z)
#define TS(i)
#define TZ(z, i)

struct Params {
  alignas(64) CUtensorMap x_g1, w1_a, w1_b2, w1_b1, k, v, w1_cs, kvz, h_st, h_st2, w2, h_ld, y_ld, x_ep, out_st, f_ld, y_st;
  const bf16 *x, *shift_k, *ssm_k, *ssm_D, *b1, *b2, *w2p, *w1p;
  bf16* kvZ;
  const uint32_t* tab;
  uint2 *stats, *cs;
  unsigned* flags;
  unsigned zero;
  unsigned char cnt[72];
  uchar4 map[NCTA];
};

constexpr int G1_W = 28672, G1_X = 16384, G1_NST = 4, OFF_X = G1_NST * G1_W;
constexpr int G2_STAGE = G1_W, G2_B = 16384, G2_NST = 6;
constexpr int CS_STAGE = 57344;
constexpr int RING = G1_NST * (G1_W + G1_X);
constexpr int OFF_C = RING;
constexpr int OFF_SR = OFF_C;
constexpr int OFF_DFT = OFF_C, OFF_G = OFF_C + 8192;
constexpr int KV_SLOT = 35 * 256, KV_V = 19 * 256;
constexpr int OFF_KVS = OFF_C + 20480, OFF_KV = OFF_KVS + 4096;
constexpr int OFF_KV4 = OFF_C + 20480 - KV_SLOT;
constexpr int OFF_T0 = K4E % 3 ? OFF_KV : OFF_C + 12288, OFF_T1 = OFF_C + 34816, OFF_T2 = K4E == 2 ? OFF_C + 12288 : K4E == 1 ? OFF_T0 : OFF_C + 20480, OFF_T3 = OFF_X + 57344, OFF_T4 = K4E == 2 ? OFF_T0 : OFF_C + 12288;
constexpr int OFF_Y0 = K4E % 3 ? OFF_KVS : OFF_C + 28672;
constexpr int OFF_XT = OFF_C + (PRE == 2 ? 28672 : 20480), XT_STEP = PRE == 2 ? 10240 : 13312, OFF_YT = OFF_C;
constexpr int OFF_EXT = 224256;
constexpr int OFF_ST1 = OFF_EXT + 3584;
constexpr int OFF_ST2 = OFF_ST1 + 2048;
constexpr int OFF_MISC = OFF_ST2 + 800;
constexpr int OFF_BAR = OFF_MISC + 32;
enum { B_FULL1 = 0  , B_KV = 4  , B_STAT = 6, B_FIRST = 7, B_EMPTY1 = 7  , B_FULL2 = 11  , B_EMPTY2 = 17  , B_G1FREE = 23, B_CX = 24  , B_RD = 29  ,
       B_EPOCH = 34, B_SKEW = 35, B_TAB = 36, B_EP = 37, B_EPY = 38, B_KVS = 39  , B_GO = 42, B_DONE = 43, B_STATFREE = 44, B_HS = 45  ,
       B_KVR = 53, B_LATE = 54, B_DFT = 55, B_HB = 56, B_H1 = 57, B_VD = 58, B_RT = 59, B_KV4 = 60, B_KVC = 61, B_DBG = 62, B_BAD = 63, B_XF = 64, B_COUNT = 66 };
constexpr int OFF_DBG = OFF_BAR + B_COUNT * 8;
constexpr int SMEM_BYTES = OFF_DBG + (DBG_TIME ? 768 : 0);
static_assert(SMEM_BYTES <= 232448, "smem");
static_assert(OFF_XT + XT_STEP + 10240 <= (PRE == 2 ? OFF_ST2 : OFF_EXT) && (PRE != 2 || OFF_T2 + 8192 <= OFF_XT) && OFF_KV + 2 * KV_SLOT <= OFF_EXT && OFF_T1 + 8192 <= OFF_EXT && OFF_T1 >= OFF_KV + KV_SLOT && OFF_T2 + 8192 <= OFF_KV + KV_SLOT && OFF_KV4 % 128 == 0, "layout");
static_assert(OFF_EXT % 1024 == 0 && OFF_XT % 1024 == 0 && XT_STEP % 1024 == 0 && OFF_T1 % 1024 == 0 && 5 * G2_STAGE + 26624 <= OFF_T3 && 3 * CS_STAGE <= RING, "layout");

#define DEV __device__ __forceinline__
#define HD __host__ __device__ constexpr
DEV uint32_t smem_u32(const void* p) { return (uint32_t)__cvta_generic_to_shared(p); }
DEV uint64_t make_desc(uint32_t addr, uint32_t lbo, uint32_t sbo, uint32_t swz) {
  uint64_t d;
  asm volatile("mov.b64 %0, {%1, %2};" : "=l"(d) : "r"(((addr & 0x3FFFF) >> 4) | ((lbo >> 4) << 16)), "r"((sbo >> 4) | (swz << 30)));
  return d;
}
DEV void wg_fence() { asm volatile("wgmma.fence.sync.aligned;" ::: "memory"); }
DEV void wg_commit() { asm volatile("wgmma.commit_group.sync.aligned;" ::: "memory"); }
template <int n> DEV void wg_wait() { asm volatile("wgmma.wait_group.sync.aligned %0;" ::"n"(n) : "memory"); }
DEV void mbar_init(uint32_t bar, int cnt) { asm volatile("mbarrier.init.shared::cta.b64 [%0], %1;" ::"r"(bar), "r"(cnt) : "memory"); }
DEV void mbar_expect(uint32_t bar, int bytes) { asm volatile("mbarrier.arrive.expect_tx.shared::cta.b64 _, [%0], %1;" ::"r"(bar), "r"(bytes) : "memory"); }
DEV void mbar_arrive(uint32_t bar) { asm volatile("mbarrier.arrive.shared::cta.b64 _, [%0];" ::"r"(bar) : "memory"); }
DEV void mbar_wait(uint32_t bar, uint32_t parity) {
  asm volatile("{\n.reg .pred p;\nW: mbarrier.try_wait.parity.shared::cta.b64 p, [%0], %1;\n@p bra X;\nbra W;\nX:\n}" ::"r"(bar), "r"(parity) : "memory");
}
DEV bool mbar_test(uint32_t bar, uint32_t parity) {
  uint32_t r;
  asm volatile("{\n.reg .pred p;\nmbarrier.test_wait.parity.shared::cta.b64 p, [%1], %2;\nselp.u32 %0, 1, 0, p;\n}" : "=r"(r) : "r"(bar), "r"(parity) : "memory");
  return __any_sync(0xffffffffu, r);
}
DEV void mbar_wait_b(uint32_t bar, uint32_t parity) {
  asm volatile("{\n.reg .pred p;\n.reg .u32 i;\nmov.u32 i, 0;\n"
               "W: mbarrier.try_wait.parity.shared::cta.b64 p, [%0], %1;\n@p bra X;\nadd.u32 i, i, 1;\nsetp.lt.u32 p, i, 262144;\n@p bra W;\ntrap;\nX:\n}"
               ::"r"(bar), "r"(parity) : "memory");
}
DEV void clk_wait(int n) {
  if (n) asm volatile("{\n.reg .pred p;\n.reg .u32 a, b;\nmov.u32 a, %%clock;\nW: mov.u32 b, %%clock;\nsub.u32 b, b, a;\nsetp.lt.u32 p, b, %0;\n@p bra W;\n}" ::"r"(n) : "memory");
}
DEV void trap_above(int n, int lim) { asm volatile("{\n.reg .pred p;\nsetp.gt.s32 p, %0, %1;\n@p trap;\n}" ::"r"(n), "r"(lim)); }
DEV unsigned flag_load(const unsigned* p) {
  unsigned v;
  asm volatile("ld.acquire.gpu.global.u32 %0, [%1];" : "=r"(v) : "l"(p) : "memory");
  return v;
}
template <bool BOUNDED> DEV void flag_wait(const unsigned* p, unsigned target) {
#pragma unroll 1
  for (int i = 0; !BOUNDED || i < (1 << 22); i++)
    if ((int)(flag_load(p) - target) >= 0) return;
  __trap();
}
DEV void tag_store(uint2* p, float a, float b, unsigned ep) {
  const unsigned long long v = (unsigned long long)__float_as_uint(a) | ((unsigned long long)((__float_as_uint(b) & ~255u) | (ep & 255u)) << 32);
  asm volatile("st.relaxed.gpu.global.u64 [%0], %1;" ::"l"(p), "l"(v) : "memory");
}
DEV uint2 tag_load(const uint2* p) { uint2 v; asm volatile("{\n.reg .b64 t;\nld.relaxed.gpu.global.b64 t, [%2];\nmov.b64 {%0,%1}, t;\n}" : "=r"(v.x), "=r"(v.y) : "l"(p) : "memory"); return v; }
template <int N> DEV void tag_wait(const uint2* const (&p)[N], uint2 (&v)[N], unsigned ep) {
#pragma unroll 1
  for (;;) {
    unsigned bad = 0;
#pragma unroll
    for (int j = 0; j < N; j++) bad |= v[j].y ^ ep;
    if (!__any_sync(0xffffffffu, (bad & 255u) != 0)) break;
#pragma unroll
    for (int j = 0; j < N; j++) v[j] = tag_load(p[j]);
  }
#pragma unroll
  for (int j = 0; j < N; j++) v[j].y &= ~255u;
}
#define REL 4
DEV void pub_fence(int bit) { if (REL & bit) asm volatile("fence.acq_rel.gpu;" ::: "memory"); }
DEV void flag_add_rlx(unsigned* p, unsigned n) { asm volatile("red.relaxed.gpu.global.add.u32 [%0], %1;" ::"l"(p), "r"(n) : "memory"); }
DEV void fence_async_smem() { asm volatile("fence.proxy.async.shared::cta;" ::: "memory"); }
#define RF 15
DEV void wfence(int bit) { if (!(RF & bit)) fence_async_smem(); }
DEV void rfence(int bit) { if ((RF & bit) && !(RF & 16)) fence_async_smem(); }
DEV void fence_async_global() { asm volatile("fence.proxy.async.global;" ::: "memory"); }
DEV void bar_sync(int id) { asm volatile("bar.sync %0, 128;" ::"r"(id) : "memory"); }
DEV bool elect() {
  uint32_t p;
  asm volatile("{\n.reg .pred p;\nelect.sync _|p, 0xffffffff;\nselp.u32 %0, 1, 0, p;\n}" : "=r"(p));
  return p;
}
DEV void warp_arrive(uint32_t bar) { __syncwarp(); if (elect()) mbar_arrive(bar); }
DEV void bulk_g2s(uint32_t dst, const void* src, int bytes, uint32_t bar) {
  asm volatile("cp.async.bulk.shared::cluster.global.mbarrier::complete_tx::bytes [%0], [%1], %2, [%3];" ::"r"(dst), "l"(src), "r"(bytes), "r"(bar) : "memory");
}
DEV void bulk_s2g(void* dst, uint32_t src, int bytes) { asm volatile("cp.async.bulk.global.shared::cta.bulk_group [%0], [%1], %2;" ::"l"(dst), "r"(src), "r"(bytes) : "memory"); }
DEV void bulk_prefetch(const void* src, int bytes) { asm volatile("cp.async.bulk.prefetch.L2.global [%0], %1;" ::"l"(src), "r"(bytes) : "memory"); }
DEV void tma2d(uint32_t dst, const CUtensorMap* m, int c0, int c1, uint32_t bar) {
  asm volatile("cp.async.bulk.tensor.2d.shared::cluster.global.mbarrier::complete_tx::bytes [%0], [%1, {%3, %4}], [%2];" ::"r"(dst), "l"(m), "r"(bar), "r"(c0), "r"(c1) : "memory");
}
DEV void tma3d(uint32_t dst, const CUtensorMap* m, int c0, int c1, int c2, uint32_t bar) {
  asm volatile("cp.async.bulk.tensor.3d.shared::cluster.global.mbarrier::complete_tx::bytes [%0], [%1, {%3, %4, %5}], [%2];" ::"r"(dst), "l"(m), "r"(bar), "r"(c0), "r"(c1), "r"(c2) : "memory");
}
DEV void tma2d_st(const CUtensorMap* m, int c0, int c1, uint32_t src) {
  asm volatile("cp.async.bulk.tensor.2d.global.shared::cta.bulk_group [%0, {%2, %3}], [%1];" ::"l"(m), "r"(src), "r"(c0), "r"(c1) : "memory");
}
DEV void bulk_commit() { asm volatile("cp.async.bulk.commit_group;" ::: "memory"); }
DEV void bulk_wait_read() { asm volatile("cp.async.bulk.wait_group.read 0;" ::: "memory"); }
DEV void bulk_wait_all() { asm volatile("cp.async.bulk.wait_group 0;" ::: "memory"); }
DEV void prefetch_map(const CUtensorMap* m) { asm volatile("prefetch.tensormap [%0];" ::"l"(m) : "memory"); }
DEV uint32_t lds32(uint32_t a) { uint32_t v; asm volatile("ld.shared.b32 %0, [%1];" : "=r"(v) : "r"(a) : "memory"); return v; }
DEV uint2 lds64(uint32_t a) { uint2 v; asm volatile("ld.shared.v2.b32 {%0,%1}, [%2];" : "=r"(v.x), "=r"(v.y) : "r"(a) : "memory"); return v; }
DEV uint4 lds128(uint32_t a) { uint4 v; asm volatile("ld.shared.v4.b32 {%0,%1,%2,%3}, [%4];" : "=r"(v.x), "=r"(v.y), "=r"(v.z), "=r"(v.w) : "r"(a) : "memory"); return v; }
DEV void sts32(uint32_t a, uint32_t v) { asm volatile("st.shared.b32 [%0], %1;" ::"r"(a), "r"(v) : "memory"); }
DEV void sts128(uint32_t a, uint4 v) { asm volatile("st.shared.v4.b32 [%0], {%1,%2,%3,%4};" ::"r"(a), "r"(v.x), "r"(v.y), "r"(v.z), "r"(v.w) : "memory"); }
DEV void stsm4(uint32_t a, uint32_t r0, uint32_t r1, uint32_t r2, uint32_t r3) { asm volatile("stmatrix.sync.aligned.m8n8.x4.shared.b16 [%0], {%1,%2,%3,%4};" ::"r"(a), "r"(r0), "r"(r1), "r"(r2), "r"(r3) : "memory"); }
DEV void stsm4t(uint32_t a, uint32_t r0, uint32_t r1, uint32_t r2, uint32_t r3) { asm volatile("stmatrix.sync.aligned.m8n8.x4.trans.shared.b16 [%0], {%1,%2,%3,%4};" ::"r"(a), "r"(r0), "r"(r1), "r"(r2), "r"(r3) : "memory"); }
DEV void ldsm4(uint32_t a, uint32_t (&r)[4]) { asm volatile("ldmatrix.sync.aligned.m8n8.x4.shared.b16 {%0,%1,%2,%3}, [%4];" : "=r"(r[0]), "=r"(r[1]), "=r"(r[2]), "=r"(r[3]) : "r"(a) : "memory"); }
DEV void ldsm4t(uint32_t a, uint32_t (&r)[4]) { asm volatile("ldmatrix.sync.aligned.m8n8.x4.trans.shared.b16 {%0,%1,%2,%3}, [%4];" : "=r"(r[0]), "=r"(r[1]), "=r"(r[2]), "=r"(r[3]) : "r"(a) : "memory"); }
DEV uint32_t pack2(float lo, float hi) { uint32_t r; asm("cvt.rn.bf16x2.f32 %0, %1, %2;" : "=r"(r) : "f"(hi), "f"(lo)); return r; }
DEV uint32_t pack2v(float lo, float hi) { uint32_t r; asm volatile("cvt.rn.bf16x2.f32 %0, %1, %2;" : "=r"(r) : "f"(hi), "f"(lo)); return r; }
DEV float faddv(float a, float b) { float r; asm volatile("add.rn.f32 %0, %1, %2;" : "=f"(r) : "f"(a), "f"(b)); return r; }
DEV float blo(uint32_t u) { return __uint_as_float(u << 16); }
DEV float bhi(uint32_t u) { return __uint_as_float(u & 0xffff0000u); }
DEV float rcp_fast(float x) { float y; asm("rcp.approx.ftz.f32 %0, %1;" : "=f"(y) : "f"(x)); return y; }
DEV float tanh_fast(float x) { float y; asm("tanh.approx.f32 %0, %1;" : "=f"(y) : "f"(x)); return y; }
DEV uint32_t htanh2(uint32_t a) { uint32_t r; asm("tanh.approx.bf16x2 %0, %1;" : "=r"(r) : "r"(a)); return r; }
DEV uint32_t hadd2(uint32_t a, uint32_t b) { uint32_t r; asm("add.rn.bf16x2 %0, %1, %2;" : "=r"(r) : "r"(a), "r"(b)); return r; }
DEV uint32_t hadd2v(uint32_t a, uint32_t b) { uint32_t r; asm volatile("add.rn.bf16x2 %0, %1, %2;" : "=r"(r) : "r"(a), "r"(b)); return r; }
DEV uint32_t hmul2(uint32_t a, uint32_t b) { uint32_t r; asm("mul.rn.bf16x2 %0, %1, %2;" : "=r"(r) : "r"(a), "r"(b)); return r; }
DEV uint32_t hfma2(uint32_t a, uint32_t b, uint32_t c) { uint32_t r; asm("fma.rn.bf16x2 %0, %1, %2, %3;" : "=r"(r) : "r"(a), "r"(b), "r"(c)); return r; }
DEV uint32_t hfma2v(uint32_t a, uint32_t b, uint32_t c) { uint32_t r; asm volatile("fma.rn.bf16x2 %0, %1, %2, %3;" : "=r"(r) : "r"(a), "r"(b), "r"(c)); return r; }
DEV uint32_t hfms2(uint32_t a, uint32_t b, uint32_t c) { uint32_t r; asm("{\n.reg .b32 t;\nmul.bf16x2 t, %1, %2;\nsub.bf16x2 %0, %3, t;\n}" : "=r"(r) : "r"(a), "r"(b), "r"(c)); return r; }
DEV uint4 ldg128(const void* p) { uint4 v; asm volatile("ld.global.nc.v4.b32 {%0,%1,%2,%3}, [%4];" : "=r"(v.x), "=r"(v.y), "=r"(v.z), "=r"(v.w) : "l"(p)); return v; }
DEV uint32_t ldg32(const void* p) { uint32_t v; asm volatile("ld.global.nc.b32 %0, [%1];" : "=r"(v) : "l"(p)); return v; }
DEV float ldg_bf16(const bf16* p) { unsigned short v; asm volatile("ld.global.nc.u16 %0, [%1];" : "=h"(v) : "l"(p)); return __uint_as_float((uint32_t)v << 16); }
DEV float bf_round(float v) { return __bfloat162float(__float2bfloat16(v)); }
DEV uint32_t gelu2(float a, float b, float c1, float c2) {
  const uint32_t p = pack2(a, b);
  return hfma2(p, htanh2(hmul2(p, hfma2(hmul2(p, p), __float_as_uint(c2), __float_as_uint(c1)))), p);
}

DEV void wgmma_ssp_80_10(float* d, uint64_t da, uint64_t db, int keep) {
  asm volatile("{\n.reg .pred p;\nsetp.ne.b32 p, %42, 0;\nwgmma.mma_async.sync.aligned.m64n80k16.f32.bf16.bf16 {%0, %1, %2, %3, %4, %5, %6, %7, %8, %9, %10, %11, %12, %13, %14, %15, %16, %17, %18, %19, %20, %21, %22, %23, %24, %25, %26, %27, %28, %29, %30, %31, %32, %33, %34, %35, %36, %37, %38, %39}, %40, %41, p, 1, 1, 1, 0;\n}\n"
    : "+f"(d[0]), "+f"(d[1]), "+f"(d[2]), "+f"(d[3]), "+f"(d[4]), "+f"(d[5]), "+f"(d[6]), "+f"(d[7]), "+f"(d[8]), "+f"(d[9]), "+f"(d[10]), "+f"(d[11]), "+f"(d[12]), "+f"(d[13]), "+f"(d[14]), "+f"(d[15]), "+f"(d[16]), "+f"(d[17]), "+f"(d[18]), "+f"(d[19]), "+f"(d[20]), "+f"(d[21]), "+f"(d[22]), "+f"(d[23]), "+f"(d[24]), "+f"(d[25]), "+f"(d[26]), "+f"(d[27]), "+f"(d[28]), "+f"(d[29]), "+f"(d[30]), "+f"(d[31]), "+f"(d[32]), "+f"(d[33]), "+f"(d[34]), "+f"(d[35]), "+f"(d[36]), "+f"(d[37]), "+f"(d[38]), "+f"(d[39])
    : "l"(da), "l"(db), "r"(keep));
}
DEV void wgmma_ss_128_01(float* d, uint64_t da, uint64_t db) {
  asm volatile("{\n.reg .pred p;\nsetp.ne.b32 p, 1, 0;\nwgmma.mma_async.sync.aligned.m64n128k16.f32.bf16.bf16 {%0, %1, %2, %3, %4, %5, %6, %7, %8, %9, %10, %11, %12, %13, %14, %15, %16, %17, %18, %19, %20, %21, %22, %23, %24, %25, %26, %27, %28, %29, %30, %31, %32, %33, %34, %35, %36, %37, %38, %39, %40, %41, %42, %43, %44, %45, %46, %47, %48, %49, %50, %51, %52, %53, %54, %55, %56, %57, %58, %59, %60, %61, %62, %63}, %64, %65, p, 1, 1, 0, 1;\n}\n"
    : "+f"(d[0]), "+f"(d[1]), "+f"(d[2]), "+f"(d[3]), "+f"(d[4]), "+f"(d[5]), "+f"(d[6]), "+f"(d[7]), "+f"(d[8]), "+f"(d[9]), "+f"(d[10]), "+f"(d[11]), "+f"(d[12]), "+f"(d[13]), "+f"(d[14]), "+f"(d[15]), "+f"(d[16]), "+f"(d[17]), "+f"(d[18]), "+f"(d[19]), "+f"(d[20]), "+f"(d[21]), "+f"(d[22]), "+f"(d[23]), "+f"(d[24]), "+f"(d[25]), "+f"(d[26]), "+f"(d[27]), "+f"(d[28]), "+f"(d[29]), "+f"(d[30]), "+f"(d[31]), "+f"(d[32]), "+f"(d[33]), "+f"(d[34]), "+f"(d[35]), "+f"(d[36]), "+f"(d[37]), "+f"(d[38]), "+f"(d[39]), "+f"(d[40]), "+f"(d[41]), "+f"(d[42]), "+f"(d[43]), "+f"(d[44]), "+f"(d[45]), "+f"(d[46]), "+f"(d[47]), "+f"(d[48]), "+f"(d[49]), "+f"(d[50]), "+f"(d[51]), "+f"(d[52]), "+f"(d[53]), "+f"(d[54]), "+f"(d[55]), "+f"(d[56]), "+f"(d[57]), "+f"(d[58]), "+f"(d[59]), "+f"(d[60]), "+f"(d[61]), "+f"(d[62]), "+f"(d[63])
    : "l"(da), "l"(db));
}
DEV void wgmma_ss_96_01(float* d, uint64_t da, uint64_t db) {
  asm volatile("{\n.reg .pred p;\nsetp.ne.b32 p, 1, 0;\nwgmma.mma_async.sync.aligned.m64n96k16.f32.bf16.bf16 {%0, %1, %2, %3, %4, %5, %6, %7, %8, %9, %10, %11, %12, %13, %14, %15, %16, %17, %18, %19, %20, %21, %22, %23, %24, %25, %26, %27, %28, %29, %30, %31, %32, %33, %34, %35, %36, %37, %38, %39, %40, %41, %42, %43, %44, %45, %46, %47}, %48, %49, p, 1, 1, 0, 1;\n}\n"
    : "+f"(d[0]), "+f"(d[1]), "+f"(d[2]), "+f"(d[3]), "+f"(d[4]), "+f"(d[5]), "+f"(d[6]), "+f"(d[7]), "+f"(d[8]), "+f"(d[9]), "+f"(d[10]), "+f"(d[11]), "+f"(d[12]), "+f"(d[13]), "+f"(d[14]), "+f"(d[15]), "+f"(d[16]), "+f"(d[17]), "+f"(d[18]), "+f"(d[19]), "+f"(d[20]), "+f"(d[21]), "+f"(d[22]), "+f"(d[23]), "+f"(d[24]), "+f"(d[25]), "+f"(d[26]), "+f"(d[27]), "+f"(d[28]), "+f"(d[29]), "+f"(d[30]), "+f"(d[31]), "+f"(d[32]), "+f"(d[33]), "+f"(d[34]), "+f"(d[35]), "+f"(d[36]), "+f"(d[37]), "+f"(d[38]), "+f"(d[39]), "+f"(d[40]), "+f"(d[41]), "+f"(d[42]), "+f"(d[43]), "+f"(d[44]), "+f"(d[45]), "+f"(d[46]), "+f"(d[47])
    : "l"(da), "l"(db));
}
DEV void wgmma_ss_80_10(float* d, uint64_t da, uint64_t db) {
  asm volatile("{\n.reg .pred p;\nsetp.ne.b32 p, 1, 0;\nwgmma.mma_async.sync.aligned.m64n80k16.f32.bf16.bf16 {%0, %1, %2, %3, %4, %5, %6, %7, %8, %9, %10, %11, %12, %13, %14, %15, %16, %17, %18, %19, %20, %21, %22, %23, %24, %25, %26, %27, %28, %29, %30, %31, %32, %33, %34, %35, %36, %37, %38, %39}, %40, %41, p, 1, 1, 1, 0;\n}\n"
    : "+f"(d[0]), "+f"(d[1]), "+f"(d[2]), "+f"(d[3]), "+f"(d[4]), "+f"(d[5]), "+f"(d[6]), "+f"(d[7]), "+f"(d[8]), "+f"(d[9]), "+f"(d[10]), "+f"(d[11]), "+f"(d[12]), "+f"(d[13]), "+f"(d[14]), "+f"(d[15]), "+f"(d[16]), "+f"(d[17]), "+f"(d[18]), "+f"(d[19]), "+f"(d[20]), "+f"(d[21]), "+f"(d[22]), "+f"(d[23]), "+f"(d[24]), "+f"(d[25]), "+f"(d[26]), "+f"(d[27]), "+f"(d[28]), "+f"(d[29]), "+f"(d[30]), "+f"(d[31]), "+f"(d[32]), "+f"(d[33]), "+f"(d[34]), "+f"(d[35]), "+f"(d[36]), "+f"(d[37]), "+f"(d[38]), "+f"(d[39])
    : "l"(da), "l"(db));
}
DEV void wgmma_ss_8_10(float* d, uint64_t da, uint64_t db) {
  asm volatile("{\n.reg .pred p;\nsetp.ne.b32 p, 1, 0;\nwgmma.mma_async.sync.aligned.m64n8k16.f32.bf16.bf16 {%0, %1, %2, %3}, %4, %5, p, 1, 1, 1, 0;\n}\n"
    : "+f"(d[0]), "+f"(d[1]), "+f"(d[2]), "+f"(d[3])
    : "l"(da), "l"(db));
}
DEV void wgmma_ss_32_10(float* d, uint64_t da, uint64_t db) {
  asm volatile("{\n.reg .pred p;\nsetp.ne.b32 p, 1, 0;\nwgmma.mma_async.sync.aligned.m64n32k16.f32.bf16.bf16 {%0, %1, %2, %3, %4, %5, %6, %7, %8, %9, %10, %11, %12, %13, %14, %15}, %16, %17, p, 1, 1, 1, 0;\n}\n"
    : "+f"(d[0]), "+f"(d[1]), "+f"(d[2]), "+f"(d[3]), "+f"(d[4]), "+f"(d[5]), "+f"(d[6]), "+f"(d[7]), "+f"(d[8]), "+f"(d[9]), "+f"(d[10]), "+f"(d[11]), "+f"(d[12]), "+f"(d[13]), "+f"(d[14]), "+f"(d[15])
    : "l"(da), "l"(db));
}
DEV void wgmma_ssz_32_10(float* d, uint64_t da, uint64_t db) {
  asm volatile("{\n.reg .pred p;\nsetp.ne.b32 p, 0, 0;\nwgmma.mma_async.sync.aligned.m64n32k16.f32.bf16.bf16 {%0, %1, %2, %3, %4, %5, %6, %7, %8, %9, %10, %11, %12, %13, %14, %15}, %16, %17, p, 1, 1, 1, 0;\n}\n"
    : "=f"(d[0]), "=f"(d[1]), "=f"(d[2]), "=f"(d[3]), "=f"(d[4]), "=f"(d[5]), "=f"(d[6]), "=f"(d[7]), "=f"(d[8]), "=f"(d[9]), "=f"(d[10]), "=f"(d[11]), "=f"(d[12]), "=f"(d[13]), "=f"(d[14]), "=f"(d[15])
    : "l"(da), "l"(db));
}
DEV void wgmma_rs_64_0(float* d, const uint32_t* a, uint64_t db) {
  asm volatile("{\n.reg .pred p;\nsetp.ne.b32 p, 1, 0;\nwgmma.mma_async.sync.aligned.m64n64k16.f32.bf16.bf16 {%0, %1, %2, %3, %4, %5, %6, %7, %8, %9, %10, %11, %12, %13, %14, %15, %16, %17, %18, %19, %20, %21, %22, %23, %24, %25, %26, %27, %28, %29, %30, %31}, {%32, %33, %34, %35}, %36, p, 1, 1, 0;\n}\n"
    : "+f"(d[0]), "+f"(d[1]), "+f"(d[2]), "+f"(d[3]), "+f"(d[4]), "+f"(d[5]), "+f"(d[6]), "+f"(d[7]), "+f"(d[8]), "+f"(d[9]), "+f"(d[10]), "+f"(d[11]), "+f"(d[12]), "+f"(d[13]), "+f"(d[14]), "+f"(d[15]), "+f"(d[16]), "+f"(d[17]), "+f"(d[18]), "+f"(d[19]), "+f"(d[20]), "+f"(d[21]), "+f"(d[22]), "+f"(d[23]), "+f"(d[24]), "+f"(d[25]), "+f"(d[26]), "+f"(d[27]), "+f"(d[28]), "+f"(d[29]), "+f"(d[30]), "+f"(d[31])
    : "r"(a[0]), "r"(a[1]), "r"(a[2]), "r"(a[3]), "l"(db));
}
DEV void wgmma_rsz_64_0(float* d, const uint32_t* a, uint64_t db) {
  asm volatile("{\n.reg .pred p;\nsetp.ne.b32 p, 0, 0;\nwgmma.mma_async.sync.aligned.m64n64k16.f32.bf16.bf16 {%0, %1, %2, %3, %4, %5, %6, %7, %8, %9, %10, %11, %12, %13, %14, %15, %16, %17, %18, %19, %20, %21, %22, %23, %24, %25, %26, %27, %28, %29, %30, %31}, {%32, %33, %34, %35}, %36, p, 1, 1, 0;\n}\n"
    : "=f"(d[0]), "=f"(d[1]), "=f"(d[2]), "=f"(d[3]), "=f"(d[4]), "=f"(d[5]), "=f"(d[6]), "=f"(d[7]), "=f"(d[8]), "=f"(d[9]), "=f"(d[10]), "=f"(d[11]), "=f"(d[12]), "=f"(d[13]), "=f"(d[14]), "=f"(d[15]), "=f"(d[16]), "=f"(d[17]), "=f"(d[18]), "=f"(d[19]), "=f"(d[20]), "=f"(d[21]), "=f"(d[22]), "=f"(d[23]), "=f"(d[24]), "=f"(d[25]), "=f"(d[26]), "=f"(d[27]), "=f"(d[28]), "=f"(d[29]), "=f"(d[30]), "=f"(d[31])
    : "r"(a[0]), "r"(a[1]), "r"(a[2]), "r"(a[3]), "l"(db));
}
DEV void wgmma_rs_64_1(float* d, const uint32_t* a, uint64_t db) {
  asm volatile("{\n.reg .pred p;\nsetp.ne.b32 p, 1, 0;\nwgmma.mma_async.sync.aligned.m64n64k16.f32.bf16.bf16 {%0, %1, %2, %3, %4, %5, %6, %7, %8, %9, %10, %11, %12, %13, %14, %15, %16, %17, %18, %19, %20, %21, %22, %23, %24, %25, %26, %27, %28, %29, %30, %31}, {%32, %33, %34, %35}, %36, p, 1, 1, 1;\n}\n"
    : "+f"(d[0]), "+f"(d[1]), "+f"(d[2]), "+f"(d[3]), "+f"(d[4]), "+f"(d[5]), "+f"(d[6]), "+f"(d[7]), "+f"(d[8]), "+f"(d[9]), "+f"(d[10]), "+f"(d[11]), "+f"(d[12]), "+f"(d[13]), "+f"(d[14]), "+f"(d[15]), "+f"(d[16]), "+f"(d[17]), "+f"(d[18]), "+f"(d[19]), "+f"(d[20]), "+f"(d[21]), "+f"(d[22]), "+f"(d[23]), "+f"(d[24]), "+f"(d[25]), "+f"(d[26]), "+f"(d[27]), "+f"(d[28]), "+f"(d[29]), "+f"(d[30]), "+f"(d[31])
    : "r"(a[0]), "r"(a[1]), "r"(a[2]), "r"(a[3]), "l"(db));
}
DEV void wgmma_rsz_64_1(float* d, const uint32_t* a, uint64_t db) {
  asm volatile("{\n.reg .pred p;\nsetp.ne.b32 p, 0, 0;\nwgmma.mma_async.sync.aligned.m64n64k16.f32.bf16.bf16 {%0, %1, %2, %3, %4, %5, %6, %7, %8, %9, %10, %11, %12, %13, %14, %15, %16, %17, %18, %19, %20, %21, %22, %23, %24, %25, %26, %27, %28, %29, %30, %31}, {%32, %33, %34, %35}, %36, p, 1, 1, 1;\n}\n"
    : "=f"(d[0]), "=f"(d[1]), "=f"(d[2]), "=f"(d[3]), "=f"(d[4]), "=f"(d[5]), "=f"(d[6]), "=f"(d[7]), "=f"(d[8]), "=f"(d[9]), "=f"(d[10]), "=f"(d[11]), "=f"(d[12]), "=f"(d[13]), "=f"(d[14]), "=f"(d[15]), "=f"(d[16]), "=f"(d[17]), "=f"(d[18]), "=f"(d[19]), "=f"(d[20]), "=f"(d[21]), "=f"(d[22]), "=f"(d[23]), "=f"(d[24]), "=f"(d[25]), "=f"(d[26]), "=f"(d[27]), "=f"(d[28]), "=f"(d[29]), "=f"(d[30]), "=f"(d[31])
    : "r"(a[0]), "r"(a[1]), "r"(a[2]), "r"(a[3]), "l"(db));
}
DEV void wgmma_rs_128_1(float* d, const uint32_t* a, uint64_t db) {
  asm volatile("{\n.reg .pred p;\nsetp.ne.b32 p, 1, 0;\nwgmma.mma_async.sync.aligned.m64n128k16.f32.bf16.bf16 {%0, %1, %2, %3, %4, %5, %6, %7, %8, %9, %10, %11, %12, %13, %14, %15, %16, %17, %18, %19, %20, %21, %22, %23, %24, %25, %26, %27, %28, %29, %30, %31, %32, %33, %34, %35, %36, %37, %38, %39, %40, %41, %42, %43, %44, %45, %46, %47, %48, %49, %50, %51, %52, %53, %54, %55, %56, %57, %58, %59, %60, %61, %62, %63}, {%64, %65, %66, %67}, %68, p, 1, 1, 1;\n}\n"
    : "+f"(d[0]), "+f"(d[1]), "+f"(d[2]), "+f"(d[3]), "+f"(d[4]), "+f"(d[5]), "+f"(d[6]), "+f"(d[7]), "+f"(d[8]), "+f"(d[9]), "+f"(d[10]), "+f"(d[11]), "+f"(d[12]), "+f"(d[13]), "+f"(d[14]), "+f"(d[15]), "+f"(d[16]), "+f"(d[17]), "+f"(d[18]), "+f"(d[19]), "+f"(d[20]), "+f"(d[21]), "+f"(d[22]), "+f"(d[23]), "+f"(d[24]), "+f"(d[25]), "+f"(d[26]), "+f"(d[27]), "+f"(d[28]), "+f"(d[29]), "+f"(d[30]), "+f"(d[31]), "+f"(d[32]), "+f"(d[33]), "+f"(d[34]), "+f"(d[35]), "+f"(d[36]), "+f"(d[37]), "+f"(d[38]), "+f"(d[39]), "+f"(d[40]), "+f"(d[41]), "+f"(d[42]), "+f"(d[43]), "+f"(d[44]), "+f"(d[45]), "+f"(d[46]), "+f"(d[47]), "+f"(d[48]), "+f"(d[49]), "+f"(d[50]), "+f"(d[51]), "+f"(d[52]), "+f"(d[53]), "+f"(d[54]), "+f"(d[55]), "+f"(d[56]), "+f"(d[57]), "+f"(d[58]), "+f"(d[59]), "+f"(d[60]), "+f"(d[61]), "+f"(d[62]), "+f"(d[63])
    : "r"(a[0]), "r"(a[1]), "r"(a[2]), "r"(a[3]), "l"(db));
}
DEV void wgmma_rs_96_1(float* d, const uint32_t* a, uint64_t db) {
  asm volatile("{\n.reg .pred p;\nsetp.ne.b32 p, 1, 0;\nwgmma.mma_async.sync.aligned.m64n96k16.f32.bf16.bf16 {%0, %1, %2, %3, %4, %5, %6, %7, %8, %9, %10, %11, %12, %13, %14, %15, %16, %17, %18, %19, %20, %21, %22, %23, %24, %25, %26, %27, %28, %29, %30, %31, %32, %33, %34, %35, %36, %37, %38, %39, %40, %41, %42, %43, %44, %45, %46, %47}, {%48, %49, %50, %51}, %52, p, 1, 1, 1;\n}\n"
    : "+f"(d[0]), "+f"(d[1]), "+f"(d[2]), "+f"(d[3]), "+f"(d[4]), "+f"(d[5]), "+f"(d[6]), "+f"(d[7]), "+f"(d[8]), "+f"(d[9]), "+f"(d[10]), "+f"(d[11]), "+f"(d[12]), "+f"(d[13]), "+f"(d[14]), "+f"(d[15]), "+f"(d[16]), "+f"(d[17]), "+f"(d[18]), "+f"(d[19]), "+f"(d[20]), "+f"(d[21]), "+f"(d[22]), "+f"(d[23]), "+f"(d[24]), "+f"(d[25]), "+f"(d[26]), "+f"(d[27]), "+f"(d[28]), "+f"(d[29]), "+f"(d[30]), "+f"(d[31]), "+f"(d[32]), "+f"(d[33]), "+f"(d[34]), "+f"(d[35]), "+f"(d[36]), "+f"(d[37]), "+f"(d[38]), "+f"(d[39]), "+f"(d[40]), "+f"(d[41]), "+f"(d[42]), "+f"(d[43]), "+f"(d[44]), "+f"(d[45]), "+f"(d[46]), "+f"(d[47])
    : "r"(a[0]), "r"(a[1]), "r"(a[2]), "r"(a[3]), "l"(db));
}

struct Dft { uint32_t E[8], tt[8], ts[8]; };
DEV void dft_load(Dft& k, const uint32_t* tab, int tid) {
#pragma unroll
  for (int q = 0; q < 6; q++) {
    const uint4 v = ldg128(tab + 3072 + 512 * q + 4 * tid);
    uint32_t* d = (q < 2 ? k.E : q < 4 ? k.tt : k.ts) + 4 * (q & 1);
    d[0] = v.x; d[1] = v.y; d[2] = v.z; d[3] = v.w;
  }
}
template <int SG> DEV void rotate(const float* d, const Dft& k, uint32_t* o) {
#pragma unroll
  for (int j = 0; j < 8; j++) {
    const uint32_t re = pack2(d[4 * j], d[4 * j + 1]), im = pack2(d[4 * j + 2], d[4 * j + 3]);
    uint32_t a, b;
    if (SG > 0) { a = hfms2(k.tt[j], im, re); b = hfma2(k.ts[j], a, im); a = hfms2(k.tt[j], b, a); }
    else { a = hfma2(k.tt[j], im, re); b = hfms2(k.ts[j], a, im); a = hfma2(k.tt[j], b, a); }
    o[2 * j] = a; o[2 * j + 1] = b;
  }
}
DEV void dft64(float* d, const uint32_t* a, uint64_t db) {
  wgmma_rsz_64_1(d, a, db);
#pragma unroll
  for (int kk = 1; kk < 4; kk++) wgmma_rs_64_1(d, a + 4 * kk, db + kk * (2048 >> 4));
}
DEV bool conv(const Dft& k, uint32_t sb, uint32_t t, uint32_t ty, float dv, int bar, int w, int lane, unsigned* go, uint32_t ep, uint32_t zero) {
  const uint32_t tag = KVCHK ? lds32(t + 1024 * w + 32 * lane + 4 * (lane & 4)) : ep;
  dv = __uint_as_float(__float_as_uint(dv) | (tag & zero));
  float dh[32], dx[32];
  uint32_t ah[16], ax[16];
  const uint64_t cs = make_desc(sb + OFF_DFT, 16, 1024, 1), bh = make_desc(t + 4096, 16, 1024, 1), bx = make_desc(t, 1024, 256, 3);
  wg_fence();
  wgmma_rsz_64_1(dh, k.E, bh); wgmma_rs_64_1(dh, k.E + 4, bh + (2048 >> 4)); wg_commit();
  wgmma_rsz_64_1(dx, k.E, bx); wgmma_rs_64_1(dx, k.E + 4, bx + (512 >> 4)); wg_commit();
  wg_wait<1>();
  dh[0] = fmaf(dv, blo(k.E[0]), dh[0]); dh[2] = fmaf(dv, blo(k.E[1]), dh[2]);
  rotate<1>(dh, k, ah);
  wg_fence(); dft64(dh, ah, cs); wg_commit();
  if (GO_AT == 1 && go) flag_add_rlx(go, 1);
  wg_wait<1>();
  rotate<1>(dx, k, ax);
  wg_fence(); dft64(dx, ax, cs); wg_commit();
  wg_wait<1>();
#pragma unroll
  for (int j = 0; j < 8; j++) { ah[2 * j] = pack2(dh[4 * j], dh[4 * j + 1]); ah[2 * j + 1] = pack2(dh[4 * j + 2], dh[4 * j + 3]); }
  wg_wait<0>();
#pragma unroll
  for (int j = 0; j < 4; j++) {
    const uint32_t pr = pack2(dx[4 * j], dx[4 * j + 1]), pi = pack2(dx[4 * j + 2], dx[4 * j + 3]);
    const uint32_t qr = pack2(dx[16 + 4 * j], dx[17 + 4 * j]), qi = pack2(dx[18 + 4 * j], dx[19 + 4 * j]);
    const uint32_t rr = ah[2 * j], ri = ah[2 * j + 1], sr = ah[8 + 2 * j], si = ah[9 + 2 * j];
    ax[2 * j] = hfma2(qi, si, hfms2(qr, sr, hfms2(pi, ri, hmul2(pr, rr))));
    ax[2 * j + 1] = hfms2(qi, sr, hfms2(qr, si, hfma2(pi, rr, hmul2(pr, ri))));
    ax[8 + 2 * j] = hfms2(qi, ri, hfma2(qr, rr, hfms2(pi, si, hmul2(pr, sr))));
    ax[9 + 2 * j] = hfma2(qi, rr, hfma2(qr, ri, hfma2(pi, sr, hmul2(pr, si))));
  }
  wg_fence();
  wgmma_rsz_64_0(dx, ax, cs);
#pragma unroll
  for (int kk = 1; kk < 4; kk++) wgmma_rs_64_0(dx, ax + 4 * kk, cs + 2 * kk);
  wg_commit();
  if (GO_AT == 2 && go) flag_add_rlx(go, 1);
  wg_wait<0>();
  rotate<-1>(dx, k, ah);
  const int m = lane >> 3, i = lane & 7;
  const uint32_t za = t + (16 * w + 8 * (m & 1) + i) * 128;
#pragma unroll
  for (int q = 0; q < 4; q++) stsm4(za + (((2 * q + (m >> 1)) ^ i) << 4), ah[4 * q], ah[4 * q + 1], ah[4 * q + 2], ah[4 * q + 3]);
  fence_async_smem();
  uint32_t ok;
  asm volatile("{\n.reg .pred p, q;\nsetp.eq.u32 p, %1, 0;\nbarrier.red.and.aligned.pred q, %2, 128, p;\nselp.u32 %0, 1, 0, q;\n}" : "=r"(ok) : "r"((tag ^ ep) & 1), "r"(bar) : "memory");
  const uint64_t da = make_desc(t, 16, 1024, 1), db = make_desc(sb + OFF_G, 16, 1024, 1);
  if (K4E) mbar_wait(sb + OFF_BAR + 8 * B_KVC, 0);
  wg_fence();
  wgmma_ssz_32_10(dh, da, db);
#pragma unroll
  for (int kk = 1; kk < 4; kk++) wgmma_ss_32_10(dh, da + kk * (2048 >> 4), db + 2 * kk);
  wg_commit();
  if (GO_AT == 3 && go) flag_add_rlx(go, 1);
  wg_wait<0>();
  if (!K4E) mbar_wait(sb + OFF_BAR + 8 * B_KVC, 0);
  const uint32_t ya = ty + (8 * (m >> 1) + i) * 128 + (((2 * w + (m & 1)) ^ i) << 4);
#pragma unroll
  for (int q = 0; q < 2; q++)
    stsm4t(ya + q * 2048, pack2(dh[8 * q], dh[8 * q + 1]), pack2(dh[8 * q + 2], dh[8 * q + 3]), pack2(dh[8 * q + 4], dh[8 * q + 5]), pack2(dh[8 * q + 6], dh[8 * q + 7]));
  wfence(4);
  return !KVCHK || __all_sync(0xffffffffu, ok);
}

DEV void g1_issue(const Params& P, uint32_t sb, int s, uint32_t fb, int kb, int rb, int fs) {
  const uint32_t st = sb + s * G1_W;
  mbar_expect(fb, G1_W + G1_X);
  tma2d(sb + OFF_X + s * G1_X, &P.x_g1, 64 * kb, 128 * rb, fb);
  tma3d(st, &P.w1_a, 0, 64 * kb, 3 * fs, fb);
  tma3d(st + 16384, &P.w1_b2, 0, 64 * kb, 6 * fs + 4, fb);
  tma3d(st + 24576, &P.w1_b1, 0, 64 * kb, 48 + fs, fb);
}
DEV void kv_issue(const Params& P, uint32_t dst, uint32_t bar, int r, int g1) {
  mbar_expect(bar, KV_SLOT);
  tma2d(dst, &P.k, 128 * r, 16 * g1 - 3, bar);
  tma2d(dst + 19 * 256, &P.v, 128 * r, 16 * g1, bar);
}
DEV void h_flag(const Params& P, int rb, int o) {
  const int j0 = (128 * rb) / 80;
  flag_add_rlx(P.flags + FL_H + 32 * (o + j0), 1); flag_add_rlx(P.flags + FL_H + 32 * (o + j0 + 1), 1);
  if (80 * (j0 + 2) < 128 * rb + 128) flag_add_rlx(P.flags + FL_H + 32 * (o + j0 + 2), 1);
}
DEV void h_wait(const Params& P, int tj, int o, unsigned ep) {
  flag_wait<false>(P.flags + FL_H + 32 * (o + tj), ep * (((80 * tj) >> 7) == (min(80 * tj + 79, S_ - 1) >> 7) ? 8 : 16));
  fence_async_global();
}
DEV uint32_t h_tag(uint32_t sb, int tj, int q, int lane) {
  const int r = min(q < 2 ? 32 * q + lane : 64 + (lane & 15), S_ - 1 - 80 * tj);
  return sb + G2_B + r * 128 + ((r & 7) << 4) + 4 * ((2 * tj + (r >> 3)) & 3);
}
DEV uint32_t conv_tile(uint32_t sb, int c) { return sb + (c == 1 ? OFF_T1 : c == 2 ? OFF_T2 : c == 3 ? OFF_T3 : c == 4 ? OFF_T4 : OFF_T0); }
DEV void conv_issue_f(const Params& P, uint32_t t, int ch, uint32_t bar) { mbar_expect(bar, 4096); tma2d(t + 4096, &P.f_ld, 0, 32 * ch, bar); }
DEV void conv_issue_x(const Params& P, uint32_t t, int ch, uint32_t bar) {
  mbar_expect(bar, 4096);
  tma3d(t, &P.kvz, 16 * ((ch & ~63) | ((ch & 3) << 4) | ((ch & 63) >> 2)), 0, 0, bar);
}
HD int h_slot(int j) { return SPLIT9 && j ? 3 - j : j; }
DEV int g2_slot(int s) { return !RM || s < 3 ? s : s == 5 ? 3 : s + 1; }
DEV int g2_block(int i) { return i < 24 ? 3 * (i & 7) + (i >> 3) : i; }
DEV int ext_col(int n, int fs) { return min(n < 192 ? 192 * fs + n : 1344 + 32 * fs + n, F_ - 2); }
DEV uint32_t ext_off(int n, int k) {
  const int m = n - 128;
  return n < 128 ? (n >> 6) * 1024 + k * 128 + ((((n & 63) >> 3) ^ k) << 4) + (n & 7) * 2
                 : 2048 + (m >> 5) * 512 + k * 64 + ((((m & 31) >> 3) ^ (k >> 1)) << 4) + (m & 7) * 2;
}
DEV uint32_t kv_elem(uint32_t k0, uint32_t k1, uint32_t k2, uint32_t k3, const uint32_t (&w)[4], uint32_t v) {
  if (MIM & 2) return hmul2(hadd2(hadd2(hadd2(hmul2(k0, w[3]), hmul2(k1, w[2])), hmul2(k2, w[1])), hmul2(k3, w[0])), v);
  return hmul2(hfma2(k3, w[0], hfma2(k2, w[1], hfma2(k1, w[2], hmul2(k0, w[3])))), v);
}
DEV void kv_store(uint32_t z, const uint32_t (&p)[8]) {
  sts128(z, make_uint4(__byte_perm(p[0], p[1], 0x5410), __byte_perm(p[2], p[3], 0x5410), __byte_perm(p[4], p[5], 0x5410), __byte_perm(p[6], p[7], 0x5410)));
  sts128(z + 512, make_uint4(__byte_perm(p[0], p[1], 0x7632), __byte_perm(p[2], p[3], 0x7632), __byte_perm(p[4], p[5], 0x7632), __byte_perm(p[6], p[7], 0x7632)));
}
DEV void kv_out(const Params& P, uint32_t src, int r, int g1) { bulk_s2g(reinterpret_cast<uint8_t*>(P.kvZ) + g1 * 20480 + r * 4096, src, 4096); }
DEV void tap_split(uint4 q, uint32_t (&w)[4]) {
  w[0] = __byte_perm(q.x, q.z, 0x5410); w[1] = __byte_perm(q.x, q.z, 0x7632); w[2] = __byte_perm(q.y, q.w, 0x5410); w[3] = __byte_perm(q.y, q.w, 0x7632);
}

}

__global__ void __launch_bounds__(512, 1) h3_fused_kernel(const __grid_constant__ Params P) {
  extern __shared__ __align__(1024) uint8_t smem_raw[];
  constexpr uint32_t sb = 1024;
#define BAR(i) (sb + OFF_BAR + 8 * (i))
  const int warp = __shfl_sync(0xffffffffu, threadIdx.x >> 5, 0);
  const int wg = warp >> 2;
  const int tid = threadIdx.x & 127, lane = threadIdx.x & 31;
  uint32_t smid, nsmid;
  asm volatile("mov.u32 %0, %%smid;" : "=r"(smid));
  asm volatile("mov.u32 %0, %%nsmid;" : "=r"(nsmid));
  const uint32_t cta = nsmid == NCTA ? smid : blockIdx.x;
  const uchar4 mp = P.map[cta];
  const int g1 = mp.x, g2 = mp.y;
  const bool has1 = g1 < 128, has2 = g2 != 255;
  const int fs = g1 & 7, rb = g1 >> 3;
  const int tj = g2 >> 3, dt = g2 & 7;

  if (warp != 12) {
    if (elect()) {
      if (smem_u32(smem_raw) != sb) __trap();
#pragma unroll 1
      for (int b = B_FIRST + warp - (warp > 12); b < B_COUNT; b += 15) mbar_init(BAR(b), P.cnt[b]);
      fence_async_smem();
    }
    __syncwarp();
    asm volatile("bar.arrive 7, 512;" ::: "memory");
    asm volatile("bar.sync 0, 512;" ::: "memory");
  }

  if (wg < 3) {
    const int w4 = warp & 3, g = lane >> 2, c = lane & 3;
    asm volatile("setmaxnreg.inc.sync.aligned.u32 %0;" ::"n"(R_G));
    Dft dft;
    uint32_t ep, dq[3];
    auto misc_load = [&]() {
      const int l = wg == 0 ? CH_W0 : wg == 1 ? CH_W1 : CH_W2;
      ep = lds32(sb + OFF_MISC);
#pragma unroll
      for (int j = 0; j < 3; j++) dq[j] = lds32(sb + OFF_MISC + 4 + 4 * ((l >> (4 * j)) & 7));
    };
    if (wg < 2) {
      if (has1) {
        float acc[112];
        const uint64_t da0 = make_desc(sb + OFF_X + wg * 8192, 16, 1024, 1), db0 = make_desc(sb, 8192, 1024, 1), dc0 = make_desc(sb + 16384, 4096, 512, 2);
        const bool lead = tid == 0;
#pragma unroll
        for (int i = 0; i < 112; i++) acc[i] = 0.f;
        auto block = [&](int kb) {
          const int s = kb & 3;
          const uint64_t o = s * (G1_W >> 4), da = da0 + s * (G1_X >> 4), db = db0 + o, dc = dc0 + o;
          mbar_wait(BAR(B_FULL1 + s), (kb >> 2) & 1);
          TZ(tid, 64 + 10 * wg + kb);
          wg_fence();
#pragma unroll
          for (int kk = 0; kk < 4; kk++) {
            wgmma_ss_128_01(acc, da + 2 * kk, db + kk * (2048 >> 4));
            wgmma_ss_96_01(acc + 64, da + 2 * kk, dc + kk * (1024 >> 4));
            if (kk == EREL - 1) {
              wg_commit(); wg_wait<1>();
              if (lead && kb && kb < 7) mbar_arrive(BAR(B_EMPTY1 + ((kb - 1) & 3)));
            }
          }
          wg_commit();
        };
#pragma unroll 1
        for (int kb = 0; kb < 10 - SPLIT9; kb++) {
          block(kb);
          if (!EREL && kb < NOW) {
            wg_wait<1>();
            if (lead && kb && kb < 7) mbar_arrive(BAR(B_EMPTY1 + ((kb - 1) & 3)));
          }
        }
        TZ(tid | (wg ^ 1), 123);
        mbar_wait(BAR(B_TAB), 0);
        TZ(tid, 8 + wg);
        const uint32_t sa = sb + OFF_ST1 + 16 * (64 * wg + 16 * w4 + g);
        const float r0 = __uint_as_float(lds32(sa + 12)), r1 = __uint_as_float(lds32(sa + 128 + 12));
        {
          uint32_t ax[4];
          ax[0] = lds32(sa + 4 * c); ax[1] = lds32(sa + 128 + 4 * c);
          if (c == 3) { ax[0] = 0; ax[1] = 0; }
          asm volatile("mov.b32 %0, 0;" : "=r"(ax[2])); asm volatile("mov.b32 %0, 0;" : "=r"(ax[3]));
          if (SPLIT9) {
            const uint64_t da = da0 + (G1_X >> 4), db = db0 + (G1_W >> 4), dc = dc0 + (G1_W >> 4);
            wg_fence();
            wgmma_rs_128_1(acc, ax, make_desc(sb + OFF_EXT, 1024, 0, 1));
            wgmma_rs_96_1(acc + 64, ax, make_desc(sb + OFF_EXT + 2048, 512, 0, 2));
            mbar_wait(BAR(B_FULL1 + 1), 0);
            TZ(tid, 64 + 10 * wg + 9);
#pragma unroll
            for (int kk = 0; kk < 4; kk++) wgmma_ss_128_01(acc, da + 2 * kk, db + kk * (2048 >> 4));
            wg_commit();
#pragma unroll
            for (int kk = 0; kk < 4; kk++) wgmma_ss_96_01(acc + 64, da + 2 * kk, dc + kk * (1024 >> 4));
            wg_commit();
          } else {
          wg_fence();
          wgmma_rs_128_1(acc, ax, make_desc(sb + OFF_EXT, 1024, 0, 1));
          wgmma_rs_96_1(acc + 64, ax, make_desc(sb + OFF_EXT + 2048, 512, 0, 2));
          wg_commit();
          }
        }
        constexpr float K1 = 0.7978845608028654f, K2 = 0.7978845608028654f * 0.044715f;
        float c10 = K1 * r0, c11 = K1 * r1, c20 = K2 * r0 * r0 * r0, c21 = K2 * r1 * r1 * r1;
        c10 = __uint_as_float(pack2(c10, c10)); c11 = __uint_as_float(pack2(c11, c11)); c20 = __uint_as_float(pack2(c20, c20)); c21 = __uint_as_float(pack2(c21, c21));
        const int hr = 16 * w4 + ((lane >> 3) & 1) * 8 + (lane & 7);
        const uint32_t hs = sb + OFF_X + wg * 8192 + hr * 128, hx = (lane >> 4) ^ (lane & 7);
        const uint32_t hs2 = sb + OFF_X + 3 * G1_X + wg * 4096 + hr * 64, hx2 = (lane >> 4) ^ ((lane >> 1) & 3);
        if (SPLIT9) wg_wait<1>(); else wg_wait<0>();
        TZ(tid, 2 + wg);
        if (!SPLIT9 && tid < 5) mbar_arrive(BAR(tid < 4 ? B_EMPTY2 + (RM && tid == 3 ? 5 : tid) : B_G1FREE));
        uint32_t zn = 0;
        misc_load();
        const uint32_t par = ep & 1;
#pragma unroll
        for (int i = 0; i < 28; i += 2) {
          if (i == 24) { if (fs >= 6) break; if (wg) mbar_wait(BAR(B_G1FREE), 0); }
          if (i && i % GELU_BF16 == 0) {
            const uint32_t z = LOOKAHEAD ? zn : lds32(sb + OFF_MISC + 24);
            c20 = __uint_as_float(__float_as_uint(c20) + z); c21 = __uint_as_float(__float_as_uint(c21) + z);
          }
          if (LOOKAHEAD && (i + LOOKAHEAD) % GELU_BF16 == 0) zn = lds32(sb + OFF_MISC + 24);
          if (SPLIT9 && i == 16) { wg_wait<0>(); if (tid < 5) mbar_arrive(BAR(tid < 4 ? B_EMPTY2 + tid : B_G1FREE)); }
          if (i == DFT_AT) dft_load(dft, P.tab, tid);
          const float* a = &acc[4 * i];
          uint32_t p0 = gelu2(a[0], a[1], c10, c20), p1 = gelu2(a[2], a[3], c11, c21);
          if (!(i & 7)) { if (c == ((2 * w4) & 3)) p0 = (p0 & ~1u) | par; if (c == ((2 * w4 + 1) & 3)) p1 = (p1 & ~1u) | par; }
          const uint32_t p2 = gelu2(a[4], a[5], c10, c20), p3 = gelu2(a[6], a[7], c11, c21);
          if (i > HS_LAG && !((i - HS_LAG) & 7)) { wfence(2); warp_arrive(BAR(B_HS + 4 * wg + (i >> 3) - 1)); }
          if (i < 24) stsm4(hs + h_slot(i >> 3) * G1_X + ((hx ^ (i & 7)) << 4), p0, p1, p2, p3);
          else stsm4(hs2 + ((hx2 ^ (i & 3)) << 4), p0, p1, p2, p3);
          if ((i == 22 && fs >= 6) || i == 26) { wfence(2); warp_arrive(BAR(B_HS + 4 * wg + (i >> 3))); }
        }
        TZ(tid, 4 + wg);
      } else if (wg == 1) {
        float cs[7][4];
#pragma unroll
        for (int j = 0; j < 7; j++) cs[j][0] = cs[j][1] = cs[j][2] = cs[j][3] = 0.f;
        if (tid < 64) sts32(sb + OFF_EXT + 4 * tid, 0x3f803f80u);
        fence_async_smem();
        bar_sync(4);
        const uint64_t da0 = make_desc(sb, 16, 1024, 1), db = make_desc(sb + OFF_EXT, 128, 128, 0);
        int s = 0, ph = 0;
#pragma unroll 1
        for (int kb = CS_KB; kb < 10; kb++) {
          mbar_wait(BAR(B_FULL1 + s), ph);
          wg_fence();
#pragma unroll 1
          for (int kk = 0; kk < 4; kk++) {
#pragma unroll
            for (int j = 0; j < 7; j++) wgmma_ss_8_10(cs[j], da0 + (s * (CS_STAGE >> 4) + kk * (2048 >> 4)) + j * (8192 >> 4), db);
            wg_commit();
          }
          wg_wait<0>();
          if (tid < 4) mbar_arrive(BAR(B_EMPTY1 + s));
          if (++s == 3) { s = 0; ph ^= 1; }
        }
        mbar_wait(BAR(B_EPOCH), 0);
        ep = lds32(sb + OFF_MISC);
#pragma unroll
        for (int j = 0; j < 7; j++) {
          const float a = (c & 1) ? cs[j][2] : cs[j][0], b = __shfl_down_sync(0xffffffffu, a, 4);
          if (c < 2 && !(g & 1)) tag_store(P.cs + CSP + 32 * (7 * (g1 - 128) + j) + 8 * w4 + 4 * c + (g >> 1), a, b, ep);
        }
        TZ(tid, 24);
        if (tid < 2 * G2_NST + 2 * RM) mbar_arrive(BAR(tid >= 2 * G2_NST ? B_G1FREE : B_EMPTY2 + (tid >> 1)));
      }
    } else {
      if (has1) {
        const bf16* skp = P.shift_k + (128 * (w4 >> 1) + 64 * (w4 & 1) + 4 * (lane & 15)) * 4;
        uint4 tap0 = ldg128(skp), tap1 = ldg128(skp + 8);
        auto stats = [&]() {
        mbar_wait(BAR(B_STAT), 0);
        TZ(tid, 19);
        float sum = 0.f, sq = 0.f;
        const uint32_t sa = sb + OFF_SR + (tid >> 3) * 1280 + 16 * (lane & 7);
        uint4 nq[2] = {lds128(sa), lds128(sa + 128)};
#pragma unroll 1
        for (int z = 0; z < 5; z++) {
          const uint4 xq[2] = {nq[0], nq[1]};
          if (z < 4) { nq[0] = lds128(sa + 256 * z + 256); nq[1] = lds128(sa + 256 * z + 384); }
          else warp_arrive(BAR(B_STATFREE) + ((xq[0].x | xq[1].x) & P.zero));
#pragma unroll
          for (int i = 0; i < 2; i++) {
            const uint32_t u[4] = {xq[i].x, xq[i].y, xq[i].z, xq[i].w};
#pragma unroll
            for (int e = 0; e < 4; e++) { const float a = blo(u[e]), b = bhi(u[e]); sum += a + b; sq = fmaf(a, a, fmaf(b, b, sq)); }
          }
        }
#pragma unroll
        for (int o = 1; o < 8; o *= 2) { sum += __shfl_xor_sync(0xffffffffu, sum, o); sq += __shfl_xor_sync(0xffffffffu, sq, o); }
        const float mean = sum * (1.f / D_), var = fmaxf(fmaf(-mean, mean, sq * (1.f / D_)), 0.f);
        const float ve = bf_round(bf_round(var) + 1e-5f);
        if ((lane & 7) == 0) tag_store(P.stats + 16 * g1 + (tid >> 3), MIM & 1 ? bf_round(mean) : mean, MIM & 1 ? rcp_fast(bf_round(ve * rsqrtf(ve))) : rsqrtf(var + 1e-5f), ep);
        TZ(tid, 22);
        };
        const uint32_t slot = sb + OFF_KV + (w4 >> 1) * KV_SLOT;
        const uint32_t ka = slot + 8 * (lane >> 4) * 256 + 128 * (w4 & 1) + 8 * (lane & 15);
        const uint32_t zo = (64 * (w4 & 1) + (lane & 15)) * 32 + (lane >> 4) * 16;
        if (DFT_EARLY == 2) dft_load(dft, P.tab, tid);
        mbar_wait(BAR(B_EPOCH), 0);
        misc_load();
        const uint32_t hf4 = (lane >> 4) ^ (w4 >> 1);
        const uint32_t tagm = lane < 16 ? 0x00010001u : 0u, tagv = (ep & 1) ? tagm : 0u;
        auto round4 = [&](uint4 tap) {
          uint32_t wa[4], p[8], kk[11];
          tap_split(tap, wa);
          const uint32_t k4 = sb + OFF_KV4 + 8 * (lane >> 4) * 256 + 128 * (w4 & 1) + 8 * (lane & 15) + 4 * hf4;
          mbar_wait(BAR(B_KV4), 0);
          TZ(tid, 62);
#pragma unroll
          for (int j = 0; j < 11; j++) kk[j] = lds32(k4 + j * 256);
#pragma unroll
          for (int j = 0; j < 8; j++) p[j] = lds32(k4 + (19 + j) * 256);
          if (DFT_EARLY == 4) dft_load(dft, P.tab, tid);
#pragma unroll
          for (int j = 0; j < 8; j++) p[j] = kv_elem(kk[j], kk[j + 1], kk[j + 2], kk[j + 3], wa, p[j]);
          bar_sync(3 + ((p[0] | p[1] | p[2] | p[3] | p[4] | p[5] | p[6] | p[7]) & P.zero));
          p[0] = (p[0] & ~tagm) | tagv;
          kv_store(sb + OFF_KV4 + KV_V + zo + 1024 * hf4, p);
          wfence(1);
          warp_arrive(BAR(B_KVS + 2));
        };
        uint4 tap4;
        if (K4E == 3) { tap4 = ldg128(P.shift_k + (512 + 64 * (w4 & 1) + 4 * (lane & 15) + 2 * hf4) * 4); stats(); }
#pragma unroll 1
        for (int r = w4 >> 1; r < (K4E ? 4 : 5); r += 2) {
          uint32_t wa[4], wb[4], p[8], q[8];
          uint2 kk[11];
          tap_split(tap0, wa); tap_split(tap1, wb);
          if (K4E) {
            if (r < 2) { skp += 1024; tap0 = ldg128(skp); tap1 = ldg128(skp + 8); }
            else { if (K4E < 3) tap0 = ldg128(P.shift_k + (512 + 64 * (w4 & 1) + 4 * (lane & 15) + 2 * hf4) * 4); if (DFT_EARLY == 3) dft_load(dft, P.tab, tid); }
          } else {
          if (r < 3) { skp += 1024; tap0 = ldg128(skp); tap1 = ldg128(skp + 8); }
          else if (DFT_EARLY == 3) dft_load(dft, P.tab, tid);
          }
          mbar_wait(BAR(B_KV + (r & 1)), (r >> 1) & 1);
          TZ(tid & 63, 58 + r);
#pragma unroll
          for (int j = 0; j < 11; j++) kk[j] = lds64(ka + j * 256);
#pragma unroll
          for (int j = 0; j < 8; j++) { const uint2 vv = lds64(ka + (19 + j) * 256); p[j] = vv.x; q[j] = vv.y; }
#pragma unroll
          for (int j = 0; j < 8; j++) {
            p[j] = kv_elem(kk[j].x, kk[j + 1].x, kk[j + 2].x, kk[j + 3].x, wa, p[j]);
            q[j] = kv_elem(kk[j].y, kk[j + 1].y, kk[j + 2].y, kk[j + 3].y, wb, q[j]);
          }
          asm volatile("bar.sync %0, 64;" ::"r"(5 + (r & 1) + ((p[0] | p[1] | p[2] | p[3] | p[4] | p[5] | p[6] | p[7]) & P.zero)) : "memory");
          TZ(tid | (r ^ 2) | (DBG_TIME == 2), 10);
          if (r < (K4E ? 2 : 4) && w4 == 0 && elect()) kv_issue(P, slot, BAR(B_KV), r + 2, g1);
          if (r == 2) mbar_wait(BAR(B_KVR), 0);
          TZ(tid | (r ^ 2) | (DBG_TIME == 2), 45);
          const uint32_t z = zo + (r < 4 && w4 < 2 ? sb + OFF_KVS : slot + KV_V);
          p[0] = (p[0] & ~tagm) | tagv; q[0] = (q[0] & ~tagm) | tagv;
          kv_store(z, p); kv_store(z + 1024, q);
          wfence(1);
          warp_arrive(BAR(B_KVS + (r >> 1)));
          TZ(tid | (r ^ 2) | (DBG_TIME == 2), 49);
          if (r < 2) { if (K4E == 3) round4(tap4); else stats(); }
        }
        if (K4E % 3) round4(tap0);
        TZ(tid, 21);
        if (!DFT_EARLY) dft_load(dft, P.tab, tid);
      }
    }

    if (has1) {
      mbar_wait(BAR(B_DFT), 0);
      int tries = 0;
#pragma unroll 1
      for (int l = wg == 0 ? CH_W0 : wg == 1 ? CH_W1 : CH_W2; (l & 15) != 15;) {
        const int i = l & 15;
        const float dv = c == 0 ? __uint_as_float(dq[0]) : 0.f;
        TZ(tid, 31 + 4 * i);
        mbar_wait(BAR(B_CX + i), tries & 1);
        TZ(tid, 30 + 4 * i);
        if (conv(dft, sb, conv_tile(sb, i), i ? conv_tile(sb, i) : sb + OFF_Y0, dv, 1 + wg, w4, lane, tid == 0 && ((GO_WG >> wg) & 1) && (l >> 4) == 15 && !tries ? P.flags + FL_G2 + 32 * mp.z : nullptr, ep, P.zero)) {
          warp_arrive(BAR(B_RD + i));
          l >>= 4; tries = 0; dq[0] = dq[1]; dq[1] = dq[2];
        } else {
          fence_async_smem();
          bar_sync(1 + wg);
          trap_above(++tries, 100000);
          if (tid == 0) { conv_issue_f(P, conv_tile(sb, i), g1 + 128 * i, BAR(B_CX + i)); conv_issue_x(P, conv_tile(sb, i), g1 + 128 * i, BAR(B_CX + i)); }
        }
        TZ(tid, 32 + 4 * i);
      }
    }
    if (!PRE && wg == 2 && has2) {
      const uint2* const ps[1] = {P.stats + min(80 * tj + tid, S_ - 1)};
      uint2 sv[1] = {tag_load(ps[0])};
      mbar_wait(BAR(B_EPOCH), 0);
      tag_wait<1>(ps, sv, lds32(sb + OFF_MISC));
      const float r = __uint_as_float(sv[0].y), mr = -__uint_as_float(sv[0].x) * (MIM & 1 ? 1.f : r);
      const float r2 = __shfl_down_sync(0xffffffffu, r, 1), mr2 = __shfl_down_sync(0xffffffffu, mr, 1);
      if (tid < 80 && !(tid & 1)) {
        const uint32_t hi = pack2(r, r2);
        sts128(sb + OFF_ST2 + 8 * tid, make_uint4(hi, pack2(mr, mr2), __float_as_uint(0.25f * r), __float_as_uint(0.25f * r2)));
        sts32(sb + OFF_ST2 + 640 + 2 * tid, pack2(r - blo(hi), r2 - bhi(hi)));
      }
      warp_arrive(BAR(B_EP));
    }
    if ((!has2 || wg == 2) && tid == 0) mbar_arrive(BAR(B_DONE));
    if (has2 && wg < 2) {
      float acc[40];
      const uint64_t da0 = make_desc(sb + wg * 8192, 16, 1024, 1), db0 = make_desc(sb + G2_B, 16, 1024, 1);
      const float b20 = 0.5f * ldg_bf16(P.b2 + 128 * dt + 64 * wg + 16 * w4 + g), b21 = 0.5f * ldg_bf16(P.b2 + 128 * dt + 64 * wg + 16 * w4 + g + 8);
      if (threadIdx.x == 0) mbar_arrive(BAR(B_GO));
      if (!PRE) mbar_wait(BAR(B_GO), 0);
      const bool lead = tid == 0;
      const int mi = lane >> 3, rr = lane & 7;
      const uint32_t xa = sb + OFF_XT + wg * XT_STEP + ((mi >> 1) * 8 + rr) * 128 + (((2 * w4 + (mi & 1)) ^ rr) << 4);
      const uint32_t ya = sb + OFF_YT + (64 * wg + 16 * w4 + (mi & 1) * 8 + rr) * 160 + (mi >> 1) * 16;
      uint32_t xr[5][4], xn[5][4];
      uint2 rq[10];
      uint32_t va = sb + OFF_MISC + 28, ta = sb + OFF_ST2 + 16 * c, tb = sb + OFF_ST2 + 640 + 4 * c;
      asm volatile("" : "+r"(ta), "+r"(tb));
#pragma unroll
      for (int i = 0; i < 40; i++) acc[i] = 0.f;
#pragma unroll 1
      for (int k0 = 0; k0 < 9; k0++) {
        const int s0 = 3 * (k0 & 1);
        const uint64_t da = da0 + s0 * (G2_STAGE >> 4), db = db0 + s0 * (G2_STAGE >> 4);
        const uint32_t fb = BAR(B_FULL2 + s0);
#pragma unroll
        for (int u = 0; u < 3; u++) {
          if (u == SK2 && k0 == 8 && wg == 1) mbar_wait(BAR(B_SKEW), 0);
          mbar_wait(fb + 8 * u, (k0 >> 1) & 1);
          TZ(threadIdx.x, 64 + 32 + 3 * k0 + u);
          wg_fence();
#pragma unroll
          for (int kk = 0; kk < 4; kk++)
            wgmma_ss_80_10(acc, da + (u * (G2_STAGE >> 4) + kk * (2048 >> 4)), db + (u * (G2_STAGE >> 4) + 2 * kk));
          wg_commit();
          if (SK2 > 2 || k0 < 8) wg_wait<1>();
          if (u) { if (lead) mbar_arrive(fb + 8 * (G2_NST + u - 1)); }
          else if (lead && k0) mbar_arrive(BAR(B_EMPTY2 + 5) - 8 * s0);
        }
      }
      if (SK2 <= 2 && threadIdx.x == 0) mbar_arrive(BAR(B_SKEW));
      if (!CHK && threadIdx.x == 0) { sts32(sb + OFF_MISC + 28, 0); mbar_arrive(BAR(B_VD)); }
      goto tail;
    repeat:
      wg_wait<0>();
#pragma unroll 1
      for (int i = 0, n = 0; i < 4 * 27 && n < 100000;) {
        if (!(i & 3)) {
          asm volatile("bar.sync 9, 256;" ::: "memory");
          if (threadIdx.x == 0) {
            mbar_expect(BAR(B_RT), 26624);
            tma3d(sb, &P.w2, 0, 64 * g2_block(i >> 2), 2 * dt, BAR(B_RT));
            tma2d(sb + G2_B, &P.h_ld, 64 * g2_block(i >> 2), 80 * tj, BAR(B_RT));
          }
          mbar_wait(BAR(B_RT), n++ & 1);
          uint32_t bad = 0;
          ep = lds32(sb + OFF_MISC);
#pragma unroll 1
          for (int q = 0; q < 6; q++) bad |= lds32(h_tag(sb, tj, q >> 1, lane) ^ (i >= 96 && (q & 1) ? 64 : 0)) ^ ep;
          if (__any_sync(0xffffffffu, bad & 1)) continue;
        }
        wg_fence();
        wgmma_ssp_80_10(acc, da0 + (i & 3) * (2048 >> 4), db0 + 2 * (i & 3), i);
        wg_commit();
        wg_wait<0>();
        i++;
      }
      va = sb + OFF_MISC + 24;
    tail:
      mbar_wait(BAR(B_EP), 0);
#pragma unroll
      for (int i = 0; i < 10; i++) {
        if (!(i & 1)) ldsm4t(xa + i * 1024, xr[i >> 1]);
        const uint4 st = lds128(ta + 64 * i);
        const uint32_t lo = MIM & 1 ? lds32(tb + 16 * i) : 0;
        rq[i] = make_uint2(st.z, st.w);
#pragma unroll
        for (int hf = 0; hf < 2; hf++) {
          if (MIM & 1) { const uint32_t d = hadd2(xr[i >> 1][2 * (i & 1) + hf], st.y); xn[i >> 1][2 * (i & 1) + hf] = hfma2v(d, st.x, hmul2(d, lo)); }
          else xn[i >> 1][2 * (i & 1) + hf] = hfma2(xr[i >> 1][2 * (i & 1) + hf], st.x, st.y);
        }
      }
      mbar_wait(BAR(B_VD), 0);
      if (FB && __any_sync(0xffffffffu, lds32(va))) goto repeat;
      wg_wait<0>();
      TZ(tid, 50 + wg);
      mbar_wait(BAR(B_EPY), 0);
      if (!(PRE && SPEC) && tid == 0) mbar_arrive(BAR(B_DONE));
      TZ(tid, 52 + wg);
#pragma unroll
      for (int i = 0; i < 10; i += 2) {
        uint32_t yq[4], ov[4];
        ldsm4(ya + i * 16, yq);
#pragma unroll
        for (int j = 0; j < 2; j++) {
#pragma unroll
          for (int hf = 0; hf < 2; hf++) {
            const float bb2 = hf ? b21 : b20;
            const float z0 = fmaf(acc[4 * (i + j) + 2 * hf], __uint_as_float(rq[i + j].x), bb2), z1 = fmaf(acc[4 * (i + j) + 2 * hf + 1], __uint_as_float(rq[i + j].y), bb2);
            const uint32_t gt = pack2(fmaf(z0, tanh_fast(z0), z0), fmaf(z1, tanh_fast(z1), z1));
            ov[2 * j + hf] = hfma2(hmul2(xn[i >> 1][2 * j + hf], yq[2 * j + hf]), gt, xr[i >> 1][2 * j + hf]);
          }
        }
        if (i == 4 || i == 8) { wfence(8); warp_arrive(BAR(B_HS + 4 * wg + (i == 8))); }
        stsm4t(xa + i * 1024, ov[0], ov[1], ov[2], ov[3]);
      }
      wfence(8);
      warp_arrive(BAR(B_HS + 4 * wg + 2));
      TZ(tid, 6 + wg);
      DBG_END(tid);
    }
  } else {
    asm volatile("setmaxnreg.dec.sync.aligned.u32 %0;" ::"n"(R_P));
    if (warp >= 14) {
      if (has1) {
        auto b1_rows = [&]() {
          const int n0 = B1E ? 2 * lane + 64 * (warp & 1) : 0;
          if (B1E) {
            const int n1 = min(128 + n0, 222);
            const uint32_t b0 = ldg32(P.b1 + ext_col(n0, fs)), b1 = ldg32(P.b1 + ext_col(n1, fs));
            const uint32_t e0 = sb + OFF_EXT + ext_off(n0, 0), e1 = sb + OFF_EXT + ext_off(n1, 0);
#pragma unroll
            for (int k = 3; k < 8; k++) { sts32((e0 + 128 * k) ^ (k << 4), k < 5 ? b0 : 0u); sts32((e1 + 64 * k) ^ ((k >> 1) << 4), k < 5 ? b1 : 0u); }
          } else
        if (warp == 15) {
#pragma unroll 1
          for (int j = 0; j < 2; j++) {
            const int n0 = 2 * lane + 64 * j, n1 = min(128 + n0, 222);
            const uint32_t b0 = ldg32(P.b1 + ext_col(n0, fs)), b1 = ldg32(P.b1 + ext_col(n1, fs));
            const uint32_t e0 = sb + OFF_EXT + ext_off(n0, 0), e1 = sb + OFF_EXT + ext_off(n1, 0);
#pragma unroll
            for (int k = 3; k < 8; k++) { sts32((e0 + 128 * k) ^ (k << 4), k < 5 ? b0 : 0u); sts32((e1 + 64 * k) ^ ((k >> 1) << 4), k < 5 ? b1 : 0u); }
          }
        }
              };
        if (B1E) b1_rows();
        {
          float cs[8];
#pragma unroll
          for (int e = 0; e < 8; e++) cs[e] = 0.f;
          const int q = min(2 * rb, 26) + (lane & 1), kr = lane >> 1;
          const uint32_t stp = rb < 8 ? 2048 : 1024;
          const uint32_t a0 = sb + (warp & 1) * 2 * stp + (rb < 8 ? (q >> 3) * 8192 + kr * 128 + (((q & 7) ^ (kr & 7)) << 4)
                                                  : 16384 + ((q - 16) >> 2) * 4096 + kr * 64 + (((q & 3) ^ ((kr >> 1) & 3)) << 4));
#pragma unroll 1
          for (int kb = 0; kb < CS_KB; kb++) {
            const uint32_t a = a0 + (kb & 3) * G1_W;
            mbar_wait(BAR(B_FULL1 + (kb & 3)), kb >> 2);
            const uint4 u = lds128(a), w = lds128(a + stp);
            warp_arrive(BAR(B_EMPTY1 + (kb & 3)) + ((u.x | w.x) & P.zero));
            cs[0] += blo(u.x) + blo(w.x); cs[1] += bhi(u.x) + bhi(w.x); cs[2] += blo(u.y) + blo(w.y); cs[3] += bhi(u.y) + bhi(w.y);
            cs[4] += blo(u.z) + blo(w.z); cs[5] += bhi(u.z) + bhi(w.z); cs[6] += blo(u.w) + blo(w.w); cs[7] += bhi(u.w) + bhi(w.w);
          }
#pragma unroll
          for (int kb = CS_KB; kb < 6; kb++) { mbar_wait(BAR(B_EMPTY1 + (kb & 3)), 0); if (elect()) mbar_arrive(BAR(B_EMPTY1 + (kb & 3))); }
#pragma unroll
          for (int e = 0; e < 4; e++) {
            const bool up = lane & 4;
            const float o = __shfl_xor_sync(0xffffffffu, up ? cs[e] : cs[e + 4], 4);
            cs[e] = (up ? cs[e + 4] : cs[e]) + o;
          }
#pragma unroll
          for (int e = 0; e < 2; e++) {
            const bool up = lane & 2;
            const float o = __shfl_xor_sync(0xffffffffu, up ? cs[e] : cs[e + 2], 2);
            cs[e] = (up ? cs[e + 2] : cs[e]) + o;
            cs[e] += __shfl_xor_sync(0xffffffffu, cs[e], 8);
            cs[e] += __shfl_xor_sync(0xffffffffu, cs[e], 16);
          }
          const uint32_t xa = sb + OFF_ST2 + 8 * (lane & 7);
          if (warp == 15 && lane < 8) { sts32(xa, __float_as_uint(cs[0])); sts32(xa + 4, __float_as_uint(cs[1])); }
          asm volatile("bar.sync 8, 64;" ::: "memory");
          if (warp == 14) {
            const uint2 o = lds64(xa);
            mbar_wait(BAR(B_EPOCH), 0);
            if (lane < 8 && rb < 14 && (rb < 12 || fs < 6))
              tag_store(P.cs + (ext_col(16 * rb, fs) >> 1) + 4 * (lane & 1) + (lane >> 1), cs[0] + __uint_as_float(o.x), cs[1] + __uint_as_float(o.y), lds32(sb + OFF_MISC));
            TZ(lane, 18);
          }
        }
        if (!B1E) b1_rows();
      }
      mbar_wait(BAR(B_EPOCH), 0);
      const unsigned ep = lds32(sb + OFF_MISC);
      if (has1) {
        const int l2 = tid - 64, n0 = 2 * l2, n1 = min(128 + 2 * l2, 222), f0 = ext_col(n0, fs), f1 = ext_col(n1, fs);
        const uint32_t e0 = sb + OFF_EXT + ext_off(n0, 0), e1 = sb + OFF_EXT + ext_off(n1, 0);
        const uint2* const pc[4] = {P.cs + (f0 >> 1), P.cs + (f1 >> 1), P.cs + CSP + (f0 >> 1), P.cs + CSP + (f1 >> 1)};
        if (warp == 14) TZ(lane, 126);
        uint2 v[4] = {tag_load(pc[0]), tag_load(pc[1]), tag_load(pc[2]), tag_load(pc[3])};
        tag_wait<4>(pc, v, ep);
#pragma unroll
        for (int i = 0; i < 2; i++) {
          const float x = __uint_as_float(v[i].x) + __uint_as_float(v[i + 2].x), y = __uint_as_float(v[i].y) + __uint_as_float(v[i + 2].y);
          const uint32_t hi = pack2(x, y), lo = pack2(x - blo(hi), y - bhi(hi));
#pragma unroll
          for (int k = 0; k < 3; k++) sts32(i ? (e1 + 64 * k) ^ ((k >> 1) << 4) : (e0 + 128 * k) ^ (k << 4), k < 2 ? hi : lo);
        }
        TZ(lane, 25);
        fence_async_smem();
        warp_arrive(BAR(B_TAB));
      }
      if (PRE && has2 && warp == 14) {
        const int q1 = 32 + (lane & 7);
        const uint2 *const p0 = P.stats + min(80 * tj + 2 * lane, S_ - 2), *const p1 = P.stats + min(80 * tj + 2 * q1, S_ - 2);
        const uint2* const ps[4] = {p0, p0 + 1, p1, p1 + 1};
        uint2 sv[4] = {tag_load(ps[0]), tag_load(ps[1]), tag_load(ps[2]), tag_load(ps[3])};
        tag_wait<4>(ps, sv, ep);
#pragma unroll
        for (int j = 0; j < 2; j++) {
          const float r = __uint_as_float(sv[2 * j].y), r2 = __uint_as_float(sv[2 * j + 1].y);
          const uint32_t hi = pack2(r, r2), q = j ? q1 : lane;
          sts128(sb + OFF_ST2 + 16 * q, make_uint4(hi, pack2(-__uint_as_float(sv[2 * j].x), -__uint_as_float(sv[2 * j + 1].x)), __float_as_uint(0.25f * r), __float_as_uint(0.25f * r2)));
          sts32(sb + OFF_ST2 + 640 + 4 * q, pack2(r - blo(hi), r2 - bhi(hi)));
        }
        warp_arrive(BAR(PRE == 2 ? B_XF : B_EP));
      }
      __syncwarp();
      if (elect()) {
        if (warp == 15) {
          if (CHK == 3) for (int s = 0; s < G2_NST; s++) mbar_arrive(BAR(B_EMPTY2 + s));
          if (has1) {
            prefetch_map(&P.h_st); prefetch_map(&P.h_st2);
#pragma unroll
            for (int j = 0; j < 4; j++) {
              mbar_wait(BAR(B_HS + 4 * (j & 1) + (j & 2)), 0); rfence(2);
              if (j & 1) TS(33 + 4 * (j & 2));
              tma2d_st(&P.h_st, 192 * fs + 64 * (j & 2), 128 * rb + 64 * (j & 1), sb + OFF_X + (j & 2) * G1_X + (j & 1) * 8192);
              if (j == 1) {
                bulk_commit();
                bulk_wait_all();
                h_flag(P, rb, 0);
                mbar_arrive(BAR(B_EMPTY2 + 4 - RM));
                TS(26);
              }
            }
            if (fs < 6) {
#pragma unroll
              for (int w = 0; w < 2; w++) {
                mbar_wait(BAR(B_HS + 4 * w + 3), 0); rfence(2);
                tma2d_st(&P.h_st2, 1536 + 32 * fs, 128 * rb + 64 * w, sb + OFF_X + 3 * G1_X + w * 4096);
              }
            }
            bulk_commit();
            bulk_wait_all();
            mbar_arrive(BAR(B_EMPTY2 + 5 - RM));
            pub_fence(2);
            h_flag(P, rb, 64);
            TS(14);
          }
          if (has2) {
            h_wait(P, tj, 64, ep);
            mbar_arrive(BAR(B_HB));
            TS(17);
          }
        }
      }
      __syncwarp();
      if (warp == 15 && has2) {
        uint32_t ta[3], bad = 0;
#pragma unroll
        for (int q = 0; q < 3; q++) ta[q] = h_tag(sb, tj, q, lane);
        int s = 0, ph = 0;
#pragma unroll 1
        for (int kb = 0; kb < 27; kb++) {
          mbar_wait(BAR(B_FULL2 + s), ph);
          uint32_t t = 0;
#pragma unroll
          for (int q = 0; q < 3; q++) t |= lds32(ta[q] + g2_slot(s) * G2_STAGE) ^ ep;
          if (kb >= 24) {
#pragma unroll
            for (int q = 0; q < 3; q++) t |= lds32((ta[q] ^ 64) + g2_slot(s) * G2_STAGE) ^ ep;
          }
          bad |= t;
          if (CHK == 3 && lane == 0) mbar_arrive(BAR(B_EMPTY2 + s) + (t & P.zero));
          if (++s == G2_NST) { s = 0; ph ^= 1; }
        }
        bad = __any_sync(0xffffffffu, bad & 1);
        if (lane == 0) { if (!PRE) sts32(sb + OFF_MISC + 28, bad); else if (bad) mbar_arrive(BAR(B_BAD)); mbar_arrive(BAR(B_VD)); }
      }
      if (elect()) {
        if (warp == 14 && has2) {
          prefetch_map(&P.h_ld);
          auto x_issue = [&]() {
            mbar_expect(BAR(B_EP), 20480);
            tma2d(sb + g2_slot(5) * G2_STAGE, &P.x_ep, 128 * dt, 80 * tj, BAR(B_EP));
            tma2d(sb + g2_slot(5) * G2_STAGE + 10240, &P.x_ep, 128 * dt + 64, 80 * tj, BAR(B_EP));
          };
          if (RM) { prefetch_map(&P.x_ep); mbar_wait(BAR(B_G1FREE), 0); }
          if (RM && XE_AT == 0) x_issue();
          if (RM && XE_AT == 3) { if (has1) mbar_wait(BAR(B_HS + 1), 0); x_issue(); }
          h_wait(P, tj, 0, ep);
          if (RM && XE_AT == 1) x_issue();
          TS(16);
#pragma unroll 1
          for (int k0 = 0; k0 < 9; k0++) {
#pragma unroll
            for (int u = 0; u < 3; u++) {
              const int kb = 3 * k0 + u, s = 3 * (k0 & 1) + u;
              if (RM && !GO5 && u == 2 && k0 == 1) mbar_wait(BAR(B_XF), 0);
              if (RM && GO5 ? u == 2 && k0 == 1 : u == 0 && k0 == 2) {
                if (USE_GO) flag_wait<false>(P.flags + FL_G2 + 32 * mp.z, ep * mp.w * GO_N);
                mbar_arrive(BAR(B_GO));
                TS(20);
              }
              if (RM && XE_AT == 2 && u == 0 && k0 == 1) x_issue();
              if (RM && GO5 && u == 2 && k0 == 1) mbar_wait(BAR(B_XF), 0);
              if (u == 2 && k0 == 2) mbar_wait(BAR(B_H1), 0);
              if (u == 1 && k0 == 5) mbar_wait(BAR(B_HB), 0);
              mbar_wait(BAR(B_EMPTY2 + s), (k0 >> 1) & 1);
              TS(64 + 96 + kb);
              mbar_expect(BAR(B_FULL2 + s), 10240);
              tma2d(sb + (u < 2 ? (RM ? 4 : 3) * (k0 & 1) + u : 2 + (RM ? 1 : 3) * (k0 & 1)) * G2_STAGE + G2_B, &P.h_ld, 64 * g2_block(kb), 80 * tj, BAR(B_FULL2 + s));
              if (u == YK % 3 && k0 == YK / 3) mbar_arrive(BAR(B_LATE));
            }
          }
        }
        if (has2) {
          const int w = 15 - warp;
          prefetch_map(&P.out_st);
#pragma unroll
          for (int j = 0; j < 5; j++) {
            if (!(j & 1)) { mbar_wait(BAR(B_HS + 4 * w + (j >> 1)), has1); rfence(8); }
            tma2d_st(&P.out_st, 128 * dt + 64 * w, 80 * tj + 16 * j, sb + OFF_XT + w * XT_STEP + j * 2048);
          }
          bulk_commit();
        }
        mbar_arrive(BAR(B_DONE));
        bulk_wait_read();
        TS(54 + 15 - warp);
        DBG_END(0);
      }
    } else if (warp == 13) {
      unsigned ep;
      asm volatile("ld.relaxed.gpu.global.u32 %0, [%1];" : "=r"(ep) : "l"(P.flags + FL_EPOCH) : "memory");
      if (has1 && lane < 5) sts32(sb + OFF_MISC + 4 + 4 * lane, __float_as_uint(ldg_bf16(P.ssm_D + g1 + 128 * lane)));
      ep += 1;
      __syncwarp();
      if (elect()) {
        sts32(sb + OFF_MISC, ep); sts32(sb + OFF_MISC + 24, 0);
        mbar_arrive(BAR(B_EPOCH));
        if (PFW && has1) bulk_prefetch(P.w1p + 256 * F_ + g1 * (PFW * F_ / 2), PFW * F_);
        flag_add_rlx(P.flags + FL_START, 1);
        if (!has1 && has2) flag_add_rlx(P.flags + FL_G2 + 32 * mp.z, GO_N);
        if (has1) {
          prefetch_map(&P.kvz); prefetch_map(&P.f_ld); prefetch_map(&P.y_st);
#define W(b) mbar_wait_b(BAR(b), 0);
#define KV(r) kv_issue(P, sb + OFF_KV + (r) * KV_SLOT, BAR(B_KV + (r)), r, g1);
#define PUBA rfence(1); kv_out(P, sb + OFF_KVS, 0, g1); kv_out(P, sb + OFF_KV + KV_SLOT + KV_V, 1, g1); bulk_commit(); bulk_wait_read(); \
  kv_issue(P, sb + OFF_KV + KV_SLOT, BAR(B_KV + 1), 3, g1); mbar_arrive(BAR(B_KVR)); bulk_wait_all(); pub_fence(1); flag_add_rlx(P.flags + FL_KV, 1); TS(56);
#define PUBB mbar_wait_b(BAR(B_KVS + 1), 0); rfence(1); kv_out(P, sb + OFF_KVS, 2, g1); kv_out(P, sb + OFF_KV + KV_SLOT + KV_V, 3, g1); bulk_commit(); bulk_wait_read();
#define FLB bulk_wait_all(); pub_fence(1); flag_add_rlx(P.flags + FL_KV + 32, 1); TS(57);
#define PUBC mbar_wait_b(BAR(B_KVS + 2), 0); rfence(1); kv_out(P, sb + (K4E ? OFF_KV4 : OFF_KV) + KV_V, 4, g1); bulk_commit(); bulk_wait_read();
#define PUBC0 mbar_wait_b(BAR(B_KVS + 2), 0); rfence(1); kv_out(P, sb + OFF_KV4 + KV_V, 4, g1); bulk_commit();
#define K4 kv_issue(P, sb + OFF_KV4, BAR(B_KV4), 4, g1);
#define KG mbar_expect(BAR(B_KVC), 4096); bulk_g2s(sb + OFF_G, P.tab + 2048, 4096, BAR(B_KVC));
#define FLC bulk_wait_all(); pub_fence(1); flag_add_rlx(P.flags + FL_KV + 64, 1); TS(63);
#define KC mbar_expect(BAR(B_DFT), K4E ? 8192 : 12288); bulk_g2s(sb + OFF_DFT, P.tab, K4E ? 8192 : 12288, BAR(B_DFT));
#define F(c) conv_issue_f(P, conv_tile(sb, c), g1 + 128 * (c), BAR(B_CX + (c)));
#define G(i) flag_wait<true>(P.flags + FL_KV + 32 * (i), ep * 128); fence_async_global(); TS((i) == 2 ? 28 : 23 + 6 * (i));
#define X(c) conv_issue_x(P, conv_tile(sb, c), g1 + 128 * (c), BAR(B_CX + (c)));
#define Y(c) mbar_wait_b(BAR(B_RD + (c)), 0); rfence(4); tma2d_st(&P.y_st, 0, 32 * (g1 + 128 * (c)), (c) ? conv_tile(sb, c) : sb + OFF_Y0); bulk_commit();
#define XE if (!RM) { mbar_expect(BAR(B_EP), 20480); tma2d(sb + OFF_XT, &P.x_ep, 128 * dt, 80 * tj, BAR(B_EP)); tma2d(sb + OFF_XT + XT_STEP, &P.x_ep, 128 * dt + 64, 80 * tj, BAR(B_EP)); }
#define R if (!RM) bulk_wait_read();
#define A(b) mbar_arrive(BAR(b));
#define PF(c) bulk_prefetch(P.ssm_k + (g1 + 128 * (c)) * S_, 4096);
#define PW bulk_prefetch(P.w2p + g1 * (F_ * D_ / 128), F_ * D_ / 64);
          AUX_SEQ
#undef W
#undef PUBA
#undef PUBB
#undef PUBC
#undef FLB
#undef FLC
#undef KC
#undef F
#undef G
#undef X
#undef Y
#undef R
#undef XE
#undef A
#undef PF
#undef PW
          bulk_wait_all(); pub_fence(4);
          flag_add_rlx(P.flags + FL_Y, 1);
          TS(12);
          if (g1 == 0) { flag_wait<true>(P.flags + FL_START, ep * NCTA); P.flags[FL_EPOCH] = ep; }
        }
        if (has2) {
          mbar_expect(BAR(B_EPY), 20480);
          prefetch_map(&P.y_ld);
          if (!RM && !has1) {
            if (PRE) mbar_wait_b(BAR(B_EMPTY2), 0);
            mbar_expect(BAR(B_EP), 20480);
            tma2d(sb + OFF_XT, &P.x_ep, 128 * dt, 80 * tj, BAR(B_EP));
            tma2d(sb + OFF_XT + XT_STEP, &P.x_ep, 128 * dt + 64, 80 * tj, BAR(B_EP));
          }
          flag_wait<true>(P.flags + FL_Y, ep * 128);
          fence_async_global();
          mbar_wait_b(BAR(B_LATE), 0);
          TS(13);
          tma2d(sb + OFF_YT, &P.y_ld, 80 * tj, 128 * dt, BAR(B_EPY));
        }
        mbar_wait_b(BAR(B_DONE), 0);
      }
    } else {
      const bool lead = elect();
      if (lead) {
        mbar_init(BAR(B_FULL1), 1);
        fence_async_smem();
        if (has1) g1_issue(P, sb, 0, BAR(B_FULL1), 0, rb, fs);
        else if (!SP_D0) { mbar_expect(BAR(B_FULL1), CS_STAGE); tma3d(sb, &P.w1_cs, 0, 64 * CS_KB, 7 * (g1 - 128), BAR(B_FULL1)); }
#pragma unroll
        for (int b = 1; b < B_FIRST; b++) mbar_init(BAR(b), 1);
        fence_async_smem();
      }
      __syncwarp();
      asm volatile("bar.arrive 0, 512;" ::: "memory");
      if (lead) {
        if (has1) {
#define S(kb) g1_issue(P, sb, kb, BAR(B_FULL1 + (kb)), kb, rb, fs);
#define K(r) kv_issue(P, sb + OFF_KV + (r) * KV_SLOT, BAR(B_KV + (r)), r, g1);
#define T mbar_expect(BAR(B_STAT), 20480); bulk_g2s(sb + OFF_SR, P.x + g1 * 16 * D_, 20480, BAR(B_STAT));
          INIT_SEQ
          TS(64 + 20 + 3);
        } else {
#pragma unroll
          for (int kb = SP_D0 ? 0 : 1; kb < 3; kb++) { clk_wait(kb ? SP_D1 : SP_D0); mbar_expect(BAR(B_FULL1 + kb), CS_STAGE); tma3d(sb + kb * CS_STAGE, &P.w1_cs, 0, 64 * (CS_KB + kb), 7 * (g1 - 128), BAR(B_FULL1 + kb)); }
        }
      }
      __syncwarp();
      asm volatile("bar.sync 7, 512;" ::: "memory");
      if (lead) {
        if (has1) {
#pragma unroll 1
          for (int kb = G1_NST; kb < STE; kb++) {
            const int s = kb & 3;
            mbar_wait(BAR(B_EMPTY1 + s), ((kb >> 2) - 1) & 1);
            TS(64 + 20 + kb);
            g1_issue(P, sb, s, BAR(B_FULL1 + s), kb, rb, fs);
          }
        }
      }
      __syncwarp();
      if (has1) {
        const uint2* const p0 = P.stats + 128 * rb + lane;
        const uint2* const ps[4] = {p0, p0 + 32, p0 + 64, p0 + 96};
        TZ(lane, 124);
        uint2 sv[4] = {tag_load(ps[0]), tag_load(ps[1]), tag_load(ps[2]), tag_load(ps[3])};
        if (lead) {
#pragma unroll
          for (int kb = STE; kb < 10; kb++) {
            const int s = kb & 3;
            mbar_wait(BAR(B_EMPTY1 + s), ((kb >> 2) - 1) & 1);
            TS(64 + 20 + kb);
            g1_issue(P, sb, s, BAR(B_FULL1 + s), kb, rb, fs);
          }
        }
        __syncwarp();
        mbar_wait(BAR(B_EPOCH), 0);
        tag_wait<4>(ps, sv, lds32(sb + OFF_MISC));
#pragma unroll
        for (int j = 0; j < 4; j++) {
          const float mn = -__uint_as_float(sv[j].x), mh = bf_round(mn), sd = rcp_fast(__uint_as_float(sv[j].y)), sh = bf_round(sd);
          sts128(sb + OFF_ST1 + 16 * (lane + 32 * j), make_uint4(pack2(mh, mn - mh), pack2(mh, sh), pack2(sd - sh, 0.f), sv[j].y));
        }
        warp_arrive(BAR(B_TAB));
        TZ(lane, 11);
      }
      if (lead) {
        if (!has1) {
#pragma unroll
          for (int kb = CS_KB + 3; kb < 10; kb++) {
            const int s = kb - CS_KB - 3;
            mbar_wait(BAR(B_EMPTY1 + s), 0);
            clk_wait(SP_D1);
            mbar_expect(BAR(B_FULL1 + s), CS_STAGE);
            tma3d(sb + s * CS_STAGE, &P.w1_cs, 0, 64 * kb, 7 * (g1 - 128), BAR(B_FULL1 + s));
          }
        }
        auto h_second = [&]() {
#pragma unroll
          for (int w = 0; w < 2; w++) {
            mbar_wait(BAR(B_HS + 4 * w + 1), 0); rfence(2);
            tma2d_st(&P.h_st, 192 * fs + 64, 128 * rb + 64 * w, sb + OFF_X + G1_X + w * 8192);
          }
          TS(37);
          bulk_commit();
          bulk_wait_all();
          mbar_arrive(BAR(B_EMPTY2 + 4 - RM)); mbar_arrive(BAR(B_EMPTY2 + 5 - RM));
          pub_fence(2);
          h_flag(P, rb, 32);
          TS(27);
        };
        if (has2) {
          prefetch_map(&P.w2);
#pragma unroll 1
          for (int k0 = 0; k0 < 9; k0++) {
#pragma unroll
            for (int u = 0; u < 3; u++) {
              const int kb = 3 * k0 + u, s = 3 * (k0 & 1) + u;
              if (u == 1 - RM && k0 == 1 && has1) h_second();
              if (RM && u == 2 && k0 == 1) mbar_wait(BAR(B_XF), 0);
              if (u == 0 && k0 == 2) { mbar_wait(BAR(B_EPOCH), 0); h_wait(P, tj, 32, lds32(sb + OFF_MISC)); mbar_arrive(BAR(B_H1)); TS(15); }
              mbar_wait(BAR(B_EMPTY2 + s), (k0 >> 1) & 1);
              mbar_expect(BAR(B_FULL2 + s), 16384);
              tma3d(sb + (u < 2 ? (RM ? 4 : 3) * (k0 & 1) + u : 2 + (RM ? 1 : 3) * (k0 & 1)) * G2_STAGE, &P.w2, 0, 64 * g2_block(kb), 2 * dt, BAR(B_FULL2 + s));
            }
          }
        }
        mbar_arrive(BAR(B_DONE));
      }
    }
  }

#undef BAR
}

typedef CUresult (*EncodeFn)(CUtensorMap*, CUtensorMapDataType, cuuint32_t, void*, const cuuint64_t*, const cuuint64_t*, const cuuint32_t*,
                             const cuuint32_t*, CUtensorMapInterleave, CUtensorMapSwizzle, CUtensorMapL2promotion, CUtensorMapFloatOOBfill);

static void enc(EncodeFn f, CUtensorMap* m, const void* base, int rank, const cuuint64_t* dims, const cuuint64_t* strides, const cuuint32_t* box, CUtensorMapSwizzle sw) {
  const cuuint32_t es[5] = {1, 1, 1, 1, 1};
  f(m, CU_TENSOR_MAP_DATA_TYPE_BFLOAT16, rank, const_cast<void*>(base), dims, strides, box, es, CU_TENSOR_MAP_INTERLEAVE_NONE, sw,
    CU_TENSOR_MAP_L2_PROMOTION_L2_128B, CU_TENSOR_MAP_FLOAT_OOB_FILL_NONE);
}
static void enc2(EncodeFn f, CUtensorMap* m, const void* base, uint64_t d0, uint64_t d1, uint32_t b0, uint32_t b1, CUtensorMapSwizzle sw) {
  const cuuint64_t dims[2] = {d0, d1}, strides[1] = {d0 * 2};
  const cuuint32_t box[2] = {b0, b1};
  enc(f, m, base, 2, dims, strides, box, sw);
}

extern "C" void kernel_launch(void* const* d_in, const int* in_sizes, int n_in, void* d_out, int out_size) {
  (void)in_sizes; (void)n_in; (void)out_size;
  static EncodeFn fn = nullptr;
  static void *p_h, *p_kvZ, *p_yT, *p_stats, *p_cs, *p_flags, *p_tab;
  if (!fn) {
    cudaDriverEntryPointQueryResult qr;
    void* f = nullptr;
    cudaGetDriverEntryPoint("cuTensorMapEncodeTiled", &f, cudaEnableDefault, &qr);
    fn = (EncodeFn)f;
    cudaFuncSetAttribute(h3_fused_kernel, cudaFuncAttributeMaxDynamicSharedMemorySize, SMEM_BYTES);
    cudaGetSymbolAddress(&p_h, g_h); cudaGetSymbolAddress(&p_kvZ, g_kvZ); cudaGetSymbolAddress(&p_yT, g_yT);
    cudaGetSymbolAddress(&p_stats, g_stats); cudaGetSymbolAddress(&p_cs, g_cs); cudaGetSymbolAddress(&p_flags, g_flags); cudaGetSymbolAddress(&p_tab, g_tab);
  }
  Params P;
  const bf16 *x = (const bf16*)d_in[0], *k = (const bf16*)d_in[1], *v = (const bf16*)d_in[2];
  const bf16 *w1 = (const bf16*)d_in[7], *w2 = (const bf16*)d_in[9];
  P.x = x; P.shift_k = (const bf16*)d_in[3]; P.ssm_k = (const bf16*)d_in[4]; P.ssm_D = (const bf16*)d_in[5];
  P.b1 = (const bf16*)d_in[8]; P.b2 = (const bf16*)d_in[10]; P.w2p = w2; P.w1p = w1;
  P.zero = 0; P.kvZ = (bf16*)p_kvZ; P.tab = (const uint32_t*)p_tab; P.stats = (uint2*)p_stats; P.cs = (uint2*)p_cs; P.flags = (unsigned*)p_flags;
  enc2(fn, &P.x_g1, x, D_, S_, 64, 128, CU_TENSOR_MAP_SWIZZLE_128B);
  {
    const cuuint64_t dims[3] = {64, D_, 27}, strides[2] = {F_ * 2, 128};
    const cuuint32_t box[3] = {64, 64, 2};
    enc(fn, &P.w1_a, w1, 3, dims, strides, box, CU_TENSOR_MAP_SWIZZLE_128B);
    const cuuint32_t box7[3] = {64, 64, 7};
    enc(fn, &P.w1_cs, w1, 3, dims, strides, box7, CU_TENSOR_MAP_SWIZZLE_128B);
    const cuuint64_t dims2[3] = {32, D_, 54}, strides2[2] = {F_ * 2, 64};
    const cuuint32_t box2[3] = {32, 64, 2}, box1[3] = {32, 64, 1};
    enc(fn, &P.w1_b2, w1, 3, dims2, strides2, box2, CU_TENSOR_MAP_SWIZZLE_64B);
    enc(fn, &P.w1_b1, w1, 3, dims2, strides2, box1, CU_TENSOR_MAP_SWIZZLE_64B);
  }
  enc2(fn, &P.h_ld, p_h, F_, S_, 64, 80, CU_TENSOR_MAP_SWIZZLE_128B);
  {
    const cuuint64_t dims[3] = {64, F_, 10}, strides[2] = {D_ * 2, 128};
    const cuuint32_t box[3] = {64, 64, 2};
    enc(fn, &P.w2, w2, 3, dims, strides, box, CU_TENSOR_MAP_SWIZZLE_128B);
  }
  enc2(fn, &P.h_st, p_h, F_, S_, 64, 64, CU_TENSOR_MAP_SWIZZLE_128B);
  enc2(fn, &P.h_st2, p_h, F_, S_, 32, 64, CU_TENSOR_MAP_SWIZZLE_64B);
  enc2(fn, &P.k, k, D_, S_, 128, 19, CU_TENSOR_MAP_SWIZZLE_NONE);
  enc2(fn, &P.v, v, D_, S_, 128, 16, CU_TENSOR_MAP_SWIZZLE_NONE);
  {
    const cuuint64_t dims[3] = {D_ * 16, 32, 4}, strides[2] = {D_ * 128, D_ * 32};
    const cuuint32_t box[3] = {16, 32, 4};
    enc(fn, &P.kvz, p_kvZ, 3, dims, strides, box, CU_TENSOR_MAP_SWIZZLE_32B);
  }
  enc2(fn, &P.f_ld, P.ssm_k, 64, D_ * 32, 64, 32, CU_TENSOR_MAP_SWIZZLE_128B);
  enc2(fn, &P.y_st, p_yT, 64, D_ * 32, 64, 32, CU_TENSOR_MAP_SWIZZLE_128B);
  enc2(fn, &P.y_ld, p_yT, S_, D_, 80, 128, CU_TENSOR_MAP_SWIZZLE_NONE);
  enc2(fn, &P.x_ep, x, D_, S_, 64, 80, CU_TENSOR_MAP_SWIZZLE_128B);
  enc2(fn, &P.out_st, d_out, D_, S_, 64, 16, CU_TENSOR_MAP_SWIZZLE_128B);
  for (int b = 0; b < 72; b++) P.cnt[b] = 1;
  P.cnt[B_XF] = PRE == 2 ? 1 : 8;
  for (int b = 0; b < 5; b++) { P.cnt[B_CX + b] = 2; P.cnt[B_RD + b] = 4; }
  for (int b = 0; b < 4; b++) P.cnt[B_EMPTY1 + b] = 4;
  for (int b = 0; b < 2 * G2_NST; b++) P.cnt[B_FULL2 + b] = CHK == 3 && b >= G2_NST ? 3 : 2;
  P.cnt[B_DBG] = 4;
  P.cnt[B_G1FREE] = P.cnt[B_GO] = 2; P.cnt[B_TAB] = 3; P.cnt[B_EP] = PRE == 2 ? 1 : PRE ? 2 : 5; P.cnt[B_DONE] = 6;
  for (int b = 0; b < 8; b++) P.cnt[B_HS + b] = 4;
  P.cnt[B_KVS] = P.cnt[B_KVS + 1] = P.cnt[B_STATFREE] = 4; P.cnt[B_KVS + 2] = K4E ? 4 : 2;
  {
    const char *g2s = G2MAP, *gos = GOMAP;
    int g1v = G1V;
    int mem[10][18], cnt[10] = {0}, used[10] = {0}, gn[9] = {0};
    for (int b = 0; b < NCTA; b++) {
      const int tpc = b >> 1;
      const int gp = tpc < 32 ? tpc % 8 : tpc < 60 ? 1 + (tpc - 32) % 7 : tpc < 62 ? tpc - 54 : tpc == 63 ? 8 : tpc == 64 ? 9 : 0;
      mem[gp][cnt[gp]++] = b;
      P.map[b] = make_uchar4(255, 255, gos[gp] - '0', 0);
    }
    const int bi[8] = {0, 0, 0, 1, 1, 2, 3, 2}, bj[8] = {0, 0, 1, 0, 1, 0, 0, 1};
    for (int gp = 1; gp < 8; gp++)
      for (int i = 0; i < 16; i++) P.map[mem[gp][i]].x = (4 * bi[gp] + (i & 3)) * 8 + 4 * bj[gp] + (i >> 2);
    for (int i = 0; i < 8; i++) P.map[mem[0][i]].x = (12 + (i & 3)) * 8 + 4 + (i >> 2);
    for (int i = 0; i < 4; i++) {
      const int gh = mem[6 + (i >> 1)][16 + (i & 1)], st = mem[8 + (i >> 1)][i & 1], a = mem[0][8 + i];
      if (g1v == 0) { P.map[gh].x = (12 + i) * 8 + 6; P.map[i < 2 ? a : mem[8][i & 1]].x = (12 + i) * 8 + 7; P.map[i < 2 ? mem[9][i] : a].x = 128 + i; }
      if (g1v == 1) { P.map[gh].x = (12 + i) * 8 + 6; P.map[a].x = (12 + i) * 8 + 7; P.map[st].x = 128 + i; }
      if (g1v == 2) { P.map[st].x = (12 + i) * 8 + 6; P.map[a].x = (12 + i) * 8 + 7; P.map[gh].x = 128 + i; }
    }
    for (int n = 0; *g2s; g2s++) {
      if (*g2s == ' ') continue;
      const int gp = *g2s < 'a' ? *g2s - 'A' : *g2s - 's' + 8;
      P.map[mem[gp][used[gp]++]].y = n / 5 * 8 + n % 5;
      gn[gos[gp] - '0']++;
      n++;
    }
    for (int b = 0; b < NCTA; b++) P.map[b].w = gn[P.map[b].z];
  }
  h3_fused_kernel<<<NCTA, 512, SMEM_BYTES, cudaStreamPerThread>>>(P);
}
```

```cpp
#include <cuda_runtime.h>
#include <cuda_bf16.h>
#include <cuda.h>
#include <stdint.h>
#include <stdlib.h>

#define K4E 0
#define INIT_SEQ S(1) S(2) S(3) K(0) K(1) T
#define AUX_PRE
#define W14ON (K4E == 4)
#define W14 W(B_G1FREE) F(3) W(B_T2) F(2) G(1) X(3) X(2)
#define AUX_SEQ AUX_PRE W(B_KVS) PUBA W(B_STATFREE) KC F(0) PF(1) G(0) X(0) PF(2) PF(3) PUBB X(1) F(1) FLB PF(4) PW PUBC A(B_KVC) F(2) FLC W(B_G1FREE) F(3) G(1) X(3) X(2) G(2) W(B_RD) X(4) F(4) AUX_END
#define G1MAP "70123465"
#define G2MAP "BBBBB BBBBB BBBBB BCCCC CCCCC CCCCC CCDDD DDDDD DDDDD DDDGG GGGGG GGGGG GGGGG HHHHH HHHHH HHHHH HHEEE EEEEE EEEEE EEssE AAAAA AAAAA AAttF FFFFF FFFFF FFFFF"
#define GOMAP "0123456745"
#define SP_FAKE 0
#define POLL 0
#define PD 200
#define TD 450
#define NREP 1
#define NREPY 1
#define FNC 3
#define OUTP 0x32210
#define STU 0
#define GRID0 0
#define GRID1 0
#define GRIDS 0
#define SP_D0 0
#define SP_D1 0
#define PRE 2
#define RM (PRE == 1)
#define AUX_END Y(0) Y(1) R XE Y(2) Y(3) Y(4)
#define SPEC 0
#define NCH 3
#define TAB_AT 0
#define NORM_AT 1
#define GO5 1
#define XE_AT 1
#define YPRE 0
#define B1E 1
#define STE 10
#define NOW 10
#define CH_W0 0xf2
#define CH_W1 0xf3
#define CH_W2 0xf410
#define CS_KB 5
#define CHK 3
#define MIM 1
#define KVCHK 1
#define FB 1
#define DFT_EARLY 3
#define GO_WG 4
#define EREL 0
#define PFW 0
#define SK2 2
#define YK 26
#define DFT_AT 16
#define USE_GO 1
#define GO_AT 2
#define HS_LAG 0
#define LOOKAHEAD 2
#define SPLIT9 0
#define GELU_BF16 4
#define R_G 160
#define R_P 32
#define DBG_TIME 0

namespace {

constexpr int GO_N = (GO_WG & 1) + ((GO_WG >> 1) & 1) + (GO_WG >> 2);
constexpr int S_ = 2048, D_ = 640, F_ = 1728;
constexpr int NCTA = 132;
typedef __nv_bfloat16 bf16;

__device__ __align__(1024) bf16 g_h[S_ * F_];
__device__ __align__(1024) bf16 g_kvZ[D_ * S_];
__device__ __align__(1024) bf16 g_yT[D_ * S_];
__device__ __align__(128) uint2 g_stats[S_];
constexpr int CSP = F_ / 2 + 32;
__device__ __align__(128) uint2 g_cs[2 * CSP];
constexpr int FL_EPOCH = 0, FL_START = 32, FL_KV = 64  , FL_Y = FL_KV + 3 * 256  , FL_H = FL_Y + 256  , FL_G2 = FL_H + 96 * 32  , FL_COUNT = FL_G2 + 9 * 32;
__device__ __align__(128) unsigned g_flags[FL_COUNT];
__device__ __align__(128) const uint32_t g_tab[6144] = {
0x3f803f80,0x3f803f80,0x3f803f80,0x3f803f80,0x3f803f80,0x3f803f80,0x3f803f80,0x3f803f80,0x3f803f80,0x3f803f80,0x3f803f80,0x3f803f80,0x3f803f80,0x3f803f80,0x3f803f80,0x3f803f80,
0x0,0x0,0x0,0x0,0x0,0x0,0x0,0x0,0x0,0x0,0x0,0x0,0x0,0x0,0x0,0x0,
0x3f183f2c,0x3edb3f04,0x3e793eac,0x3d493e16,0x3f7d3f80,0x3f713f78,0x3f5c3f67,0x3f3e3f4e,0xbf4ebf3e,0xbf67bf5c,0xbf78bf71,0xbf80bf7d,0xbe16bd49,0xbeacbe79,0xbf04bedb,0xbf2cbf18,
0x3f4e3f3e,0x3f673f5c,0x3f783f71,0x3f803f7d,0x3e163d49,0x3eac3e79,0x3f043edb,0x3f2c3f18,0x3f183f2c,0x3edb3f04,0x3e793eac,0x3d493e16,0x3f7d3f80,0x3f713f78,0x3f5c3f67,0x3f3e3f4e,
0xbf75bf7f,0xbf46bf62,0xbef1bf22,0xbdc9be95,0x3e953dc9,0x3f223ef1,0x3f623f46,0x3f7f3f75,0x3f753f7f,0x3f463f62,0x3ef13f22,0x3dc93e95,0xbe95bdc9,0xbf22bef1,0xbf62bf46,0xbf7fbf75,
0xbe95bdc9,0xbf22bef1,0xbf62bf46,0xbf7fbf75,0xbf75bf7f,0xbf46bf62,0xbef1bf22,0xbdc9be95,0x3e953dc9,0x3f223ef1,0x3f623f46,0x3f7f3f75,0x3f753f7f,0x3f463f62,0x3ef13f22,0x3dc93e95,
0x3eac3f18,0xbe793d49,0xbf3ebf04,0xbf7dbf67,0x3edb3e16,0x3f5c3f2c,0x3f803f78,0x3f4e3f71,0xbf71bf4e,0xbf78bf80,0xbf2cbf5c,0xbe16bedb,0x3f673f7d,0x3f043f3e,0xbd493e79,0xbf18beac,
0x3f713f4e,0x3f783f80,0x3f2c3f5c,0x3e163edb,0xbf67bf7d,0xbf04bf3e,0x3d49be79,0x3f183eac,0x3eac3f18,0xbe793d49,0xbf3ebf04,0xbf7dbf67,0x3edb3e16,0x3f5c3f2c,0x3f803f78,0x3f4e3f71,
0x3f0e3e48,0x3f7b3f55,0x3f553f7b,0x3e483f0e,0xbf0ebe48,0xbf7bbf55,0xbf55bf7b,0xbe48bf0e,0x3f0e3e48,0x3f7b3f55,0x3f553f7b,0x3e483f0e,0xbf0ebe48,0xbf7bbf55,0xbf55bf7b,0xbe48bf0e,
0x3f553f7b,0x3e483f0e,0xbf0ebe48,0xbf7bbf55,0xbf55bf7b,0xbe48bf0e,0x3f0e3e48,0x3f7b3f55,0x3f553f7b,0x3e483f0e,0xbf0ebe48,0xbf7bbf55,0xbf55bf7b,0xbe48bf0e,0x3f0e3e48,0x3f7b3f55,
0xbf80bf5c,0xbf18bf67,0x3eacbe16,0x3f783f3e,0x3f2c3e79,0x3f7d3f71,0x3edb3f4e,0xbf04bd49,0xbd49bf04,0x3f4e3edb,0x3f713f7d,0x3e793f2c,0x3f3e3f78,0xbe163eac,0xbf67bf18,0xbf5cbf80,
0xbd49bf04,0x3f4e3edb,0x3f713f7d,0x3e793f2c,0x3f3e3f78,0xbe163eac,0xbf67bf18,0xbf5cbf80,0x3f803f5c,0x3f183f67,0xbeac3e16,0xbf78bf3e,0xbf2cbe79,0xbf7dbf71,0xbedbbf4e,0x3f043d49,
0xbf46be95,0xbf62bf7f,0x3dc9bef1,0x3f753f22,0x3f223f75,0xbef13dc9,0xbf7fbf62,0xbe95bf46,0x3f463e95,0x3f623f7f,0xbdc93ef1,0xbf75bf22,0xbf22bf75,0x3ef1bdc9,0x3f7f3f62,0x3e953f46,
0xbf22bf75,0x3ef1bdc9,0x3f7f3f62,0x3e953f46,0xbf46be95,0xbf62bf7f,0x3dc9bef1,0x3f753f22,0x3f223f75,0xbef13dc9,0xbf7fbf62,0xbe95bf46,0x3f463e95,0x3f623f7f,0xbdc93ef1,0xbf75bf22,
0xbf78bf67,0x3d49bf18,0x3f7d3f2c,0x3eac3f5c,0xbf04bf71,0x3f3e3e16,0x3f4e3f80,0xbedb3e79,0x3e79bedb,0x3f803f4e,0x3e163f3e,0xbf71bf04,0x3f5c3eac,0x3f2c3f7d,0xbf183d49,0xbf67bf78,
0x3e79bedb,0x3f803f4e,0x3e163f3e,0xbf71bf04,0x3f5c3eac,0x3f2c3f7d,0xbf183d49,0xbf67bf78,0x3f783f67,0xbd493f18,0xbf7dbf2c,0xbeacbf5c,0x3f043f71,0xbf3ebe16,0xbf4ebf80,0x3edbbe79,
0x3ec43f6d,0xbf6dbec4,0xbec4bf6d,0x3f6d3ec4,0x3ec43f6d,0xbf6dbec4,0xbec4bf6d,0x3f6d3ec4,0x3ec43f6d,0xbf6dbec4,0xbec4bf6d,0x3f6d3ec4,0x3ec43f6d,0xbf6dbec4,0xbec4bf6d,0x3f6d3ec4,
0x3f6d3ec4,0x3ec43f6d,0xbf6dbec4,0xbec4bf6d,0x3f6d3ec4,0x3ec43f6d,0xbf6dbec4,0xbec4bf6d,0x3f6d3ec4,0x3ec43f6d,0xbf6dbec4,0xbec4bf6d,0x3f6d3ec4,0x3ec43f6d,0xbf6dbec4,0xbec4bf6d,
0xbf043eac,0xbf3ebf7d,0x3f4e3d49,0x3edb3f78,0x3e793f67,0xbf80bf18,0x3e16bf2c,0x3f713f5c,0xbf5cbf71,0x3f2cbe16,0x3f183f80,0xbf67be79,0xbf78bedb,0xbd49bf4e,0x3f7d3f3e,0xbeac3f04,
0x3f5c3f71,0xbf2c3e16,0xbf18bf80,0x3f673e79,0x3f783edb,0x3d493f4e,0xbf7dbf3e,0x3eacbf04,0xbf043eac,0xbf3ebf7d,0x3f4e3d49,0x3edb3f78,0x3e793f67,0xbf80bf18,0x3e16bf2c,0x3f713f5c,
0xbdc9bf62,0x3f753f46,0xbf223e95,0xbef1bf7f,0x3f7f3ef1,0xbe953f22,0xbf46bf75,0x3f623dc9,0x3dc93f62,0xbf75bf46,0x3f22be95,0x3ef13f7f,0xbf7fbef1,0x3e95bf22,0x3f463f75,0xbf62bdc9,
0xbf7fbef1,0x3e95bf22,0x3f463f75,0xbf62bdc9,0xbdc9bf62,0x3f753f46,0xbf223e95,0xbef1bf7f,0x3f7f3ef1,0xbe953f22,0xbf46bf75,0x3f623dc9,0x3dc93f62,0xbf75bf46,0x3f22be95,0x3ef13f7f,
0xbf3e3e79,0xbe16bf71,0x3f673f4e,0xbf5c3d49,0x3f803f04,0xbf183edb,0xbeacbf7d,0x3f783f2c,0xbf2cbf78,0x3f7d3eac,0xbedb3f18,0xbf04bf80,0xbd493f5c,0xbf4ebf67,0x3f713e16,0xbe793f3e,
0x3f2c3f78,0xbf7dbeac,0x3edbbf18,0x3f043f80,0x3d49bf5c,0x3f4e3f67,0xbf71be16,0x3e79bf3e,0xbf3e3e79,0xbe16bf71,0x3f673f4e,0xbf5c3d49,0x3f803f04,0xbf183edb,0xbeacbf7d,0x3f783f2c,
0x3f7b3f0e,0xbf553e48,0x3e48bf55,0x3f0e3f7b,0xbf7bbf0e,0x3f55be48,0xbe483f55,0xbf0ebf7b,0x3f7b3f0e,0xbf553e48,0x3e48bf55,0x3f0e3f7b,0xbf7bbf0e,0x3f55be48,0xbe483f55,0xbf0ebf7b,
0xbe483f55,0xbf0ebf7b,0x3f7b3f0e,0xbf553e48,0x3e48bf55,0x3f0e3f7b,0xbf7bbf0e,0x3f55be48,0xbe483f55,0xbf0ebf7b,0x3f7b3f0e,0xbf553e48,0x3e48bf55,0x3f0e3f7b,0xbf7bbf0e,0x3f55be48,
0xbedbbf7d,0x3f5c3f3e,0xbf80be79,0x3f4ebeac,0x3f713f18,0xbf78bd49,0x3f2cbf04,0xbe163f67,0x3f67be16,0xbf043f2c,0xbd49bf78,0x3f183f71,0xbeac3f4e,0xbe79bf80,0x3f3e3f5c,0xbf7dbedb,
0x3f67be16,0xbf043f2c,0xbd49bf78,0x3f183f71,0xbeac3f4e,0xbe79bf80,0x3f3e3f5c,0xbf7dbedb,0x3edb3f7d,0xbf5cbf3e,0x3f803e79,0xbf4e3eac,0xbf71bf18,0x3f783d49,0xbf2c3f04,0x3e16bf67,
0xbf62bf22,0x3f7f3e95,0xbf753dc9,0x3f46bef1,0xbef13f46,0x3dc9bf75,0x3e953f7f,0xbf22bf62,0x3f623f22,0xbf7fbe95,0x3f75bdc9,0xbf463ef1,0x3ef1bf46,0xbdc93f75,0xbe95bf7f,0x3f223f62,
0x3ef1bf46,0xbdc93f75,0xbe95bf7f,0x3f223f62,0xbf62bf22,0x3f7f3e95,0xbf753dc9,0x3f46bef1,0xbef13f46,0x3dc9bf75,0x3e953f7f,0xbf22bf62,0x3f623f22,0xbf7fbe95,0x3f75bdc9,0xbf463ef1,
0xbe16bf80,0x3eac3f78,0xbf04bf67,0x3f2c3f4e,0x3f18bf3e,0xbedb3f5c,0x3e79bf71,0xbd493f7d,0x3f7dbd49,0xbf713e79,0x3f5cbedb,0xbf3e3f18,0x3f4e3f2c,0xbf67bf04,0x3f783eac,0xbf80be16,
0x3f7dbd49,0xbf713e79,0x3f5cbedb,0xbf3e3f18,0x3f4e3f2c,0xbf67bf04,0x3f783eac,0xbf80be16,0x3e163f80,0xbeacbf78,0x3f043f67,0xbf2cbf4e,0xbf183f3e,0x3edbbf5c,0xbe793f71,0x3d49bf7d,
0xbf353f35,0x3f35bf35,0xbf353f35,0x3f35bf35,0xbf353f35,0x3f35bf35,0xbf353f35,0x3f35bf35,0xbf353f35,0x3f35bf35,0xbf353f35,0x3f35bf35,0xbf353f35,0x3f35bf35,0xbf353f35,0x3f35bf35,
0x3f353f35,0xbf35bf35,0x3f353f35,0xbf35bf35,0x3f353f35,0xbf35bf35,0x3f353f35,0xbf35bf35,0x3f353f35,0xbf35bf35,0x3f353f35,0xbf35bf35,0x3f353f35,0xbf35bf35,0x3f353f35,0xbf35bf35,
0xbf7dbd49,0x3f713e79,0xbf5cbedb,0x3f3e3f18,0xbf4e3f2c,0x3f67bf04,0xbf783eac,0x3f80be16,0x3e16bf80,0xbeac3f78,0x3f04bf67,0xbf2c3f4e,0xbf18bf3e,0x3edb3f5c,0xbe79bf71,0x3d493f7d,
0xbe163f80,0x3eacbf78,0xbf043f67,0x3f2cbf4e,0x3f183f3e,0xbedbbf5c,0x3e793f71,0xbd49bf7d,0xbf7dbd49,0x3f713e79,0xbf5cbedb,0x3f3e3f18,0xbf4e3f2c,0x3f67bf04,0xbf783eac,0x3f80be16,
0x3f62bf22,0xbf7f3e95,0x3f753dc9,0xbf46bef1,0x3ef13f46,0xbdc9bf75,0xbe953f7f,0x3f22bf62,0xbf623f22,0x3f7fbe95,0xbf75bdc9,0x3f463ef1,0xbef1bf46,0x3dc93f75,0x3e95bf7f,0xbf223f62,
0xbef1bf46,0x3dc93f75,0x3e95bf7f,0xbf223f62,0x3f62bf22,0xbf7f3e95,0x3f753dc9,0xbf46bef1,0x3ef13f46,0xbdc9bf75,0xbe953f7f,0x3f22bf62,0xbf623f22,0x3f7fbe95,0xbf75bdc9,0x3f463ef1,
0xbf67be16,0x3f043f2c,0x3d49bf78,0xbf183f71,0x3eac3f4e,0x3e79bf80,0xbf3e3f5c,0x3f7dbedb,0x3edbbf7d,0xbf5c3f3e,0x3f80be79,0xbf4ebeac,0xbf713f18,0x3f78bd49,0xbf2cbf04,0x3e163f67,
0xbedb3f7d,0x3f5cbf3e,0xbf803e79,0x3f4e3eac,0x3f71bf18,0xbf783d49,0x3f2c3f04,0xbe16bf67,0xbf67be16,0x3f043f2c,0x3d49bf78,0xbf183f71,0x3eac3f4e,0x3e79bf80,0xbf3e3f5c,0x3f7dbedb,
0x3e483f55,0x3f0ebf7b,0xbf7b3f0e,0x3f553e48,0xbe48bf55,0xbf0e3f7b,0x3f7bbf0e,0xbf55be48,0x3e483f55,0x3f0ebf7b,0xbf7b3f0e,0x3f553e48,0xbe48bf55,0xbf0e3f7b,0x3f7bbf0e,0xbf55be48,
0xbf7b3f0e,0x3f553e48,0xbe48bf55,0xbf0e3f7b,0x3f7bbf0e,0xbf55be48,0x3e483f55,0x3f0ebf7b,0xbf7b3f0e,0x3f553e48,0xbe48bf55,0xbf0e3f7b,0x3f7bbf0e,0xbf55be48,0x3e483f55,0x3f0ebf7b,
0x3f2cbf78,0xbf7d3eac,0x3edb3f18,0x3f04bf80,0x3d493f5c,0x3f4ebf67,0xbf713e16,0x3e793f3e,0x3f3e3e79,0x3e16bf71,0xbf673f4e,0x3f5c3d49,0xbf803f04,0x3f183edb,0x3eacbf7d,0xbf783f2c,
0x3f3e3e79,0x3e16bf71,0xbf673f4e,0x3f5c3d49,0xbf803f04,0x3f183edb,0x3eacbf7d,0xbf783f2c,0xbf2c3f78,0x3f7dbeac,0xbedbbf18,0xbf043f80,0xbd49bf5c,0xbf4e3f67,0x3f71be16,0xbe79bf3e,
0x3dc9bf62,0xbf753f46,0x3f223e95,0x3ef1bf7f,0xbf7f3ef1,0x3e953f22,0x3f46bf75,0xbf623dc9,0xbdc93f62,0x3f75bf46,0xbf22be95,0xbef13f7f,0x3f7fbef1,0xbe95bf22,0xbf463f75,0x3f62bdc9,
0x3f7fbef1,0xbe95bf22,0xbf463f75,0x3f62bdc9,0x3dc9bf62,0xbf753f46,0x3f223e95,0x3ef1bf7f,0xbf7f3ef1,0x3e953f22,0x3f46bf75,0xbf623dc9,0xbdc93f62,0x3f75bf46,0xbf22be95,0xbef13f7f,
0x3f5cbf71,0xbf2cbe16,0xbf183f80,0x3f67be79,0x3f78bedb,0x3d49bf4e,0xbf7d3f3e,0x3eac3f04,0x3f043eac,0x3f3ebf7d,0xbf4e3d49,0xbedb3f78,0xbe793f67,0x3f80bf18,0xbe16bf2c,0xbf713f5c,
0x3f043eac,0x3f3ebf7d,0xbf4e3d49,0xbedb3f78,0xbe793f67,0x3f80bf18,0xbe16bf2c,0xbf713f5c,0xbf5c3f71,0x3f2c3e16,0x3f18bf80,0xbf673e79,0xbf783edb,0xbd493f4e,0x3f7dbf3e,0xbeacbf04,
0xbf6d3ec4,0xbec43f6d,0x3f6dbec4,0x3ec4bf6d,0xbf6d3ec4,0xbec43f6d,0x3f6dbec4,0x3ec4bf6d,0xbf6d3ec4,0xbec43f6d,0x3f6dbec4,0x3ec4bf6d,0xbf6d3ec4,0xbec43f6d,0x3f6dbec4,0x3ec4bf6d,
0xbec43f6d,0x3f6dbec4,0x3ec4bf6d,0xbf6d3ec4,0xbec43f6d,0x3f6dbec4,0x3ec4bf6d,0xbf6d3ec4,0xbec43f6d,0x3f6dbec4,0x3ec4bf6d,0xbf6d3ec4,0xbec43f6d,0x3f6dbec4,0x3ec4bf6d,0xbf6d3ec4,
0xbe79bedb,0xbf803f4e,0xbe163f3e,0x3f71bf04,0xbf5c3eac,0xbf2c3f7d,0x3f183d49,0x3f67bf78,0x3f78bf67,0xbd49bf18,0xbf7d3f2c,0xbeac3f5c,0x3f04bf71,0xbf3e3e16,0xbf4e3f80,0x3edb3e79,
0xbf783f67,0x3d493f18,0x3f7dbf2c,0x3eacbf5c,0xbf043f71,0x3f3ebe16,0x3f4ebf80,0xbedbbe79,0xbe79bedb,0xbf803f4e,0xbe163f3e,0x3f71bf04,0xbf5c3eac,0xbf2c3f7d,0x3f183d49,0x3f67bf78,
0x3f46be95,0x3f62bf7f,0xbdc9bef1,0xbf753f22,0xbf223f75,0x3ef13dc9,0x3f7fbf62,0x3e95bf46,0xbf463e95,0xbf623f7f,0x3dc93ef1,0x3f75bf22,0x3f22bf75,0xbef1bdc9,0xbf7f3f62,0xbe953f46,
0x3f22bf75,0xbef1bdc9,0xbf7f3f62,0xbe953f46,0x3f46be95,0x3f62bf7f,0xbdc9bef1,0xbf753f22,0xbf223f75,0x3ef13dc9,0x3f7fbf62,0x3e95bf46,0xbf463e95,0xbf623f7f,0x3dc93ef1,0x3f75bf22,
0x3d49bf04,0xbf4e3edb,0xbf713f7d,0xbe793f2c,0xbf3e3f78,0x3e163eac,0x3f67bf18,0x3f5cbf80,0x3f80bf5c,0x3f18bf67,0xbeacbe16,0xbf783f3e,0xbf2c3e79,0xbf7d3f71,0xbedb3f4e,0x3f04bd49,
0xbf803f5c,0xbf183f67,0x3eac3e16,0x3f78bf3e,0x3f2cbe79,0x3f7dbf71,0x3edbbf4e,0xbf043d49,0x3d49bf04,0xbf4e3edb,0xbf713f7d,0xbe793f2c,0xbf3e3f78,0x3e163eac,0x3f67bf18,0x3f5cbf80,
0xbf553f7b,0xbe483f0e,0x3f0ebe48,0x3f7bbf55,0x3f55bf7b,0x3e48bf0e,0xbf0e3e48,0xbf7b3f55,0xbf553f7b,0xbe483f0e,0x3f0ebe48,0x3f7bbf55,0x3f55bf7b,0x3e48bf0e,0xbf0e3e48,0xbf7b3f55,
0xbf0e3e48,0xbf7b3f55,0xbf553f7b,0xbe483f0e,0x3f0ebe48,0x3f7bbf55,0x3f55bf7b,0x3e48bf0e,0xbf0e3e48,0xbf7b3f55,0xbf553f7b,0xbe483f0e,0x3f0ebe48,0x3f7bbf55,0x3f55bf7b,0x3e48bf0e,
0x3f71bf4e,0x3f78bf80,0x3f2cbf5c,0x3e16bedb,0xbf673f7d,0xbf043f3e,0x3d493e79,0x3f18beac,0xbeac3f18,0x3e793d49,0x3f3ebf04,0x3f7dbf67,0xbedb3e16,0xbf5c3f2c,0xbf803f78,0xbf4e3f71,
0xbeac3f18,0x3e793d49,0x3f3ebf04,0x3f7dbf67,0xbedb3e16,0xbf5c3f2c,0xbf803f78,0xbf4e3f71,0xbf713f4e,0xbf783f80,0xbf2c3f5c,0xbe163edb,0x3f67bf7d,0x3f04bf3e,0xbd49be79,0xbf183eac,
0x3f75bf7f,0x3f46bf62,0x3ef1bf22,0x3dc9be95,0xbe953dc9,0xbf223ef1,0xbf623f46,0xbf7f3f75,0xbf753f7f,0xbf463f62,0xbef13f22,0xbdc93e95,0x3e95bdc9,0x3f22bef1,0x3f62bf46,0x3f7fbf75,
0x3e95bdc9,0x3f22bef1,0x3f62bf46,0x3f7fbf75,0x3f75bf7f,0x3f46bf62,0x3ef1bf22,0x3dc9be95,0xbe953dc9,0xbf223ef1,0xbf623f46,0xbf7f3f75,0xbf753f7f,0xbf463f62,0xbef13f22,0xbdc93e95,
0x3f4ebf3e,0x3f67bf5c,0x3f78bf71,0x3f80bf7d,0x3e16bd49,0x3eacbe79,0x3f04bedb,0x3f2cbf18,0xbf183f2c,0xbedb3f04,0xbe793eac,0xbd493e16,0xbf7d3f80,0xbf713f78,0xbf5c3f67,0xbf3e3f4e,
0xbf183f2c,0xbedb3f04,0xbe793eac,0xbd493e16,0xbf7d3f80,0xbf713f78,0xbf5c3f67,0xbf3e3f4e,0xbf4e3f3e,0xbf673f5c,0xbf783f71,0xbf803f7d,0xbe163d49,0xbeac3e79,0xbf043edb,0xbf2c3f18,
0xa554248d,0xa5f725b0,0xa731261f,0xa742a68d,0xa754a654,0xa765a60d,0xa777a58e,0xa784a137,0xa78d258d,0xa796260d,0xa79f280d,0x2731268d,0xa7b12816,0x270d26d4,0xa7c2281f,0x26d4270d,
0xbf803f80,0xbf803f80,0xbf803f80,0xbf803f80,0xbf803f80,0xbf803f80,0xbf803f80,0xbf803f80,0xbf803f80,0xbf803f80,0xbf803f80,0xbf803f80,0xbf803f80,0xbf803f80,0xbf803f80,0xbf803f80,
0x3f4ebf3e,0x3f67bf5c,0x3f78bf71,0x3f80bf7d,0x3e16bd49,0x3eacbe79,0x3f04bedb,0x3f2cbf18,0x3f18bf2c,0x3edbbf04,0x3e79beac,0x3d49be16,0x3f7dbf80,0x3f71bf78,0x3f5cbf67,0x3f3ebf4e,
0xbf183f2c,0xbedb3f04,0xbe793eac,0xbd493e16,0xbf7d3f80,0xbf713f78,0xbf5c3f67,0xbf3e3f4e,0x3f4ebf3e,0x3f67bf5c,0x3f78bf71,0x3f80bf7d,0x3e16bd49,0x3eacbe79,0x3f04bedb,0x3f2cbf18,
0xbe953dc9,0xbf223ef1,0xbf623f46,0xbf7f3f75,0xbf753f7f,0xbf463f62,0xbef13f22,0xbdc93e95,0x3e95bdc9,0x3f22bef1,0x3f62bf46,0x3f7fbf75,0x3f75bf7f,0x3f46bf62,0x3ef1bf22,0x3dc9be95,
0x3f75bf7f,0x3f46bf62,0x3ef1bf22,0x3dc9be95,0xbe953dc9,0xbf223ef1,0xbf623f46,0xbf7f3f75,0xbf753f7f,0xbf463f62,0xbef13f22,0xbdc93e95,0x3e95bdc9,0x3f22bef1,0x3f62bf46,0x3f7fbf75,
0x3f71bf4e,0x3f78bf80,0x3f2cbf5c,0x3e16bedb,0xbf673f7d,0xbf043f3e,0x3d493e79,0x3f18beac,0x3eacbf18,0xbe79bd49,0xbf3e3f04,0xbf7d3f67,0x3edbbe16,0x3f5cbf2c,0x3f80bf78,0x3f4ebf71,
0xbeac3f18,0x3e793d49,0x3f3ebf04,0x3f7dbf67,0xbedb3e16,0xbf5c3f2c,0xbf803f78,0xbf4e3f71,0x3f71bf4e,0x3f78bf80,0x3f2cbf5c,0x3e16bedb,0xbf673f7d,0xbf043f3e,0x3d493e79,0x3f18beac,
0xbf553f7b,0xbe483f0e,0x3f0ebe48,0x3f7bbf55,0x3f55bf7b,0x3e48bf0e,0xbf0e3e48,0xbf7b3f55,0xbf553f7b,0xbe483f0e,0x3f0ebe48,0x3f7bbf55,0x3f55bf7b,0x3e48bf0e,0xbf0e3e48,0xbf7b3f55,
0x3f0ebe48,0x3f7bbf55,0x3f55bf7b,0x3e48bf0e,0xbf0e3e48,0xbf7b3f55,0xbf553f7b,0xbe483f0e,0x3f0ebe48,0x3f7bbf55,0x3f55bf7b,0x3e48bf0e,0xbf0e3e48,0xbf7b3f55,0xbf553f7b,0xbe483f0e,
0x3d49bf04,0xbf4e3edb,0xbf713f7d,0xbe793f2c,0xbf3e3f78,0x3e163eac,0x3f67bf18,0x3f5cbf80,0xbf803f5c,0xbf183f67,0x3eac3e16,0x3f78bf3e,0x3f2cbe79,0x3f7dbf71,0x3edbbf4e,0xbf043d49,
0xbf803f5c,0xbf183f67,0x3eac3e16,0x3f78bf3e,0x3f2cbe79,0x3f7dbf71,0x3edbbf4e,0xbf043d49,0xbd493f04,0x3f4ebedb,0x3f71bf7d,0x3e79bf2c,0x3f3ebf78,0xbe16beac,0xbf673f18,0xbf5c3f80,
0x3f22bf75,0xbef1bdc9,0xbf7f3f62,0xbe953f46,0x3f46be95,0x3f62bf7f,0xbdc9bef1,0xbf753f22,0xbf223f75,0x3ef13dc9,0x3f7fbf62,0x3e95bf46,0xbf463e95,0xbf623f7f,0x3dc93ef1,0x3f75bf22,
0xbf463e95,0xbf623f7f,0x3dc93ef1,0x3f75bf22,0x3f22bf75,0xbef1bdc9,0xbf7f3f62,0xbe953f46,0x3f46be95,0x3f62bf7f,0xbdc9bef1,0xbf753f22,0xbf223f75,0x3ef13dc9,0x3f7fbf62,0x3e95bf46,
0xbe79bedb,0xbf803f4e,0xbe163f3e,0x3f71bf04,0xbf5c3eac,0xbf2c3f7d,0x3f183d49,0x3f67bf78,0xbf783f67,0x3d493f18,0x3f7dbf2c,0x3eacbf5c,0xbf043f71,0x3f3ebe16,0x3f4ebf80,0xbedbbe79,
0xbf783f67,0x3d493f18,0x3f7dbf2c,0x3eacbf5c,0xbf043f71,0x3f3ebe16,0x3f4ebf80,0xbedbbe79,0x3e793edb,0x3f80bf4e,0x3e16bf3e,0xbf713f04,0x3f5cbeac,0x3f2cbf7d,0xbf18bd49,0xbf673f78,
0x3f6dbec4,0x3ec4bf6d,0xbf6d3ec4,0xbec43f6d,0x3f6dbec4,0x3ec4bf6d,0xbf6d3ec4,0xbec43f6d,0x3f6dbec4,0x3ec4bf6d,0xbf6d3ec4,0xbec43f6d,0x3f6dbec4,0x3ec4bf6d,0xbf6d3ec4,0xbec43f6d,
0xbec43f6d,0x3f6dbec4,0x3ec4bf6d,0xbf6d3ec4,0xbec43f6d,0x3f6dbec4,0x3ec4bf6d,0xbf6d3ec4,0xbec43f6d,0x3f6dbec4,0x3ec4bf6d,0xbf6d3ec4,0xbec43f6d,0x3f6dbec4,0x3ec4bf6d,0xbf6d3ec4,
0x3f5cbf71,0xbf2cbe16,0xbf183f80,0x3f67be79,0x3f78bedb,0x3d49bf4e,0xbf7d3f3e,0x3eac3f04,0xbf04beac,0xbf3e3f7d,0x3f4ebd49,0x3edbbf78,0x3e79bf67,0xbf803f18,0x3e163f2c,0x3f71bf5c,
0x3f043eac,0x3f3ebf7d,0xbf4e3d49,0xbedb3f78,0xbe793f67,0x3f80bf18,0xbe16bf2c,0xbf713f5c,0x3f5cbf71,0xbf2cbe16,0xbf183f80,0x3f67be79,0x3f78bedb,0x3d49bf4e,0xbf7d3f3e,0x3eac3f04,
0xbf7f3ef1,0x3e953f22,0x3f46bf75,0xbf623dc9,0xbdc93f62,0x3f75bf46,0xbf22be95,0xbef13f7f,0x3f7fbef1,0xbe95bf22,0xbf463f75,0x3f62bdc9,0x3dc9bf62,0xbf753f46,0x3f223e95,0x3ef1bf7f,
0x3dc9bf62,0xbf753f46,0x3f223e95,0x3ef1bf7f,0xbf7f3ef1,0x3e953f22,0x3f46bf75,0xbf623dc9,0xbdc93f62,0x3f75bf46,0xbf22be95,0xbef13f7f,0x3f7fbef1,0xbe95bf22,0xbf463f75,0x3f62bdc9,
0x3f2cbf78,0xbf7d3eac,0x3edb3f18,0x3f04bf80,0x3d493f5c,0x3f4ebf67,0xbf713e16,0x3e793f3e,0xbf3ebe79,0xbe163f71,0x3f67bf4e,0xbf5cbd49,0x3f80bf04,0xbf18bedb,0xbeac3f7d,0x3f78bf2c,
0x3f3e3e79,0x3e16bf71,0xbf673f4e,0x3f5c3d49,0xbf803f04,0x3f183edb,0x3eacbf7d,0xbf783f2c,0x3f2cbf78,0xbf7d3eac,0x3edb3f18,0x3f04bf80,0x3d493f5c,0x3f4ebf67,0xbf713e16,0x3e793f3e,
0x3e483f55,0x3f0ebf7b,0xbf7b3f0e,0x3f553e48,0xbe48bf55,0xbf0e3f7b,0x3f7bbf0e,0xbf55be48,0x3e483f55,0x3f0ebf7b,0xbf7b3f0e,0x3f553e48,0xbe48bf55,0xbf0e3f7b,0x3f7bbf0e,0xbf55be48,
0x3f7bbf0e,0xbf55be48,0x3e483f55,0x3f0ebf7b,0xbf7b3f0e,0x3f553e48,0xbe48bf55,0xbf0e3f7b,0x3f7bbf0e,0xbf55be48,0x3e483f55,0x3f0ebf7b,0xbf7b3f0e,0x3f553e48,0xbe48bf55,0xbf0e3f7b,
0xbf67be16,0x3f043f2c,0x3d49bf78,0xbf183f71,0x3eac3f4e,0x3e79bf80,0xbf3e3f5c,0x3f7dbedb,0xbedb3f7d,0x3f5cbf3e,0xbf803e79,0x3f4e3eac,0x3f71bf18,0xbf783d49,0x3f2c3f04,0xbe16bf67,
0xbedb3f7d,0x3f5cbf3e,0xbf803e79,0x3f4e3eac,0x3f71bf18,0xbf783d49,0x3f2c3f04,0xbe16bf67,0x3f673e16,0xbf04bf2c,0xbd493f78,0x3f18bf71,0xbeacbf4e,0xbe793f80,0x3f3ebf5c,0xbf7d3edb,
0xbef1bf46,0x3dc93f75,0x3e95bf7f,0xbf223f62,0x3f62bf22,0xbf7f3e95,0x3f753dc9,0xbf46bef1,0x3ef13f46,0xbdc9bf75,0xbe953f7f,0x3f22bf62,0xbf623f22,0x3f7fbe95,0xbf75bdc9,0x3f463ef1,
0xbf623f22,0x3f7fbe95,0xbf75bdc9,0x3f463ef1,0xbef1bf46,0x3dc93f75,0x3e95bf7f,0xbf223f62,0x3f62bf22,0xbf7f3e95,0x3f753dc9,0xbf46bef1,0x3ef13f46,0xbdc9bf75,0xbe953f7f,0x3f22bf62,
0xbf7dbd49,0x3f713e79,0xbf5cbedb,0x3f3e3f18,0xbf4e3f2c,0x3f67bf04,0xbf783eac,0x3f80be16,0xbe163f80,0x3eacbf78,0xbf043f67,0x3f2cbf4e,0x3f183f3e,0xbedbbf5c,0x3e793f71,0xbd49bf7d,
0xbe163f80,0x3eacbf78,0xbf043f67,0x3f2cbf4e,0x3f183f3e,0xbedbbf5c,0x3e793f71,0xbd49bf7d,0x3f7d3d49,0xbf71be79,0x3f5c3edb,0xbf3ebf18,0x3f4ebf2c,0xbf673f04,0x3f78beac,0xbf803e16,
0x3f35bf35,0xbf353f35,0x3f35bf35,0xbf353f35,0x3f35bf35,0xbf353f35,0x3f35bf35,0xbf353f35,0x3f35bf35,0xbf353f35,0x3f35bf35,0xbf353f35,0x3f35bf35,0xbf353f35,0x3f35bf35,0xbf353f35,
0x3f353f35,0xbf35bf35,0x3f353f35,0xbf35bf35,0x3f353f35,0xbf35bf35,0x3f353f35,0xbf35bf35,0x3f353f35,0xbf35bf35,0x3f353f35,0xbf35bf35,0x3f353f35,0xbf35bf35,0x3f353f35,0xbf35bf35,
0xbe16bf80,0x3eac3f78,0xbf04bf67,0x3f2c3f4e,0x3f18bf3e,0xbedb3f5c,0x3e79bf71,0xbd493f7d,0xbf7d3d49,0x3f71be79,0xbf5c3edb,0x3f3ebf18,0xbf4ebf2c,0x3f673f04,0xbf78beac,0x3f803e16,
0x3f7dbd49,0xbf713e79,0x3f5cbedb,0xbf3e3f18,0x3f4e3f2c,0xbf67bf04,0x3f783eac,0xbf80be16,0xbe16bf80,0x3eac3f78,0xbf04bf67,0x3f2c3f4e,0x3f18bf3e,0xbedb3f5c,0x3e79bf71,0xbd493f7d,
0xbef13f46,0x3dc9bf75,0x3e953f7f,0xbf22bf62,0x3f623f22,0xbf7fbe95,0x3f75bdc9,0xbf463ef1,0x3ef1bf46,0xbdc93f75,0xbe95bf7f,0x3f223f62,0xbf62bf22,0x3f7f3e95,0xbf753dc9,0x3f46bef1,
0xbf62bf22,0x3f7f3e95,0xbf753dc9,0x3f46bef1,0xbef13f46,0x3dc9bf75,0x3e953f7f,0xbf22bf62,0x3f623f22,0xbf7fbe95,0x3f75bdc9,0xbf463ef1,0x3ef1bf46,0xbdc93f75,0xbe95bf7f,0x3f223f62,
0xbedbbf7d,0x3f5c3f3e,0xbf80be79,0x3f4ebeac,0x3f713f18,0xbf78bd49,0x3f2cbf04,0xbe163f67,0xbf673e16,0x3f04bf2c,0x3d493f78,0xbf18bf71,0x3eacbf4e,0x3e793f80,0xbf3ebf5c,0x3f7d3edb,
0x3f67be16,0xbf043f2c,0xbd49bf78,0x3f183f71,0xbeac3f4e,0xbe79bf80,0x3f3e3f5c,0xbf7dbedb,0xbedbbf7d,0x3f5c3f3e,0xbf80be79,0x3f4ebeac,0x3f713f18,0xbf78bd49,0x3f2cbf04,0xbe163f67,
0x3f7b3f0e,0xbf553e48,0x3e48bf55,0x3f0e3f7b,0xbf7bbf0e,0x3f55be48,0xbe483f55,0xbf0ebf7b,0x3f7b3f0e,0xbf553e48,0x3e48bf55,0x3f0e3f7b,0xbf7bbf0e,0x3f55be48,0xbe483f55,0xbf0ebf7b,
0x3e48bf55,0x3f0e3f7b,0xbf7bbf0e,0x3f55be48,0xbe483f55,0xbf0ebf7b,0x3f7b3f0e,0xbf553e48,0x3e48bf55,0x3f0e3f7b,0xbf7bbf0e,0x3f55be48,0xbe483f55,0xbf0ebf7b,0x3f7b3f0e,0xbf553e48,
0xbf3e3e79,0xbe16bf71,0x3f673f4e,0xbf5c3d49,0x3f803f04,0xbf183edb,0xbeacbf7d,0x3f783f2c,0x3f2c3f78,0xbf7dbeac,0x3edbbf18,0x3f043f80,0x3d49bf5c,0x3f4e3f67,0xbf71be16,0x3e79bf3e,
0x3f2c3f78,0xbf7dbeac,0x3edbbf18,0x3f043f80,0x3d49bf5c,0x3f4e3f67,0xbf71be16,0x3e79bf3e,0x3f3ebe79,0x3e163f71,0xbf67bf4e,0x3f5cbd49,0xbf80bf04,0x3f18bedb,0x3eac3f7d,0xbf78bf2c,
0xbf7fbef1,0x3e95bf22,0x3f463f75,0xbf62bdc9,0xbdc9bf62,0x3f753f46,0xbf223e95,0xbef1bf7f,0x3f7f3ef1,0xbe953f22,0xbf46bf75,0x3f623dc9,0x3dc93f62,0xbf75bf46,0x3f22be95,0x3ef13f7f,
0x3dc93f62,0xbf75bf46,0x3f22be95,0x3ef13f7f,0xbf7fbef1,0x3e95bf22,0x3f463f75,0xbf62bdc9,0xbdc9bf62,0x3f753f46,0xbf223e95,0xbef1bf7f,0x3f7f3ef1,0xbe953f22,0xbf46bf75,0x3f623dc9,
0xbf043eac,0xbf3ebf7d,0x3f4e3d49,0x3edb3f78,0x3e793f67,0xbf80bf18,0x3e16bf2c,0x3f713f5c,0x3f5c3f71,0xbf2c3e16,0xbf18bf80,0x3f673e79,0x3f783edb,0x3d493f4e,0xbf7dbf3e,0x3eacbf04,
0x3f5c3f71,0xbf2c3e16,0xbf18bf80,0x3f673e79,0x3f783edb,0x3d493f4e,0xbf7dbf3e,0x3eacbf04,0x3f04beac,0x3f3e3f7d,0xbf4ebd49,0xbedbbf78,0xbe79bf67,0x3f803f18,0xbe163f2c,0xbf71bf5c,
0xbec4bf6d,0x3f6d3ec4,0x3ec43f6d,0xbf6dbec4,0xbec4bf6d,0x3f6d3ec4,0x3ec43f6d,0xbf6dbec4,0xbec4bf6d,0x3f6d3ec4,0x3ec43f6d,0xbf6dbec4,0xbec4bf6d,0x3f6d3ec4,0x3ec43f6d,0xbf6dbec4,
0x3f6d3ec4,0x3ec43f6d,0xbf6dbec4,0xbec4bf6d,0x3f6d3ec4,0x3ec43f6d,0xbf6dbec4,0xbec4bf6d,0x3f6d3ec4,0x3ec43f6d,0xbf6dbec4,0xbec4bf6d,0x3f6d3ec4,0x3ec43f6d,0xbf6dbec4,0xbec4bf6d,
0xbf78bf67,0x3d49bf18,0x3f7d3f2c,0x3eac3f5c,0xbf04bf71,0x3f3e3e16,0x3f4e3f80,0xbedb3e79,0xbe793edb,0xbf80bf4e,0xbe16bf3e,0x3f713f04,0xbf5cbeac,0xbf2cbf7d,0x3f18bd49,0x3f673f78,
0x3e79bedb,0x3f803f4e,0x3e163f3e,0xbf71bf04,0x3f5c3eac,0x3f2c3f7d,0xbf183d49,0xbf67bf78,0xbf78bf67,0x3d49bf18,0x3f7d3f2c,0x3eac3f5c,0xbf04bf71,0x3f3e3e16,0x3f4e3f80,0xbedb3e79,
0x3f223f75,0xbef13dc9,0xbf7fbf62,0xbe95bf46,0x3f463e95,0x3f623f7f,0xbdc93ef1,0xbf75bf22,0xbf22bf75,0x3ef1bdc9,0x3f7f3f62,0x3e953f46,0xbf46be95,0xbf62bf7f,0x3dc9bef1,0x3f753f22,
0xbf46be95,0xbf62bf7f,0x3dc9bef1,0x3f753f22,0x3f223f75,0xbef13dc9,0xbf7fbf62,0xbe95bf46,0x3f463e95,0x3f623f7f,0xbdc93ef1,0xbf75bf22,0xbf22bf75,0x3ef1bdc9,0x3f7f3f62,0x3e953f46,
0xbf80bf5c,0xbf18bf67,0x3eacbe16,0x3f783f3e,0x3f2c3e79,0x3f7d3f71,0x3edb3f4e,0xbf04bd49,0x3d493f04,0xbf4ebedb,0xbf71bf7d,0xbe79bf2c,0xbf3ebf78,0x3e16beac,0x3f673f18,0x3f5c3f80,
0xbd49bf04,0x3f4e3edb,0x3f713f7d,0x3e793f2c,0x3f3e3f78,0xbe163eac,0xbf67bf18,0xbf5cbf80,0xbf80bf5c,0xbf18bf67,0x3eacbe16,0x3f783f3e,0x3f2c3e79,0x3f7d3f71,0x3edb3f4e,0xbf04bd49,
0x3f0e3e48,0x3f7b3f55,0x3f553f7b,0x3e483f0e,0xbf0ebe48,0xbf7bbf55,0xbf55bf7b,0xbe48bf0e,0x3f0e3e48,0x3f7b3f55,0x3f553f7b,0x3e483f0e,0xbf0ebe48,0xbf7bbf55,0xbf55bf7b,0xbe48bf0e,
0xbf55bf7b,0xbe48bf0e,0x3f0e3e48,0x3f7b3f55,0x3f553f7b,0x3e483f0e,0xbf0ebe48,0xbf7bbf55,0xbf55bf7b,0xbe48bf0e,0x3f0e3e48,0x3f7b3f55,0x3f553f7b,0x3e483f0e,0xbf0ebe48,0xbf7bbf55,
0x3eac3f18,0xbe793d49,0xbf3ebf04,0xbf7dbf67,0x3edb3e16,0x3f5c3f2c,0x3f803f78,0x3f4e3f71,0x3f713f4e,0x3f783f80,0x3f2c3f5c,0x3e163edb,0xbf67bf7d,0xbf04bf3e,0x3d49be79,0x3f183eac,
0x3f713f4e,0x3f783f80,0x3f2c3f5c,0x3e163edb,0xbf67bf7d,0xbf04bf3e,0x3d49be79,0x3f183eac,0xbeacbf18,0x3e79bd49,0x3f3e3f04,0x3f7d3f67,0xbedbbe16,0xbf5cbf2c,0xbf80bf78,0xbf4ebf71,
0xbe95bdc9,0xbf22bef1,0xbf62bf46,0xbf7fbf75,0xbf75bf7f,0xbf46bf62,0xbef1bf22,0xbdc9be95,0x3e953dc9,0x3f223ef1,0x3f623f46,0x3f7f3f75,0x3f753f7f,0x3f463f62,0x3ef13f22,0x3dc93e95,
0x3f753f7f,0x3f463f62,0x3ef13f22,0x3dc93e95,0xbe95bdc9,0xbf22bef1,0xbf62bf46,0xbf7fbf75,0xbf75bf7f,0xbf46bf62,0xbef1bf22,0xbdc9be95,0x3e953dc9,0x3f223ef1,0x3f623f46,0x3f7f3f75,
0x3f183f2c,0x3edb3f04,0x3e793eac,0x3d493e16,0x3f7d3f80,0x3f713f78,0x3f5c3f67,0x3f3e3f4e,0x3f4e3f3e,0x3f673f5c,0x3f783f71,0x3f803f7d,0x3e163d49,0x3eac3e79,0x3f043edb,0x3f2c3f18,
0x3f4e3f3e,0x3f673f5c,0x3f783f71,0x3f803f7d,0x3e163d49,0x3eac3e79,0x3f043edb,0x3f2c3f18,0xbf18bf2c,0xbedbbf04,0xbe79beac,0xbd49be16,0xbf7dbf80,0xbf71bf78,0xbf5cbf67,0xbf3ebf4e,
0x38fb37c9,0x39a13960,0x39fc39cf,0x3a273a13,0xba7eba80,0xba73ba7a,0xba5fba6a,0xba42ba51,0x3a4a3a39,0x3a653a58,0x3a773a6f,0x3a7f3a7c,0xba1dba31,0xb9e6ba09,0xb989b9b8,0xb897b92f,
0x3a7e3a80,0x3a733a7a,0x3a5f3a6a,0x3a423a51,0x38fb37c9,0x39a13960,0x39fc39cf,0x3a273a13,0x3a1d3a31,0x39e63a09,0x398939b8,0x3897392f,0x3a4a3a39,0x3a653a58,0x3a773a6f,0x3a7f3a7c,
0xba6fba7f,0xba13ba4a,0xb7c9b9a1,0x3a093989,0x39b83897,0x3a513a1d,0x3a803a73,0x3a583a77,0x3a6a3a42,0x3a7c3a7e,0x3a393a65,0x396039fc,0x39cf3a27,0xb92f38fb,0xba31b9e6,0xba7aba5f,
0xb9b8b897,0xba51ba1d,0xba80ba73,0xba58ba77,0xba6fba7f,0xba13ba4a,0xb7c9b9a1,0x3a093989,0xb9cfba27,0x392fb8fb,0x3a3139e6,0x3a7a3a5f,0x3a6a3a42,0x3a7c3a7e,0x3a393a65,0x396039fc,
0xba7cba4a,0xba31ba73,0x3960b989,0x3a6f3a27,0x392f3a1d,0xba39b9a1,0xba7aba77,0xb9b8ba42,0x3a1338fb,0x3a803a65,0x3a093a5f,0xb9cf3897,0xba51ba7e,0x37c9b9e6,0x3a5839fc,0x3a6a3a7f,
0xb92fba1d,0x3a3939a1,0x3a7a3a77,0x39b83a42,0xba7cba4a,0xba31ba73,0x3960b989,0x3a6f3a27,0x3a513a7e,0xb7c939e6,0xba58b9fc,0xba6aba7f,0x3a1338fb,0x3a803a65,0x3a093a5f,0xb9cf3897,
0xba7fba51,0xb8fbba39,0x3a733a09,0x39fc3a6f,0x3897ba13,0x3a7e3a31,0x39a13a58,0xba5fb9b8,0xba27ba7c,0x3a1db7c9,0x3a653a7a,0xb98939cf,0x3a42392f,0x3a4a3a80,0xb9e63960,0xba77ba6a,
0xb8973a13,0xba7eba31,0xb9a1ba58,0x3a5f39b8,0xba7fba51,0xb8fbba39,0x3a733a09,0x39fc3a6f,0xba42b92f,0xba4aba80,0x39e6b960,0x3a773a6a,0xba27ba7c,0x3a1db7c9,0x3a653a7a,0xb98939cf,
0x39e63a7a,0xba77b9cf,0xb897ba51,0x3a7e3a39,0x3a653960,0x39893a6a,0xba7fba13,0x38fbba31,0xb9a13a09,0xba5fba6f,0x3a27b92f,0x3a1d3a80,0x3a733a58,0xb9fc39b8,0xba42ba7c,0x3a4a37c9,
0x3a653960,0x39893a6a,0xba7fba13,0x38fbba31,0xb9e6ba7a,0x3a7739cf,0x38973a51,0xba7eba39,0x3a733a58,0xb9fc39b8,0xba42ba7c,0x3a4a37c9,0x39a1ba09,0x3a5f3a6f,0xba27392f,0xba1dba80,
0xba7ab989,0x39b8ba27,0x3a133a7e,0xba80b9e6,0xb960ba77,0x3a6f3a42,0xba5138fb,0xb7c9ba65,0x3a09b9fc,0x39cf3a7f,0xba7cba1d,0x3a31b9a1,0x3a583a5f,0xba6ab897,0x392fba4a,0x3a393a73,
0xb960ba77,0x3a6f3a42,0xba5138fb,0xb7c9ba65,0x3a7a3989,0xb9b83a27,0xba13ba7e,0x3a8039e6,0x3a583a5f,0xba6ab897,0x392fba4a,0x3a393a73,0xba0939fc,0xb9cfba7f,0x3a7c3a1d,0xba3139a1,
0x3a39b9e6,0xb9603a5f,0xb9b8ba7f,0x3a513a4a,0xba31ba65,0x3a7a39fc,0xba6f3897,0x3a13ba1d,0xb7c93a73,0xba09ba77,0x3a6a3a27,0xba7cb8fb,0x3a8039a1,0xba583989,0x39cfba42,0x392f3a7e,
0xba31ba65,0x3a7a39fc,0xba6f3897,0x3a13ba1d,0xba3939e6,0x3960ba5f,0x39b83a7f,0xba51ba4a,0x3a8039a1,0xba583989,0x39cfba42,0x392f3a7e,0x37c9ba73,0x3a093a77,0xba6aba27,0x3a7c38fb,
0xba5f39cf,0x3a42ba13,0xba1d3a39,0x39e6ba58,0xb9fcba6a,0x3a273a51,0xba4aba31,0x3a653a09,0xba77b9b8,0x3a7f392f,0xba7e37c9,0x3a73b960,0x3989ba6f,0xb8973a7c,0xb8fbba80,0x39a13a7a,
0xb9fcba6a,0x3a273a51,0xba4aba31,0x3a653a09,0x3a5fb9cf,0xba423a13,0x3a1dba39,0xb9e63a58,0x3989ba6f,0xb8973a7c,0xb8fbba80,0x39a13a7a,0x3a7739b8,0xba7fb92f,0x3a7eb7c9,0xba733960,
0x3a5f39cf,0xba42ba13,0x3a1d3a39,0xb9e6ba58,0x39fcba6a,0xba273a51,0x3a4aba31,0xba653a09,0x39893a6f,0xb897ba7c,0xb8fb3a80,0x39a1ba7a,0x3a77b9b8,0xba7f392f,0x3a7e37c9,0xba73b960,
0xb9fc3a6a,0x3a27ba51,0xba4a3a31,0x3a65ba09,0x3a5f39cf,0xba42ba13,0x3a1d3a39,0xb9e6ba58,0xba7739b8,0x3a7fb92f,0xba7eb7c9,0x3a733960,0x39893a6f,0xb897ba7c,0xb8fb3a80,0x39a1ba7a,
0x3a31ba65,0xba7a39fc,0x3a6f3897,0xba13ba1d,0x3a3939e6,0xb960ba5f,0xb9b83a7f,0x3a51ba4a,0x37c93a73,0x3a09ba77,0xba6a3a27,0x3a7cb8fb,0xba8039a1,0x3a583989,0xb9cfba42,0xb92f3a7e,
0xba39b9e6,0x39603a5f,0x39b8ba7f,0xba513a4a,0x3a31ba65,0xba7a39fc,0x3a6f3897,0xba13ba1d,0x3a80b9a1,0xba58b989,0x39cf3a42,0x392fba7e,0x37c93a73,0x3a09ba77,0xba6a3a27,0x3a7cb8fb,
0x3960ba77,0xba6f3a42,0x3a5138fb,0x37c9ba65,0xba7a3989,0x39b83a27,0x3a13ba7e,0xba8039e6,0x3a0939fc,0x39cfba7f,0xba7c3a1d,0x3a3139a1,0x3a58ba5f,0xba6a3897,0x392f3a4a,0x3a39ba73,
0x3a7ab989,0xb9b8ba27,0xba133a7e,0x3a80b9e6,0x3960ba77,0xba6f3a42,0x3a5138fb,0x37c9ba65,0xba583a5f,0x3a6ab897,0xb92fba4a,0xba393a73,0x3a0939fc,0x39cfba7f,0xba7c3a1d,0x3a3139a1,
0x39e6ba7a,0xba7739cf,0xb8973a51,0x3a7eba39,0x3a65b960,0x3989ba6a,0xba7f3a13,0x38fb3a31,0x3a73ba58,0xb9fcb9b8,0xba423a7c,0x3a4ab7c9,0x39a13a09,0x3a5fba6f,0xba27b92f,0xba1d3a80,
0xba653960,0xb9893a6a,0x3a7fba13,0xb8fbba31,0x39e6ba7a,0xba7739cf,0xb8973a51,0x3a7eba39,0xb9a1ba09,0xba5f3a6f,0x3a27392f,0x3a1dba80,0x3a73ba58,0xb9fcb9b8,0xba423a7c,0x3a4ab7c9,
0xba7f3a51,0xb8fb3a39,0x3a73ba09,0x39fcba6f,0x38973a13,0x3a7eba31,0x39a1ba58,0xba5f39b8,0xba42392f,0xba4a3a80,0x39e63960,0x3a77ba6a,0xba273a7c,0x3a1d37c9,0x3a65ba7a,0xb989b9cf,
0x38973a13,0x3a7eba31,0x39a1ba58,0xba5f39b8,0x3a7fba51,0x38fbba39,0xba733a09,0xb9fc3a6f,0xba273a7c,0x3a1d37c9,0x3a65ba7a,0xb989b9cf,0x3a42b92f,0x3a4aba80,0xb9e6b960,0xba773a6a,
0x392fba1d,0xba3939a1,0xba7a3a77,0xb9b83a42,0x3a7cba4a,0x3a31ba73,0xb960b989,0xba6f3a27,0x3a13b8fb,0x3a80ba65,0x3a09ba5f,0xb9cfb897,0xba513a7e,0x37c939e6,0x3a58b9fc,0x3a6aba7f,
0x3a7cba4a,0x3a31ba73,0xb960b989,0xba6f3a27,0xb92f3a1d,0x3a39b9a1,0x3a7aba77,0x39b8ba42,0xba513a7e,0x37c939e6,0x3a58b9fc,0x3a6aba7f,0xba1338fb,0xba803a65,0xba093a5f,0x39cf3897,
0x39b8b897,0x3a51ba1d,0x3a80ba73,0x3a58ba77,0x3a6fba7f,0x3a13ba4a,0x37c9b9a1,0xba093989,0xba6a3a42,0xba7c3a7e,0xba393a65,0xb96039fc,0xb9cf3a27,0x392f38fb,0x3a31b9e6,0x3a7aba5f,
0x3a6fba7f,0x3a13ba4a,0x37c9b9a1,0xba093989,0xb9b83897,0xba513a1d,0xba803a73,0xba583a77,0xb9cf3a27,0x392f38fb,0x3a31b9e6,0x3a7aba5f,0x3a6aba42,0x3a7cba7e,0x3a39ba65,0x3960b9fc,
0xb8fb37c9,0xb9a13960,0xb9fc39cf,0xba273a13,0x3a7eba80,0x3a73ba7a,0x3a5fba6a,0x3a42ba51,0x3a1dba31,0x39e6ba09,0x3989b9b8,0x3897b92f,0x3a4aba39,0x3a65ba58,0x3a77ba6f,0x3a7fba7c,
0x3a7eba80,0x3a73ba7a,0x3a5fba6a,0x3a42ba51,0x38fbb7c9,0x39a1b960,0x39fcb9cf,0x3a27ba13,0x3a4aba39,0x3a65ba58,0x3a77ba6f,0x3a7fba7c,0xba1d3a31,0xb9e63a09,0xb98939b8,0xb897392f,
0xba4a3a39,0xba653a58,0xba773a6f,0xba7f3a7c,0x3a1dba31,0x39e6ba09,0x3989b9b8,0x3897b92f,0xba7e3a80,0xba733a7a,0xba5f3a6a,0xba423a51,0xb8fb37c9,0xb9a13960,0xb9fc39cf,0xba273a13,
0xba1d3a31,0xb9e63a09,0xb98939b8,0xb897392f,0xba4a3a39,0xba653a58,0xba773a6f,0xba7f3a7c,0x38fbb7c9,0x39a1b960,0x39fcb9cf,0x3a27ba13,0xba7e3a80,0xba733a7a,0xba5f3a6a,0xba423a51,
0x39cfba27,0xb92fb8fb,0xba3139e6,0xba7a3a5f,0xba6a3a42,0xba7c3a7e,0xba393a65,0xb96039fc,0xba6f3a7f,0xba133a4a,0xb7c939a1,0x3a09b989,0x39b8b897,0x3a51ba1d,0x3a80ba73,0x3a58ba77,
0x3a6aba42,0x3a7cba7e,0x3a39ba65,0x3960b9fc,0x39cfba27,0xb92fb8fb,0xba3139e6,0xba7a3a5f,0xb9b83897,0xba513a1d,0xba803a73,0xba583a77,0xba6f3a7f,0xba133a4a,0xb7c939a1,0x3a09b989,
0x3a51ba7e,0xb7c9b9e6,0xba5839fc,0xba6a3a7f,0x3a13b8fb,0x3a80ba65,0x3a09ba5f,0xb9cfb897,0xba7c3a4a,0xba313a73,0x39603989,0x3a6fba27,0x392fba1d,0xba3939a1,0xba7a3a77,0xb9b83a42,
0xba1338fb,0xba803a65,0xba093a5f,0x39cf3897,0x3a51ba7e,0xb7c9b9e6,0xba5839fc,0xba6a3a7f,0xb92f3a1d,0x3a39b9a1,0x3a7aba77,0x39b8ba42,0xba7c3a4a,0xba313a73,0x39603989,0x3a6fba27,
0x3a27ba7c,0xba1db7c9,0xba653a7a,0x398939cf,0xba42392f,0xba4a3a80,0x39e63960,0x3a77ba6a,0xb897ba13,0xba7e3a31,0xb9a13a58,0x3a5fb9b8,0xba7f3a51,0xb8fb3a39,0x3a73ba09,0x39fcba6f,
0x3a42b92f,0x3a4aba80,0xb9e6b960,0xba773a6a,0x3a27ba7c,0xba1db7c9,0xba653a7a,0x398939cf,0x3a7fba51,0x38fbba39,0xba733a09,0xb9fc3a6f,0xb897ba13,0xba7e3a31,0xb9a13a58,0x3a5fb9b8,
0x39a13a09,0x3a5fba6f,0xba27b92f,0xba1d3a80,0xba733a58,0x39fc39b8,0x3a42ba7c,0xba4a37c9,0x3a65b960,0x3989ba6a,0xba7f3a13,0x38fb3a31,0xb9e63a7a,0x3a77b9cf,0x3897ba51,0xba7e3a39,
0xba733a58,0x39fc39b8,0x3a42ba7c,0xba4a37c9,0xb9a1ba09,0xba5f3a6f,0x3a27392f,0x3a1dba80,0xb9e63a7a,0x3a77b9cf,0x3897ba51,0xba7e3a39,0xba653960,0xb9893a6a,0x3a7fba13,0xb8fbba31,
0x3a58ba5f,0xba6a3897,0x392f3a4a,0x3a39ba73,0xba09b9fc,0xb9cf3a7f,0x3a7cba1d,0xba31b9a1,0xba7a3989,0x39b83a27,0x3a13ba7e,0xba8039e6,0xb9603a77,0x3a6fba42,0xba51b8fb,0xb7c93a65,
0xba09b9fc,0xb9cf3a7f,0x3a7cba1d,0xba31b9a1,0xba583a5f,0x3a6ab897,0xb92fba4a,0xba393a73,0xb9603a77,0x3a6fba42,0xba51b8fb,0xb7c93a65,0x3a7ab989,0xb9b8ba27,0xba133a7e,0x3a80b9e6,
0xba8039a1,0x3a583989,0xb9cfba42,0xb92f3a7e,0xb7c9ba73,0xba093a77,0x3a6aba27,0xba7c38fb,0x3a3939e6,0xb960ba5f,0xb9b83a7f,0x3a51ba4a,0xba313a65,0x3a7ab9fc,0xba6fb897,0x3a133a1d,
0xb7c9ba73,0xba093a77,0x3a6aba27,0xba7c38fb,0x3a80b9a1,0xba58b989,0x39cf3a42,0x392fba7e,0xba313a65,0x3a7ab9fc,0xba6fb897,0x3a133a1d,0xba39b9e6,0x39603a5f,0x39b8ba7f,0xba513a4a,
0x3a77b9b8,0xba7f392f,0x3a7e37c9,0xba73b960,0xb989ba6f,0x38973a7c,0x38fbba80,0xb9a13a7a,0x39fcba6a,0xba273a51,0x3a4aba31,0xba653a09,0xba5fb9cf,0x3a423a13,0xba1dba39,0x39e63a58,
0xb989ba6f,0x38973a7c,0x38fbba80,0xb9a13a7a,0xba7739b8,0x3a7fb92f,0xba7eb7c9,0x3a733960,0xba5fb9cf,0x3a423a13,0xba1dba39,0x39e63a58,0xb9fc3a6a,0x3a27ba51,0xba4a3a31,0x3a65ba09,
0xb9893a6f,0x3897ba7c,0x38fb3a80,0xb9a1ba7a,0xba77b9b8,0x3a7f392f,0xba7e37c9,0x3a73b960,0x39fc3a6a,0xba27ba51,0x3a4a3a31,0xba65ba09,0xba5f39cf,0x3a42ba13,0xba1d3a39,0x39e6ba58,
0x3a7739b8,0xba7fb92f,0x3a7eb7c9,0xba733960,0xb9893a6f,0x3897ba7c,0x38fb3a80,0xb9a1ba7a,0x3a5fb9cf,0xba423a13,0x3a1dba39,0xb9e63a58,0x39fc3a6a,0xba27ba51,0x3a4a3a31,0xba65ba09,
0xba80b9a1,0x3a58b989,0xb9cf3a42,0xb92fba7e,0xb7c93a73,0xba09ba77,0x3a6a3a27,0xba7cb8fb,0x3a313a65,0xba7ab9fc,0x3a6fb897,0xba133a1d,0x3a39b9e6,0xb9603a5f,0xb9b8ba7f,0x3a513a4a,
0x37c9ba73,0x3a093a77,0xba6aba27,0x3a7c38fb,0xba80b9a1,0x3a58b989,0xb9cf3a42,0xb92fba7e,0xba3939e6,0x3960ba5f,0x39b83a7f,0xba51ba4a,0x3a313a65,0xba7ab9fc,0x3a6fb897,0xba133a1d,
0xba58ba5f,0x3a6a3897,0xb92f3a4a,0xba39ba73,0x3a09b9fc,0x39cf3a7f,0xba7cba1d,0x3a31b9a1,0x39603a77,0xba6fba42,0x3a51b8fb,0x37c93a65,0xba7ab989,0x39b8ba27,0x3a133a7e,0xba80b9e6,
0xba0939fc,0xb9cfba7f,0x3a7c3a1d,0xba3139a1,0xba58ba5f,0x3a6a3897,0xb92f3a4a,0xba39ba73,0x3a7a3989,0xb9b83a27,0xba13ba7e,0x3a8039e6,0x39603a77,0xba6fba42,0x3a51b8fb,0x37c93a65,
0xba73ba58,0x39fcb9b8,0x3a423a7c,0xba4ab7c9,0xb9a13a09,0xba5fba6f,0x3a27b92f,0x3a1d3a80,0xba65b960,0xb989ba6a,0x3a7f3a13,0xb8fb3a31,0x39e63a7a,0xba77b9cf,0xb897ba51,0x3a7e3a39,
0x39a1ba09,0x3a5f3a6f,0xba27392f,0xba1dba80,0xba73ba58,0x39fcb9b8,0x3a423a7c,0xba4ab7c9,0xb9e6ba7a,0x3a7739cf,0x38973a51,0xba7eba39,0xba65b960,0xb989ba6a,0x3a7f3a13,0xb8fb3a31,
0x3a42392f,0x3a4a3a80,0xb9e63960,0xba77ba6a,0x3a273a7c,0xba1d37c9,0xba65ba7a,0x3989b9cf,0x3897ba13,0x3a7e3a31,0x39a13a58,0xba5fb9b8,0x3a7f3a51,0x38fb3a39,0xba73ba09,0xb9fcba6f,
0x3a273a7c,0xba1d37c9,0xba65ba7a,0x3989b9cf,0xba42b92f,0xba4aba80,0x39e6b960,0x3a773a6a,0x3a7f3a51,0x38fb3a39,0xba73ba09,0xb9fcba6f,0xb8973a13,0xba7eba31,0xb9a1ba58,0x3a5f39b8,
0xba51ba7e,0x37c9b9e6,0x3a5839fc,0x3a6a3a7f,0xba13b8fb,0xba80ba65,0xba09ba5f,0x39cfb897,0x392f3a1d,0xba39b9a1,0xba7aba77,0xb9b8ba42,0x3a7c3a4a,0x3a313a73,0xb9603989,0xba6fba27,
0xba13b8fb,0xba80ba65,0xba09ba5f,0x39cfb897,0x3a513a7e,0xb7c939e6,0xba58b9fc,0xba6aba7f,0x3a7c3a4a,0x3a313a73,0xb9603989,0xba6fba27,0xb92fba1d,0x3a3939a1,0x3a7a3a77,0x39b83a42,
0x39cf3a27,0xb92f38fb,0xba31b9e6,0xba7aba5f,0xba6aba42,0xba7cba7e,0xba39ba65,0xb960b9fc,0x39b83897,0x3a513a1d,0x3a803a73,0x3a583a77,0x3a6f3a7f,0x3a133a4a,0x37c939a1,0xba09b989,
0xba6aba42,0xba7cba7e,0xba39ba65,0xb960b9fc,0xb9cfba27,0x392fb8fb,0x3a3139e6,0x3a7a3a5f,0x3a6f3a7f,0x3a133a4a,0x37c939a1,0xba09b989,0xb9b8b897,0xba51ba1d,0xba80ba73,0xba58ba77,
0xba1dba31,0xb9e6ba09,0xb989b9b8,0xb897b92f,0xba4aba39,0xba65ba58,0xba77ba6f,0xba7fba7c,0xba7eba80,0xba73ba7a,0xba5fba6a,0xba42ba51,0xb8fbb7c9,0xb9a1b960,0xb9fcb9cf,0xba27ba13,
0xba4aba39,0xba65ba58,0xba77ba6f,0xba7fba7c,0x3a1d3a31,0x39e63a09,0x398939b8,0x3897392f,0xb8fbb7c9,0xb9a1b960,0xb9fcb9cf,0xba27ba13,0x3a7e3a80,0x3a733a7a,0x3a5f3a6a,0x3a423a51,
0x3d973cc9,0xbf7fbf80,0x3ee63ecf,0xbf65bf6a,0x3e2f3dfb,0xbf7cbf7e,0x3f093efc,0xbf58bf5f,0x3e893e60,0xbf77bf7a,0x3f1d3f13,0xbf4abf51,0x3eb83ea1,0xbf6fbf73,0x3f313f27,0xbf39bf42,
0x3eb83dfb,0xbf6fbf7e,0x3f393f5f,0x3f313efc,0x3f423f13,0xbf27bf51,0x3ea13f09,0x3f733f58,0x3f7a3f65,0xbe60bee6,0xbe2f3d97,0x3f7c3f7f,0x3f773f80,0x3e893cc9,0xbf1dbecf,0x3f4a3f6a,
0x3f1d3e60,0xbf4abf7a,0xbf5fbf13,0x3efc3f51,0x3f803f65,0xbcc9bee6,0xbf6fbf7f,0xbeb83d97,0x3f273f6a,0x3f423ecf,0xbea1bf31,0xbf73bf39,0xbe2f3e89,0x3f7c3f77,0x3f093dfb,0xbf58bf7e,
0x3f513ea1,0xbf13bf73,0xbe60bf42,0xbf7abf27,0x3f4a3f80,0x3f1d3cc9,0x3f5f3ecf,0xbefcbf6a,0xbeb83e89,0x3f6f3f77,0x3f393f7e,0x3f313dfb,0xbf7fbf58,0xbd973f09,0xbee63e2f,0x3f653f7c,
0x3f733ecf,0xbea1bf6a,0x3f7f3f39,0x3d97bf31,0x3e603f5f,0x3f7a3efc,0xbe2f3f1d,0x3f7c3f4a,0xbf7ebf13,0x3dfb3f51,0xbf77bf58,0xbe893f09,0xbcc9bf42,0xbf80bf27,0x3eb8bee6,0xbf6fbf65,
0x3f803efc,0xbcc9bf5f,0xbeb83f1d,0x3f6f3f4a,0xbee63f09,0x3f653f58,0xbf27bf7c,0xbf423e2f,0xbf13bf7f,0xbf513d97,0x3f7a3ea1,0xbe60bf73,0x3f7e3ecf,0xbdfbbf6a,0xbe893f31,0x3f773f39,
0x3f773f13,0x3e89bf51,0xbf4abf58,0xbf1d3f09,0xbf6a3d97,0x3ecf3f7f,0x3f803ea1,0xbcc9bf73,0x3ee6bf31,0xbf65bf39,0xbf423eb8,0x3f273f6f,0x3e603f7e,0x3f7a3dfb,0x3e2fbf5f,0xbf7cbefc,
0x3f583f27,0x3f09bf42,0x3f51bee6,0xbf13bf65,0xbf77becf,0xbe893f6a,0xbf1d3f31,0x3f4a3f39,0x3f803dfb,0xbcc9bf7e,0x3eb8bf5f,0xbf6fbefc,0xbf733e2f,0x3ea13f7c,0xbd973f7a,0x3f7f3e60,
0x3f273f39,0x3f42bf31,0x3ea13f6f,0x3f73beb8,0xbf13bf4a,0xbf513f1d,0xbe60bf77,0xbf7a3e89,0x3efc3f58,0x3f5fbf09,0x3dfb3f7c,0x3f7ebe2f,0xbecfbf65,0xbf6a3ee6,0xbcc9bf7f,0xbf803d97,
0x3ecf3f4a,0x3f6abf1d,0xbf803e89,0x3cc93f77,0x3d97bf7c,0xbf7f3e2f,0x3f653e60,0x3ee6bf7a,0xbf093f73,0x3f583ea1,0xbf13bf27,0xbf513f42,0x3f5fbf31,0xbefcbf39,0x3dfb3f6f,0x3f7ebeb8,
0x3dfb3f58,0x3f7ebf09,0x3e89bf7c,0xbf773e2f,0x3f31bf73,0xbf39bea1,0xbf6a3f42,0x3ecf3f27,0xbf7f3eb8,0xbd973f6f,0x3f653cc9,0x3ee6bf80,0x3f133efc,0x3f51bf5f,0xbe60bf4a,0xbf7a3f1d,
0xbe2f3f65,0x3f7cbee6,0x3f58bd97,0x3f09bf7f,0x3f7ebf31,0xbdfbbf39,0x3e89bf6f,0xbf773eb8,0xbecfbefc,0xbf6a3f5f,0xbf803f1d,0x3cc93f4a,0xbf423f7a,0x3f273e60,0x3ea13f13,0x3f73bf51,
0xbee63f6f,0x3f65beb8,0xbf423f80,0x3f273cc9,0x3f58be89,0x3f09bf77,0x3f133dfb,0x3f51bf7e,0x3f1dbf7c,0xbf4a3e2f,0x3f5fbf7a,0xbefcbe60,0xbf393d97,0xbf313f7f,0xbecfbea1,0xbf6a3f73,
0xbf313f77,0x3f39be89,0xbecfbdfb,0xbf6a3f7e,0x3ea13e60,0x3f73bf7a,0xbf7f3f51,0xbd973f13,0x3f7cbf42,0x3e2fbf27,0xbf093f65,0x3f58bee6,0x3f1dbf6f,0xbf4a3eb8,0x3efc3cc9,0x3f5fbf80,
0xbf5f3f7c,0x3efcbe2f,0x3f7ebf7a,0xbdfbbe60,0xbeb83f27,0x3f6fbf42,0x3f31bf65,0xbf393ee6,0x3ea13cc9,0x3f73bf80,0x3d97becf,0xbf7f3f6a,0x3f58bf1d,0x3f09bf4a,0xbf133e89,0xbf513f77,
0xbf7a3f7f,0x3e60bd97,0xbe2f3ea1,0x3f7cbf73,0xbf5f3f6f,0x3efcbeb8,0x3dfb3cc9,0x3f7ebf80,0xbf313f4a,0x3f39bf1d,0x3ecfbe89,0x3f6abf77,0xbee63f13,0x3f65bf51,0x3f27bf09,0x3f42bf58,
0xbf7f3f80,0xbd973cc9,0xbf653f6a,0xbee63ecf,0xbf7c3f7e,0xbe2f3dfb,0xbf583f5f,0xbf093efc,0xbf773f7a,0xbe893e60,0xbf4a3f51,0xbf1d3f13,0xbf6f3f73,0xbeb83ea1,0xbf393f42,0xbf313f27,
0xbf6f3f7e,0xbeb83dfb,0x3f31befc,0xbf393f5f,0xbf273f51,0xbf423f13,0x3f73bf58,0xbea13f09,0xbe603ee6,0xbf7a3f65,0x3f7cbf7f,0x3e2f3d97,0x3e89bcc9,0xbf773f80,0x3f4abf6a,0x3f1dbecf,
0xbf4a3f7a,0xbf1d3e60,0x3efcbf51,0x3f5fbf13,0xbcc93ee6,0xbf803f65,0xbeb8bd97,0x3f6fbf7f,0x3f42becf,0xbf273f6a,0xbf733f39,0x3ea1bf31,0x3f7cbf77,0x3e2f3e89,0xbf583f7e,0xbf093dfb,
0xbf133f73,0xbf513ea1,0xbf7a3f27,0x3e60bf42,0x3f1dbcc9,0xbf4a3f80,0xbefc3f6a,0xbf5f3ecf,0x3f6fbf77,0x3eb83e89,0x3f31bdfb,0xbf393f7e,0xbd97bf09,0x3f7fbf58,0x3f65bf7c,0x3ee63e2f,
0xbea13f6a,0xbf733ecf,0x3d973f31,0xbf7f3f39,0x3f7abefc,0xbe603f5f,0x3f7cbf4a,0x3e2f3f1d,0x3dfbbf51,0x3f7ebf13,0xbe89bf09,0x3f77bf58,0xbf803f27,0x3cc9bf42,0xbf6f3f65,0xbeb8bee6,
0xbcc93f5f,0xbf803efc,0x3f6fbf4a,0x3eb83f1d,0x3f65bf58,0x3ee63f09,0xbf42be2f,0x3f27bf7c,0xbf51bd97,0x3f13bf7f,0xbe603f73,0xbf7a3ea1,0xbdfb3f6a,0xbf7e3ecf,0x3f77bf39,0x3e893f31,
0x3e893f51,0xbf773f13,0xbf1dbf09,0x3f4abf58,0x3ecfbf7f,0x3f6a3d97,0xbcc93f73,0xbf803ea1,0xbf653f39,0xbee6bf31,0x3f27bf6f,0x3f423eb8,0x3f7abdfb,0xbe603f7e,0xbf7c3efc,0xbe2fbf5f,
0x3f093f42,0xbf583f27,0xbf133f65,0xbf51bee6,0xbe89bf6a,0x3f77becf,0x3f4abf39,0x3f1d3f31,0xbcc93f7e,0xbf803dfb,0xbf6f3efc,0xbeb8bf5f,0x3ea1bf7c,0x3f733e2f,0x3f7fbe60,0x3d973f7a,
0x3f423f31,0xbf273f39,0x3f733eb8,0xbea13f6f,0xbf51bf1d,0x3f13bf4a,0xbf7abe89,0x3e60bf77,0x3f5f3f09,0xbefc3f58,0x3f7e3e2f,0xbdfb3f7c,0xbf6abee6,0x3ecfbf65,0xbf80bd97,0x3cc9bf7f,
0x3f6a3f1d,0xbecf3f4a,0x3cc9bf77,0x3f803e89,0xbf7fbe2f,0xbd97bf7c,0x3ee63f7a,0xbf653e60,0x3f58bea1,0x3f093f73,0xbf51bf42,0x3f13bf27,0xbefc3f39,0xbf5fbf31,0x3f7e3eb8,0xbdfb3f6f,
0x3f7e3f09,0xbdfb3f58,0xbf77be2f,0xbe89bf7c,0xbf393ea1,0xbf31bf73,0x3ecfbf27,0x3f6a3f42,0xbd97bf6f,0x3f7f3eb8,0x3ee63f80,0xbf653cc9,0x3f513f5f,0xbf133efc,0xbf7abf1d,0x3e60bf4a,
0x3f7c3ee6,0x3e2f3f65,0x3f093f7f,0xbf58bd97,0xbdfb3f39,0xbf7ebf31,0xbf77beb8,0xbe89bf6f,0xbf6abf5f,0x3ecfbefc,0x3cc9bf4a,0x3f803f1d,0x3f27be60,0x3f423f7a,0x3f733f51,0xbea13f13,
0x3f653eb8,0x3ee63f6f,0x3f27bcc9,0x3f423f80,0x3f093f77,0xbf58be89,0x3f513f7e,0xbf133dfb,0xbf4abe2f,0xbf1dbf7c,0xbefc3e60,0xbf5fbf7a,0xbf31bf7f,0x3f393d97,0xbf6abf73,0x3ecfbea1,
0x3f393e89,0x3f313f77,0xbf6abf7e,0x3ecfbdfb,0x3f733f7a,0xbea13e60,0xbd97bf13,0x3f7f3f51,0x3e2f3f27,0xbf7cbf42,0x3f583ee6,0x3f093f65,0xbf4abeb8,0xbf1dbf6f,0x3f5f3f80,0xbefc3cc9,
0x3efc3e2f,0x3f5f3f7c,0xbdfb3e60,0xbf7ebf7a,0x3f6f3f42,0x3eb83f27,0xbf39bee6,0xbf31bf65,0x3f733f80,0xbea13cc9,0xbf7fbf6a,0xbd97becf,0x3f093f4a,0xbf58bf1d,0xbf51bf77,0x3f133e89,
0x3e603d97,0x3f7a3f7f,0x3f7c3f73,0x3e2f3ea1,0x3efc3eb8,0x3f5f3f6f,0x3f7e3f80,0xbdfb3cc9,0x3f393f1d,0x3f313f4a,0x3f6a3f77,0xbecfbe89,0x3f653f51,0x3ee63f13,0x3f423f58,0xbf27bf09,
0x3f423f39,0xbf27bf31,0x3f733f6f,0xbea1beb8,0x3f513f4a,0xbf13bf1d,0x3f7a3f77,0xbe60be89,0x3f5f3f58,0xbefcbf09,0x3f7e3f7c,0xbdfbbe2f,0x3f6a3f65,0xbecfbee6,0x3f803f7f,0xbcc9bd97,
0xbf6abf4a,0x3ecf3f1d,0xbcc9be89,0xbf80bf77,0xbf7fbf7c,0xbd973e2f,0x3ee63e60,0xbf65bf7a,0xbf58bf73,0xbf09bea1,0x3f513f27,0xbf13bf42,0xbefcbf31,0xbf5fbf39,0x3f7e3f6f,0xbdfbbeb8,
0x3f7e3f58,0xbdfbbf09,0xbf77bf7c,0xbe893e2f,0x3f393f73,0x3f313ea1,0xbecfbf42,0xbf6abf27,0xbd973eb8,0x3f7f3f6f,0x3ee63cc9,0xbf65bf80,0xbf51befc,0x3f133f5f,0x3f7a3f4a,0xbe60bf1d,
0xbf7cbf65,0xbe2f3ee6,0xbf093d97,0x3f583f7f,0xbdfbbf31,0xbf7ebf39,0xbf77bf6f,0xbe893eb8,0x3f6a3efc,0xbecfbf5f,0xbcc9bf1d,0xbf80bf4a,0x3f273f7a,0x3f423e60,0x3f733f13,0xbea1bf51,
0x3f653f6f,0x3ee6beb8,0x3f273f80,0x3f423cc9,0xbf093e89,0x3f583f77,0xbf51bdfb,0x3f133f7e,0xbf4abf7c,0xbf1d3e2f,0xbefcbf7a,0xbf5fbe60,0x3f31bd97,0xbf39bf7f,0x3f6a3ea1,0xbecfbf73,
0xbf39bf77,0xbf313e89,0x3f6a3dfb,0xbecfbf7e,0x3f733e60,0xbea1bf7a,0xbd973f51,0x3f7f3f13,0xbe2f3f42,0x3f7c3f27,0xbf58bf65,0xbf093ee6,0xbf4abf6f,0xbf1d3eb8,0x3f5f3cc9,0xbefcbf80,
0x3efc3f7c,0x3f5fbe2f,0xbdfbbf7a,0xbf7ebe60,0xbf6fbf27,0xbeb83f42,0x3f393f65,0x3f31bee6,0x3f733cc9,0xbea1bf80,0xbf7fbecf,0xbd973f6a,0xbf093f1d,0x3f583f4a,0x3f51be89,0xbf13bf77,
0xbe60bf7f,0xbf7a3d97,0xbf7cbea1,0xbe2f3f73,0x3efc3f6f,0x3f5fbeb8,0x3f7e3cc9,0xbdfbbf80,0xbf39bf4a,0xbf313f1d,0xbf6a3e89,0x3ecf3f77,0x3f653f13,0x3ee6bf51,0x3f42bf09,0xbf27bf58,
0xbd973f80,0x3f7f3cc9,0xbee63f6a,0x3f653ecf,0x3e2fbf7e,0xbf7cbdfb,0x3f09bf5f,0xbf58befc,0xbe893f7a,0x3f773e60,0xbf1d3f51,0x3f4a3f13,0x3eb8bf73,0xbf6fbea1,0x3f31bf42,0xbf39bf27,
0x3eb8bf7e,0xbf6fbdfb,0x3f393efc,0x3f31bf5f,0xbf423f51,0x3f273f13,0xbea1bf58,0xbf733f09,0x3f7abee6,0xbe60bf65,0xbe2f3f7f,0x3f7cbd97,0xbf77bcc9,0xbe893f80,0x3f1dbf6a,0xbf4abecf,
0xbf1d3f7a,0x3f4a3e60,0x3f5fbf51,0xbefcbf13,0x3f80bee6,0xbcc9bf65,0xbf6f3d97,0xbeb83f7f,0xbf27becf,0xbf423f6a,0x3ea13f39,0x3f73bf31,0xbe2f3f77,0x3f7cbe89,0x3f09bf7e,0xbf58bdfb,
0x3f51bf73,0xbf13bea1,0xbe60bf27,0xbf7a3f42,0xbf4abcc9,0xbf1d3f80,0xbf5f3f6a,0x3efc3ecf,0xbeb83f77,0x3f6fbe89,0x3f393dfb,0x3f31bf7e,0x3f7fbf09,0x3d97bf58,0x3ee6bf7c,0xbf653e2f,
0xbf733f6a,0x3ea13ecf,0xbf7f3f31,0xbd973f39,0x3e603efc,0x3f7abf5f,0xbe2f3f4a,0x3f7cbf1d,0x3f7ebf51,0xbdfbbf13,0x3f77bf09,0x3e89bf58,0xbcc9bf27,0xbf803f42,0x3eb8bf65,0xbf6f3ee6,
0x3f80bf5f,0xbcc9befc,0xbeb83f4a,0x3f6fbf1d,0x3ee6bf58,0xbf653f09,0x3f27be2f,0x3f42bf7c,0xbf133d97,0xbf513f7f,0x3f7abf73,0xbe60bea1,0xbf7e3f6a,0x3dfb3ecf,0x3e89bf39,0xbf773f31,
0xbf773f51,0xbe893f13,0x3f4abf09,0x3f1dbf58,0xbf6a3f7f,0x3ecfbd97,0x3f80bf73,0xbcc9bea1,0xbee63f39,0x3f65bf31,0x3f42bf6f,0xbf273eb8,0x3e603dfb,0x3f7abf7e,0x3e2fbefc,0xbf7c3f5f,
0x3f58bf42,0x3f09bf27,0x3f51bf65,0xbf133ee6,0x3f77bf6a,0x3e89becf,0x3f1dbf39,0xbf4a3f31,0x3f80bf7e,0xbcc9bdfb,0x3eb8befc,0xbf6f3f5f,0x3f73bf7c,0xbea13e2f,0x3d97be60,0xbf7f3f7a,
0xbf273f31,0xbf423f39,0xbea13eb8,0xbf733f6f,0xbf133f1d,0xbf513f4a,0xbe603e89,0xbf7a3f77,0xbefc3f09,0xbf5f3f58,0xbdfb3e2f,0xbf7e3f7c,0xbecf3ee6,0xbf6a3f65,0xbcc93d97,0xbf803f7f,
0x3ecfbf1d,0x3f6abf4a,0xbf803f77,0x3cc9be89,0xbd97be2f,0x3f7fbf7c,0xbf653f7a,0xbee63e60,0xbf093ea1,0x3f58bf73,0xbf133f42,0xbf513f27,0xbf5f3f39,0x3efcbf31,0xbdfb3eb8,0xbf7e3f6f,
0xbdfb3f09,0xbf7e3f58,0xbe89be2f,0x3f77bf7c,0x3f31bea1,0xbf393f73,0xbf6a3f27,0x3ecfbf42,0x3f7fbf6f,0x3d973eb8,0xbf653f80,0xbee63cc9,0x3f13bf5f,0x3f51befc,0xbe603f1d,0xbf7a3f4a,
0xbe2fbee6,0x3f7cbf65,0x3f58bf7f,0x3f093d97,0xbf7e3f39,0x3dfbbf31,0xbe89beb8,0x3f77bf6f,0xbecf3f5f,0xbf6a3efc,0xbf803f4a,0x3cc9bf1d,0x3f42be60,0xbf273f7a,0xbea13f51,0xbf733f13,
0x3ee63eb8,0xbf653f6f,0x3f42bcc9,0xbf273f80,0x3f58bf77,0x3f093e89,0x3f13bf7e,0x3f51bdfb,0xbf1dbe2f,0x3f4abf7c,0xbf5f3e60,0x3efcbf7a,0xbf393f7f,0xbf31bd97,0xbecf3f73,0xbf6a3ea1,
0xbf31be89,0x3f39bf77,0xbecf3f7e,0xbf6a3dfb,0xbea13f7a,0xbf733e60,0x3f7fbf13,0x3d973f51,0x3f7cbf27,0x3e2f3f42,0xbf09bee6,0x3f58bf65,0xbf1dbeb8,0x3f4abf6f,0xbefc3f80,0xbf5f3cc9,
0x3f5f3e2f,0xbefc3f7c,0xbf7e3e60,0x3dfbbf7a,0xbeb8bf42,0x3f6fbf27,0x3f313ee6,0xbf393f65,0xbea13f80,0xbf733cc9,0xbd97bf6a,0x3f7fbecf,0x3f58bf4a,0x3f093f1d,0xbf133f77,0xbf51be89,
0xbf7abd97,0x3e60bf7f,0xbe2fbf73,0x3f7cbea1,0x3f5f3eb8,0xbefc3f6f,0xbdfb3f80,0xbf7e3cc9,0xbf31bf1d,0x3f39bf4a,0x3ecfbf77,0x3f6a3e89,0x3ee63f51,0xbf653f13,0xbf273f58,0xbf42bf09,
0x3f7fbcc9,0x3d973f80,0x3f65becf,0x3ee63f6a,0xbf7c3dfb,0xbe2fbf7e,0xbf583efc,0xbf09bf5f,0x3f77be60,0x3e893f7a,0x3f4abf13,0x3f1d3f51,0xbf6f3ea1,0xbeb8bf73,0xbf393f27,0xbf31bf42,
0xbf6f3dfb,0xbeb8bf7e,0x3f313f5f,0xbf393efc,0x3f27bf13,0x3f423f51,0xbf73bf09,0x3ea1bf58,0xbe603f65,0xbf7abee6,0x3f7c3d97,0x3e2f3f7f,0xbe89bf80,0x3f77bcc9,0xbf4a3ecf,0xbf1dbf6a,
0x3f4abe60,0x3f1d3f7a,0xbefc3f13,0xbf5fbf51,0xbcc93f65,0xbf80bee6,0xbeb8bf7f,0x3f6f3d97,0xbf42bf6a,0x3f27becf,0x3f733f31,0xbea13f39,0x3f7c3e89,0x3e2f3f77,0xbf583dfb,0xbf09bf7e,
0xbf133ea1,0xbf51bf73,0xbf7abf42,0x3e60bf27,0xbf1dbf80,0x3f4abcc9,0x3efcbecf,0x3f5f3f6a,0x3f6f3e89,0x3eb83f77,0x3f313f7e,0xbf393dfb,0x3d973f58,0xbf7fbf09,0xbf65be2f,0xbee6bf7c,
0x3ea1becf,0x3f733f6a,0xbd97bf39,0x3f7f3f31,0x3f7a3f5f,0xbe603efc,0x3f7c3f1d,0x3e2f3f4a,0xbdfb3f13,0xbf7ebf51,0x3e893f58,0xbf77bf09,0xbf80bf42,0x3cc9bf27,0xbf6fbee6,0xbeb8bf65,
0xbcc93efc,0xbf80bf5f,0x3f6f3f1d,0x3eb83f4a,0xbf65bf09,0xbee6bf58,0x3f423f7c,0xbf27be2f,0xbf51bf7f,0x3f133d97,0xbe603ea1,0xbf7abf73,0x3dfbbecf,0x3f7e3f6a,0xbf77bf31,0xbe89bf39,
0xbe89bf13,0x3f773f51,0x3f1d3f58,0xbf4abf09,0x3ecf3d97,0x3f6a3f7f,0xbcc93ea1,0xbf80bf73,0x3f653f31,0x3ee63f39,0xbf27beb8,0xbf42bf6f,0x3f7a3f7e,0xbe603dfb,0xbf7cbf5f,0xbe2fbefc,
0x3f093f27,0xbf58bf42,0xbf13bee6,0xbf51bf65,0x3e893ecf,0xbf77bf6a,0xbf4abf31,0xbf1dbf39,0xbcc93dfb,0xbf80bf7e,0xbf6fbf5f,0xbeb8befc,0xbea1be2f,0xbf73bf7c,0xbf7fbf7a,0xbd97be60,
0x3f6e3f7a,0x3f1f3f28,0x3ec23ed0,0x3e2f3e48,0x3f583f63,0x3f0e3f17,0x3ea63eb4,0x3df93e15,0x3f443f4e,0x3efd3f06,0x3e8b3e99,0x3d953dc7,0x3f313f3a,0x3edf3eee,0x3e623e7c,0x3cc63d46,
0x3f583f62,0x3f133f1b,0x3eb53ec2,0x3e243e3b,0x3f453f4f,0x3f043f0b,0x3e9b3ea8,0x3de93e0c,0x3f333f3c,0x3eeb3ef9,0x3e823e8f,0x3d8b3dba,0x3f233f2b,0x3ecf3edd,0x3e533e6c,0x3cb93d39,
0x3f443f4d,0x3f073f0e,0x3ea83eb4,0x3e183e2e,0x3f343f3c,0x3ef33f00,0x3e903e9c,0x3dd93e02,0x3f243f2c,0x3ed93ee6,0x3e723e84,0x3d823dad,0x3f153f1c,0x3ec03ecc,0x3e453e5b,0x3cad3d2d,
0x3f323f39,0x3ef73f02,0x3e9b3ea6,0x3e0d3e22,0x3f233f2a,0x3edf3eeb,0x3e853e90,0x3dc93df1,0x3f153f1c,0x3ec83ed3,0x3e603e75,0x3d713da1,0x3f083f0f,0x3eb13ebc,0x3e363e4b,0x3ca03d20,
0x3f203f27,0x3ee13eec,0x3e8e3e98,0x3e023e15,0x3f133f1a,0x3ecc3ed6,0x3e743e84,0x3db93dde,0x3f073f0d,0x3eb73ec1,0x3e4e3e61,0x3d5e3d94,0x3ef83f02,0x3ea23eac,0x3e283e3b,0x3c943d14,
0x3f103f15,0x3ecc3ed6,0x3e813e8a,0x3ded3e08,0x3f053f0a,0x3eb93ec2,0x3e5f3e71,0x3da93dcb,0x3ef43eff,0x3ea63eaf,0x3e3c3e4d,0x3d4b3d87,0x3ee03eea,0x3e933e9d,0x3e193e2a,0x3c873d07,
0x3f003f05,0x3eb73ec0,0x3e6a3e7a,0x3dd73df6,0x3eed3ef6,0x3ea63eaf,0x3e4a3e5a,0x3d993db8,0x3edb3ee4,0x3e963e9e,0x3e2a3e3a,0x3d383d75,0x3ec93ed2,0x3e853e8d,0x3e0b3e1a,0x3c753cf5,
0x3ee23eeb,0x3ea33eab,0x3e513e5f,0x3dc13ddd,0x3ed23eda,0x3e943e9c,0x3e353e43,0x3d8a3da5,0x3ec23eca,0x3e853e8d,0x3e183e26,0x3d253d5c,0x3eb33eba,0x3e6e3e7c,0x3df93e0a,0x3c5c3cdc,
0x3ec63ecd,0x3e903e96,0x3e393e45,0x3dab3dc3,0x3eb83ebf,0x3e833e89,0x3e203e2c,0x3d743d92,0x3eaa3eb1,0x3e6b3e78,0x3e073e13,0x3d123d43,0x3e9d3ea3,0x3e523e5f,0x3ddc3df5,0x3c433cc3,
0x3eaa3eb0,0x3e793e82,0x3e203e2b,0x3d953daa,0x3e9f3ea4,0x3e623e6d,0x3e0b3e15,0x3d543d7f,0x3e933e99,0x3e4c3e57,0x3dea3e00,0x3cff3d2a,0x3e883e8d,0x3e363e41,0x3dbf3dd5,0x3c2a3caa,
0x3e903e94,0x3e533e5c,0x3e083e11,0x3d7d3d91,0x3e863e8b,0x3e403e49,0x3dec3dfe,0x3d353d59,0x3e793e81,0x3e2d3e37,0x3dc73dda,0x3cd93d11,0x3e663e6f,0x3e1b3e24,0x3da33db5,0x3c113c91,
0x3e6b3e73,0x3e2d3e35,0x3de13df0,0x3d513d6f,0x3e5c3e63,0x3e1e3e26,0x3dc33dd2,0x3d153d33,0x3e4c3e54,0x3e0f3e16,0x3da53db4,0x3cb33cef,0x3e3d3e44,0x3dff3e07,0x3d863d95,0x3bef3c6f,
0x3e393e3f,0x3e083e0e,0x3db13dbd,0x3d253d3d,0x3e2c3e32,0x3df93e02,0x3d993da5,0x3cec3d0d,0x3e203e26,0x3de13ded,0x3d823d8e,0x3c8d3cbd,0x3e143e1a,0x3dc93dd5,0x3d543d6c,0x3bbc3c3d,
0x3e073e0b,0x3dc73dd0,0x3d823d8a,0x3cf23d0a,0x3dfc3e02,0x3db63dbf,0x3d613d72,0x3cad3ccf,0x3dea3df3,0x3da53dad,0x3d3e3d50,0x3c4f3c8a,0x3dd93de2,0x3d933d9c,0x3d1c3d2d,0x3b8a3c0a,
0x3dab3db0,0x3d7d3d84,0x3d253d30,0x3c9a3cb0,0x3da03da5,0x3d673d72,0x3d0f3d1a,0x3c5c3c84,0x3d953d9a,0x3d513d5c,0x3cf23d04,0x3c043c30,0x3d8a3d8f,0x3d3b3d46,0x3cc63cdc,0x3b303bb0,
0x3d123d17,0x3cd93ce2,0x3c8d3c97,0x3c043c17,0x3d093d0d,0x3cc63ccf,0x3c753c84,0x3bbc3be2,0x3cff3d04,0x3cb33cbd,0x3c4f3c62,0x3b623b97,0x3cec3cf5,0x3ca03caa,0x3c2a3c3d,0x3a973b17,
0xbc43bc49,0xbc11bc17,0xbbbcbbc9,0xbb30bb49,0xbc36bc3d,0xbc04bc0a,0xbba3bbb0,0xbafbbb17,0xbc2abc30,0xbbefbbfb,0xbb8abb97,0xba97bac9,0xbc1dbc23,0xbbd6bbe2,0xbb62bb7b,0xb9c9ba49,
0xbd74bd7c,0xbd35bd3d,0xbcecbcfb,0xbc5cbc7b,0xbd64bd6c,0xbd25bd2d,0xbcccbcdc,0xbc1dbc3d,0xbd54bd5c,0xbd15bd1d,0xbcadbcbd,0xbbbcbbfb,0xbd45bd4c,0xbd06bd0d,0xbc8dbc9d,0xbafbbb7b,
0xbddcbde3,0xbda3bdaa,0xbd54bd62,0xbcc6bce2,0xbdcebdd5,0xbd95bd9c,0xbd38bd46,0xbc8dbcaa,0xbdbfbdc7,0xbd86bd8e,0xbd1cbd2a,0xbc2abc62,0xbdb1bdb8,0xbd71bd7f,0xbcffbd0d,0xbb62bbe2,
0xbe20be25,0xbdecbdf6,0xbd99bda4,0xbd0fbd23,0xbe15be1a,0xbdd7bde2,0xbd85bd8f,0xbcccbcf5,0xbe0bbe10,0xbdc3bdcd,0xbd61bd75,0xbc75bca3,0xbe00be05,0xbdaebdb8,0xbd38bd4c,0xbba3bc23,
0xbe52be59,0xbe1bbe22,0xbdc9bdd6,0xbd3bbd56,0xbe44be4b,0xbe0dbe14,0xbdaebdbb,0xbd06bd20,0xbe36be3d,0xbdffbe06,0xbd93bda1,0xbca0bcd6,0xbe28be2f,0xbde4bdf1,0xbd71bd86,0xbbd6bc56,
0xbe83be87,0xbe40be48,0xbdf9be05,0xbd67bd84,0xbe74be7c,0xbe2fbe37,0xbdd7bde8,0xbd25bd46,0xbe62be6b,0xbe1ebe26,0xbdb6bdc7,0xbcc6bd04,0xbe51be5a,0xbe0dbe15,0xbd95bda5,0xbc04bc84,
0xbe9dbea2,0xbe66be70,0xbe14be1e,0xbd8abd9d,0xbe92be97,0xbe51be5b,0xbe00be0a,0xbd45bd6c,0xbe88be8d,0xbe3dbe47,0xbdd9bded,0xbcecbd1d,0xbe7abe82,0xbe28be32,0xbdb1bdc5,0xbc1dbc9d,
0xbeb8bebe,0xbe86be8c,0xbe2cbe38,0xbda0bdb7,0xbeabbeb1,0xbe74be80,0xbe15be21,0xbd64bd89,0xbe9fbea5,0xbe5cbe68,0xbdfcbe09,0xbd09bd36,0xbe92be98,0xbe44be50,0xbdcebde5,0xbc36bcb6,
0xbed4bedb,0xbe99bea0,0xbe45be52,0xbdb6bdd0,0xbec5becc,0xbe8bbe92,0xbe2abe37,0xbd82bd9c,0xbeb6bebd,0xbe7bbe84,0xbe0fbe1d,0xbd1cbd50,0xbea8beaf,0xbe60be6d,0xbdeabe02,0xbc4fbccf,
0xbef1befa,0xbeadbeb5,0xbe5dbe6d,0xbdccbde9,0xbedfbee8,0xbe9dbea5,0xbe3fbe4e,0xbd92bdaf,0xbecebed7,0xbe8dbe95,0xbe21be30,0xbd2ebd69,0xbebebec6,0xbe7cbe86,0xbe03be12,0xbc68bce9,
0xbf08bf0d,0xbec2becb,0xbe76be84,0xbde2be01,0xbefbbf03,0xbeafbeb9,0xbe54be65,0xbda1bdc2,0xbee7bef1,0xbe9ebea7,0xbe33be44,0xbd41bd81,0xbed4bede,0xbe8cbe95,0xbe12be22,0xbc81bd01,
0xbf18bf1e,0xbed7bee1,0xbe88be91,0xbdf9be0e,0xbf0cbf12,0xbec2becc,0xbe6abe7c,0xbdb1bdd5,0xbf01bf06,0xbeaebeb8,0xbe45be57,0xbd54bd8e,0xbeecbef6,0xbe9bbea4,0xbe20be32,0xbc8dbd0d,
0xbf29bf30,0xbeecbef8,0xbe94be9f,0xbe07be1b,0xbf1bbf22,0xbed5bee1,0xbe7fbe8a,0xbdc1bde8,0xbf0ebf15,0xbebfbeca,0xbe57be6b,0xbd67bd9a,0xbf02bf08,0xbea9beb4,0xbe2fbe43,0xbc9abd1a,
0xbf3bbf43,0xbf01bf08,0xbea1bead,0xbe13be28,0xbf2bbf33,0xbee9bef6,0xbe8bbe96,0xbdd1bdfb,0xbf1dbf24,0xbed0bedc,0xbe69be7f,0xbd7abda7,0xbf0fbf15,0xbeb8bec4,0xbe3dbe53,0xbca7bd27,
0xbf4ebf57,0xbf0dbf14,0xbeaebebb,0xbe1ebe35,0xbf3cbf45,0xbefdbf06,0xbe96bea2,0xbde1be07,0xbf2bbf34,0xbee2beef,0xbe7bbe89,0xbd86bdb4,0xbf1cbf23,0xbec8bed5,0xbe4cbe63,0xbcb3bd33,
0xbf63bf6e,0xbf19bf21,0xbebbbec9,0xbe29be42,0xbf4ebf58,0xbf09bf11,0xbea1beae,0xbdf1be11,0xbf3bbf45,0xbef4bf01,0xbe87be94,0xbd90bdc0,0xbf29bf32,0xbed7bee5,0xbe5bbe74,0xbcc0bd40,
0xbcc68000,0xbe62be48,0xbedfbed0,0xbf31bf28,0xbd95bd46,0xbe8bbe7c,0xbefdbeee,0xbf44bf3a,0xbdf9bdc7,0xbea6be99,0xbf0ebf06,0xbf58bf4e,0xbe2fbe15,0xbec2beb4,0xbf1fbf17,0xbf6ebf63,
0xbcb98000,0xbe53be3b,0xbecfbec2,0xbf23bf1b,0xbd8bbd39,0xbe82be6c,0xbeebbedd,0xbf33bf2b,0xbde9bdba,0xbe9bbe8f,0xbf04bef9,0xbf45bf3c,0xbe24be0c,0xbeb5bea8,0xbf13bf0b,0xbf58bf4f,
0xbcad8000,0xbe45be2e,0xbec0beb4,0xbf15bf0e,0xbd82bd2d,0xbe72be5b,0xbed9becc,0xbf24bf1c,0xbdd9bdad,0xbe90be84,0xbef3bee6,0xbf34bf2c,0xbe18be02,0xbea8be9c,0xbf07bf00,0xbf44bf3c,
0xbca08000,0xbe36be22,0xbeb1bea6,0xbf08bf02,0xbd71bd20,0xbe60be4b,0xbec8bebc,0xbf15bf0f,0xbdc9bda1,0xbe85be75,0xbedfbed3,0xbf23bf1c,0xbe0dbdf1,0xbe9bbe90,0xbef7beeb,0xbf32bf2a,
0xbc948000,0xbe28be15,0xbea2be98,0xbef8beec,0xbd5ebd14,0xbe4ebe3b,0xbeb7beac,0xbf07bf02,0xbdb9bd94,0xbe74be61,0xbeccbec1,0xbf13bf0d,0xbe02bdde,0xbe8ebe84,0xbee1bed6,0xbf20bf1a,
0xbc878000,0xbe19be08,0xbe93be8a,0xbee0bed6,0xbd4bbd07,0xbe3cbe2a,0xbea6be9d,0xbef4beea,0xbda9bd87,0xbe5fbe4d,0xbeb9beaf,0xbf05beff,0xbdedbdcb,0xbe81be71,0xbeccbec2,0xbf10bf0a,
0xbc758000,0xbe0bbdf6,0xbe85be7a,0xbec9bec0,0xbd38bcf5,0xbe2abe1a,0xbe96be8d,0xbedbbed2,0xbd99bd75,0xbe4abe3a,0xbea6be9e,0xbeedbee4,0xbdd7bdb8,0xbe6abe5a,0xbeb7beaf,0xbf00bef6,
0xbc5c8000,0xbdf9bddd,0xbe6ebe5f,0xbeb3beab,0xbd25bcdc,0xbe18be0a,0xbe85be7c,0xbec2beba,0xbd8abd5c,0xbe35be26,0xbe94be8d,0xbed2beca,0xbdc1bda5,0xbe51be43,0xbea3be9c,0xbee2beda,
0xbc438000,0xbddcbdc3,0xbe52be45,0xbe9dbe96,0xbd12bcc3,0xbe07bdf5,0xbe6bbe5f,0xbeaabea3,0xbd74bd43,0xbe20be13,0xbe83be78,0xbeb8beb1,0xbdabbd92,0xbe39be2c,0xbe90be89,0xbec6bebf,
0xbc2a8000,0xbdbfbdaa,0xbe36be2b,0xbe88be82,0xbcffbcaa,0xbdeabdd5,0xbe4cbe41,0xbe93be8d,0xbd54bd2a,0xbe0bbe00,0xbe62be57,0xbe9fbe99,0xbd95bd7f,0xbe20be15,0xbe79be6d,0xbeaabea4,
0xbc118000,0xbda3bd91,0xbe1bbe11,0xbe66be5c,0xbcd9bc91,0xbdc7bdb5,0xbe2dbe24,0xbe79be6f,0xbd35bd11,0xbdecbdda,0xbe40be37,0xbe86be81,0xbd7dbd59,0xbe08bdfe,0xbe53be49,0xbe90be8b,
0xbbef8000,0xbd86bd6f,0xbdffbdf0,0xbe3dbe35,0xbcb3bc6f,0xbda5bd95,0xbe0fbe07,0xbe4cbe44,0xbd15bcef,0xbdc3bdb4,0xbe1ebe16,0xbe5cbe54,0xbd51bd33,0xbde1bdd2,0xbe2dbe26,0xbe6bbe63,
0xbbbc8000,0xbd54bd3d,0xbdc9bdbd,0xbe14be0e,0xbc8dbc3d,0xbd82bd6c,0xbde1bdd5,0xbe20be1a,0xbcecbcbd,0xbd99bd8e,0xbdf9bded,0xbe2cbe26,0xbd25bd0d,0xbdb1bda5,0xbe08be02,0xbe39be32,
0xbb8a8000,0xbd1cbd0a,0xbd93bd8a,0xbdd9bdd0,0xbc4fbc0a,0xbd3ebd2d,0xbda5bd9c,0xbdeabde2,0xbcadbc8a,0xbd61bd50,0xbdb6bdad,0xbdfcbdf3,0xbcf2bccf,0xbd82bd72,0xbdc7bdbf,0xbe07be02,
0xbb308000,0xbcc6bcb0,0xbd3bbd30,0xbd8abd84,0xbc04bbb0,0xbcf2bcdc,0xbd51bd46,0xbd95bd8f,0xbc5cbc30,0xbd0fbd04,0xbd67bd5c,0xbda0bd9a,0xbc9abc84,0xbd25bd1a,0xbd7dbd72,0xbdabbda5,
0xba978000,0xbc2abc17,0xbca0bc97,0xbcecbce2,0xbb62bb17,0xbc4fbc3d,0xbcb3bcaa,0xbcffbcf5,0xbbbcbb97,0xbc75bc62,0xbcc6bcbd,0xbd09bd04,0xbc04bbe2,0xbc8dbc84,0xbcd9bccf,0xbd12bd0d,
0x39c90000,0x3b623b49,0x3bd63bc9,0x3c1d3c17,0x3a973a49,0x3b8a3b7b,0x3bef3be2,0x3c2a3c23,0x3afb3ac9,0x3ba33b97,0x3c043bfb,0x3c363c30,0x3b303b17,0x3bbc3bb0,0x3c113c0a,0x3c433c3d,
0x3afb0000,0x3c8d3c7b,0x3d063cfb,0x3d453d3d,0x3bbc3b7b,0x3cad3c9d,0x3d153d0d,0x3d543d4c,0x3c1d3bfb,0x3ccc3cbd,0x3d253d1d,0x3d643d5c,0x3c5c3c3d,0x3cec3cdc,0x3d353d2d,0x3d743d6c,
0x3b620000,0x3cff3ce2,0x3d713d62,0x3db13daa,0x3c2a3be2,0x3d1c3d0d,0x3d863d7f,0x3dbf3db8,0x3c8d3c62,0x3d383d2a,0x3d953d8e,0x3dce3dc7,0x3cc63caa,0x3d543d46,0x3da33d9c,0x3ddc3dd5,
0x3ba30000,0x3d383d23,0x3dae3da4,0x3e003df6,0x3c753c23,0x3d613d4c,0x3dc33db8,0x3e0b3e05,0x3ccc3ca3,0x3d853d75,0x3dd73dcd,0x3e153e10,0x3d0f3cf5,0x3d993d8f,0x3dec3de2,0x3e203e1a,
0x3bd60000,0x3d713d56,0x3de43dd6,0x3e283e22,0x3ca03c56,0x3d933d86,0x3dff3df1,0x3e363e2f,0x3d063cd6,0x3dae3da1,0x3e0d3e06,0x3e443e3d,0x3d3b3d20,0x3dc93dbb,0x3e1b3e14,0x3e523e4b,
0x3c040000,0x3d953d84,0x3e0d3e05,0x3e513e48,0x3cc63c84,0x3db63da5,0x3e1e3e15,0x3e623e5a,0x3d253d04,0x3dd73dc7,0x3e2f3e26,0x3e743e6b,0x3d673d46,0x3df93de8,0x3e403e37,0x3e833e7c,
0x3c1d0000,0x3db13d9d,0x3e283e1e,0x3e7a3e70,0x3cec3c9d,0x3dd93dc5,0x3e3d3e32,0x3e883e82,0x3d453d1d,0x3e003ded,0x3e513e47,0x3e923e8d,0x3d8a3d6c,0x3e143e0a,0x3e663e5b,0x3e9d3e97,
0x3c360000,0x3dce3db7,0x3e443e38,0x3e923e8c,0x3d093cb6,0x3dfc3de5,0x3e5c3e50,0x3e9f3e98,0x3d643d36,0x3e153e09,0x3e743e68,0x3eab3ea5,0x3da03d89,0x3e2c3e21,0x3e863e80,0x3eb83eb1,
0x3c4f0000,0x3dea3dd0,0x3e603e52,0x3ea83ea0,0x3d1c3ccf,0x3e0f3e02,0x3e7b3e6d,0x3eb63eaf,0x3d823d50,0x3e2a3e1d,0x3e8b3e84,0x3ec53ebd,0x3db63d9c,0x3e453e37,0x3e993e92,0x3ed43ecc,
0x3c680000,0x3e033de9,0x3e7c3e6d,0x3ebe3eb5,0x3d2e3ce9,0x3e213e12,0x3e8d3e86,0x3ece3ec6,0x3d923d69,0x3e3f3e30,0x3e9d3e95,0x3edf3ed7,0x3dcc3daf,0x3e5d3e4e,0x3ead3ea5,0x3ef13ee8,
0x3c810000,0x3e123e01,0x3e8c3e84,0x3ed43ecb,0x3d413d01,0x3e333e22,0x3e9e3e95,0x3ee73ede,0x3da13d81,0x3e543e44,0x3eaf3ea7,0x3efb3ef1,0x3de23dc2,0x3e763e65,0x3ec23eb9,0x3f083f03,
0x3c8d0000,0x3e203e0e,0x3e9b3e91,0x3eec3ee1,0x3d543d0d,0x3e453e32,0x3eae3ea4,0x3f013ef6,0x3db13d8e,0x3e6a3e57,0x3ec23eb8,0x3f0c3f06,0x3df93dd5,0x3e883e7c,0x3ed73ecc,0x3f183f12,
0x3c9a0000,0x3e2f3e1b,0x3ea93e9f,0x3f023ef8,0x3d673d1a,0x3e573e43,0x3ebf3eb4,0x3f0e3f08,0x3dc13d9a,0x3e7f3e6b,0x3ed53eca,0x3f1b3f15,0x3e073de8,0x3e943e8a,0x3eec3ee1,0x3f293f22,
0x3ca70000,0x3e3d3e28,0x3eb83ead,0x3f0f3f08,0x3d7a3d27,0x3e693e53,0x3ed03ec4,0x3f1d3f15,0x3dd13da7,0x3e8b3e7f,0x3ee93edc,0x3f2b3f24,0x3e133dfb,0x3ea13e96,0x3f013ef6,0x3f3b3f33,
0x3cb30000,0x3e4c3e35,0x3ec83ebb,0x3f1c3f14,0x3d863d33,0x3e7b3e63,0x3ee23ed5,0x3f2b3f23,0x3de13db4,0x3e963e89,0x3efd3eef,0x3f3c3f34,0x3e1e3e07,0x3eae3ea2,0x3f0d3f06,0x3f4e3f45,
0x3cc00000,0x3e5b3e42,0x3ed73ec9,0x3f293f21,0x3d903d40,0x3e873e74,0x3ef43ee5,0x3f3b3f32,0x3df13dc0,0x3ea13e94,0x3f093f01,0x3f4e3f45,0x3e293e11,0x3ebb3eae,0x3f193f11,0x3f633f58,
0x3f7f3f80,0x3f653f6b,0x3f2a3f33,0x3eaa3ec1,0x3f7c3f7e,0x3f593f60,0x3f163f20,0x3e753e92,0x3f773f7a,0x3f4b3f53,0x3f023f0c,0x3e143e45,0x3f6f3f73,0x3f3b3f44,0x3ed83eee,0x3d463dc6,
0x3f7c3f7e,0x3f5d3f63,0x3f213f2a,0x3e9f3eb5,0x3f773f7a,0x3f503f57,0x3f0e3f18,0x3e663e89,0x3f713f74,0x3f423f49,0x3ef43f04,0x3e0b3e38,0x3f683f6c,0x3f323f3a,0x3ecb3ee0,0x3d393db9,
0x3f773f7a,0x3f533f59,0x3f173f20,0x3e953eaa,0x3f713f74,0x3f463f4d,0x3f053f0f,0x3e563e80,0x3f693f6d,0x3f383f3f,0x3ee53ef8,0x3e013e2c,0x3f5f3f64,0x3f283f30,0x3ebe3ed2,0x3d2d3dad,
0x3f703f73,0x3f483f4f,0x3f0e3f16,0x3e8a3e9e,0x3f683f6c,0x3f3b3f42,0x3ef93f05,0x3e473e6e,0x3f5f3f64,0x3f2d3f34,0x3ed63ee8,0x3df03e20,0x3f543f5a,0x3f1e3f26,0x3eb13ec3,0x3d203da0,
0x3f663f6a,0x3f3d3f43,0x3f043f0c,0x3e803e92,0x3f5d3f62,0x3f303f36,0x3ee73ef8,0x3e383e5c,0x3f543f59,0x3f223f29,0x3ec63ed7,0x3ddd3e13,0x3f493f4e,0x3f133f1b,0x3ea33eb5,0x3d143d94,
0x3f5a3f5f,0x3f303f36,0x3ef33f01,0x3e6a3e86,0x3f513f56,0x3f233f2a,0x3ed53ee4,0x3e283e49,0x3f473f4c,0x3f163f1d,0x3eb63ec5,0x3dca3e07,0x3f3c3f42,0x3f083f0f,0x3e963ea6,0x3d073d87,
0x3f4d3f51,0x3f233f28,0x3ede3eec,0x3e553e73,0x3f433f48,0x3f163f1d,0x3ec23ed0,0x3e193e37,0x3f393f3e,0x3f0a3f10,0x3ea53eb4,0x3db83df4,0x3f2e3f34,0x3ef93f03,0x3e883e97,0x3cf53d75,
0x3f3d3f42,0x3f143f1a,0x3ec93ed5,0x3e3f3e5a,0x3f343f39,0x3f093f0f,0x3eaf3ebc,0x3e093e24,0x3f2a3f2f,0x3efa3f03,0x3e953ea2,0x3da53ddb,0x3f1f3f25,0x3ee23eee,0x3e753e88,0x3cdc3d5c,
0x3f2c3f31,0x3f053f0a,0x3eb33ebe,0x3e2a3e42,0x3f233f28,0x3ef53f00,0x3e9c3ea7,0x3df33e12,0x3f193f1e,0x3ee03eea,0x3e843e90,0x3d923dc2,0x3f0f3f14,0x3ec93ed4,0x3e593e71,0x3cc33d43,
0x3f193f1d,0x3eeb3ef4,0x3e9c3ea7,0x3e143e29,0x3f113f15,0x3ed83ee1,0x3e883e92,0x3dd43dfe,0x3f083f0c,0x3ec43ece,0x3e673e7c,0x3d7e3da9,0x3efd3f03,0x3eb13eba,0x3e3e3e53,0x3caa3d2a,
0x3f053f09,0x3eca3ed2,0x3e863e8f,0x3dfc3e10,0x3efb3f01,0x3eb93ec2,0x3e693e7a,0x3db43dd8,0x3eeb3ef3,0x3ea83eb1,0x3e453e57,0x3d593d90,0x3edb3ee3,0x3e973ea0,0x3e223e34,0x3c913d10,
0x3ee03ee6,0x3ea83eaf,0x3e5e3e6d,0x3dd13dee,0x3ed23ed9,0x3e9a3ea1,0x3e413e4f,0x3d953db3,0x3ec43ecb,0x3e8c3e93,0x3e233e32,0x3d333d6f,0x3eb63ebd,0x3e7b3e85,0x3e063e15,0x3c6f3cef,
0x3eb33eb8,0x3e863e8c,0x3e303e3b,0x3da53dbc,0x3ea83ead,0x3e753e80,0x3e193e24,0x3d6b3d8d,0x3e9c3ea2,0x3e5e3e6a,0x3e013e0d,0x3d0d3d3c,0x3e913e97,0x3e473e53,0x3dd43deb,0x3c3c3cbc,
0x3e843e89,0x3e453e4e,0x3e013e0a,0x3d723d8a,0x3e783e80,0x3e343e3d,0x3de03df1,0x3d2d3d4f,0x3e673e70,0x3e233e2c,0x3dbe3dcf,0x3ccf3d0a,0x3e563e5f,0x3e123e1b,0x3d9b3dad,0x3c0a3c8a,
0x3e2a3e2f,0x3dfc3e04,0x3da53db0,0x3d1a3d30,0x3e1f3e24,0x3de63df1,0x3d8f3d9a,0x3cdc3d04,0x3e143e19,0x3dd13ddb,0x3d723d84,0x3c843cb0,0x3e093e0e,0x3dbb3dc6,0x3d463d5c,0x3bb03c30,
0x3d923d97,0x3d593d62,0x3d0d3d17,0x3c843c97,0x3d893d8d,0x3d463d4f,0x3cf53d04,0x3c3c3c62,0x3d7e3d84,0x3d333d3c,0x3ccf3ce2,0x3be23c17,0x3d6b3d75,0x3d203d2a,0x3caa3cbc,0x3b173b97,
0xbcc3bcc9,0xbc91bc97,0xbc3cbc49,0xbbb0bbc9,0xbcb6bcbc,0xbc84bc8a,0xbc23bc30,0xbb7bbb97,0xbcaabcb0,0xbc6fbc7b,0xbc0abc17,0xbb17bb49,0xbc9dbca3,0xbc56bc62,0xbbe2bbfb,0xba49bac9,
0xbdf3bdfb,0xbdb4bdbc,0xbd6bbd7b,0xbcdcbcfb,0xbde3bdeb,0xbda5bdad,0xbd4cbd5c,0xbc9dbcbc,0xbdd4bddb,0xbd95bd9d,0xbd2dbd3c,0xbc3cbc7b,0xbdc4bdcc,0xbd85bd8d,0xbd0dbd1d,0xbb7bbbfb,
0xbe59be60,0xbe22be29,0xbdd4bde2,0xbd46bd62,0xbe4cbe53,0xbe14be1b,0xbdb8bdc6,0xbd0dbd2a,0xbe3ebe45,0xbe06be0d,0xbd9bbda9,0xbcaabce2,0xbe30be37,0xbdf0bdfe,0xbd7ebd8d,0xbbe2bc62,
0xbe9cbea1,0xbe69be73,0xbe19be23,0xbd8fbda3,0xbe92be97,0xbe55be5f,0xbe04be0e,0xbd4cbd75,0xbe88be8d,0xbe41be4b,0xbde0bdf4,0xbcf5bd23,0xbe7dbe83,0xbe2dbe37,0xbdb8bdcc,0xbc23bca3,
0xbec9becf,0xbe97be9e,0xbe47be54,0xbdbbbdd5,0xbebdbec3,0xbe8abe91,0xbe2dbe3a,0xbd85bda0,0xbeb1beb7,0xbe7bbe84,0xbe12be20,0xbd20bd56,0xbea4beaa,0xbe61be6e,0xbdf0be05,0xbc56bcd6,
0xbef5befc,0xbeb9bec1,0xbe75be82,0xbde6be04,0xbee7beee,0xbeaabeb2,0xbe55be65,0xbda5bdc6,0xbed8bedf,0xbe9abea2,0xbe34be45,0xbd46bd84,0xbec9bed0,0xbe8abe92,0xbe14be24,0xbc84bd04,
0xbf0fbf13,0xbedbbee3,0xbe91be9b,0xbe09be1c,0xbf07bf0b,0xbec9bed2,0xbe7dbe88,0xbdc4bdeb,0xbefdbf03,0xbeb6bec0,0xbe56be6a,0xbd6bbd9d,0xbeecbef5,0xbea4bead,0xbe30be43,0xbc9dbd1d,
0xbf23bf27,0xbefbbf02,0xbea8beb2,0xbe1fbe35,0xbf1abf1e,0xbee7bef1,0xbe92be9d,0xbde3be08,0xbf11bf15,0xbed2bedc,0xbe78be87,0xbd89bdb6,0xbf07bf0c,0xbebdbec8,0xbe4cbe62,0xbcb6bd36,
0xbf35bf39,0xbf0dbf12,0xbebebeca,0xbe34be4e,0xbf2bbf30,0xbf02bf07,0xbea5beb2,0xbe01be1b,0xbf22bf27,0xbeedbef8,0xbe8dbe99,0xbd9bbdcf,0xbf17bf1d,0xbed6bee1,0xbe67be80,0xbccfbd4f,
0xbf45bf4a,0xbf1bbf21,0xbed3bee1,0xbe4abe66,0xbf3cbf41,0xbf10bf16,0xbeb9bec6,0xbe11be2e,0xbf32bf37,0xbf03bf0a,0xbe9dbeab,0xbdaebde8,0xbf27bf2c,0xbeeebefa,0xbe81be8f,0xbce8bd68,
0xbf54bf58,0xbf29bf2f,0xbee9bef7,0xbe60be7f,0xbf4abf4f,0xbf1dbf23,0xbeccbeda,0xbe20be40,0xbf40bf45,0xbf10bf17,0xbeaebebd,0xbdc1be00,0xbf35bf3b,0xbf02bf09,0xbe8fbe9e,0xbd01bd81,
0xbf61bf65,0xbf37bf3d,0xbefdbf06,0xbe75be8c,0xbf58bf5c,0xbf2abf30,0xbedebeee,0xbe30be53,0xbf4ebf53,0xbf1cbf23,0xbebebece,0xbdd4be0d,0xbf42bf48,0xbf0ebf15,0xbe9cbead,0xbd0dbd8d,
0xbf6bbf6f,0xbf43bf49,0xbf09bf11,0xbe85be98,0xbf63bf67,0xbf36bf3c,0xbef0bf01,0xbe3fbe65,0xbf59bf5e,0xbf28bf2f,0xbecebedf,0xbde6be19,0xbf4fbf54,0xbf19bf20,0xbeaabebc,0xbd1abd9a,
0xbf74bf77,0xbf4ebf54,0xbf13bf1b,0xbe90bea4,0xbf6dbf70,0xbf41bf48,0xbf01bf0a,0xbe4fbe77,0xbf64bf68,0xbf33bf3a,0xbeddbef0,0xbdf9be26,0xbf5abf5f,0xbf23bf2b,0xbeb7beca,0xbd26bda6,
0xbf7abf7c,0xbf58bf5e,0xbf1cbf25,0xbe9abeaf,0xbf74bf77,0xbf4bbf52,0xbf0abf13,0xbe5ebe85,0xbf6dbf71,0xbf3dbf44,0xbeedbf00,0xbe06be32,0xbf63bf68,0xbf2dbf35,0xbec4bed9,0xbd33bdb3,
0xbf7ebf7f,0xbf61bf67,0xbf25bf2e,0xbea5bebb,0xbf7abf7c,0xbf55bf5b,0xbf12bf1c,0xbe6dbe8e,0xbf74bf77,0xbf47bf4e,0xbefcbf08,0xbe0fbe3f,0xbf6cbf70,0xbf37bf3f,0xbed1bee7,0xbd40bdbf,
0xbd468000,0xbed8bec1,0xbf3bbf33,0xbf6fbf6b,0xbe14bdc6,0xbf02beee,0xbf4bbf44,0xbf77bf73,0xbe75be45,0xbf16bf0c,0xbf59bf53,0xbf7cbf7a,0xbeaabe92,0xbf2abf20,0xbf65bf60,0xbf7fbf7e,
0xbd398000,0xbecbbeb5,0xbf32bf2a,0xbf68bf63,0xbe0bbdb9,0xbef4bee0,0xbf42bf3a,0xbf71bf6c,0xbe66be38,0xbf0ebf04,0xbf50bf49,0xbf77bf74,0xbe9fbe89,0xbf21bf18,0xbf5dbf57,0xbf7cbf7a,
0xbd2d8000,0xbebebeaa,0xbf28bf20,0xbf5fbf59,0xbe01bdad,0xbee5bed2,0xbf38bf30,0xbf69bf64,0xbe56be2c,0xbf05bef8,0xbf46bf3f,0xbf71bf6d,0xbe95be80,0xbf17bf0f,0xbf53bf4d,0xbf77bf74,
0xbd208000,0xbeb1be9e,0xbf1ebf16,0xbf54bf4f,0xbdf0bda0,0xbed6bec3,0xbf2dbf26,0xbf5fbf5a,0xbe47be20,0xbef9bee8,0xbf3bbf34,0xbf68bf64,0xbe8abe6e,0xbf0ebf05,0xbf48bf42,0xbf70bf6c,
0xbd148000,0xbea3be92,0xbf13bf0c,0xbf49bf43,0xbdddbd94,0xbec6beb5,0xbf22bf1b,0xbf54bf4e,0xbe38be13,0xbee7bed7,0xbf30bf29,0xbf5dbf59,0xbe80be5c,0xbf04bef8,0xbf3dbf36,0xbf66bf62,
0xbd078000,0xbe96be86,0xbf08bf01,0xbf3cbf36,0xbdcabd87,0xbeb6bea6,0xbf16bf0f,0xbf47bf42,0xbe28be07,0xbed5bec5,0xbf23bf1d,0xbf51bf4c,0xbe6abe49,0xbef3bee4,0xbf30bf2a,0xbf5abf56,
0xbcf58000,0xbe88be73,0xbef9beec,0xbf2ebf28,0xbdb8bd75,0xbea5be97,0xbf0abf03,0xbf39bf34,0xbe19bdf4,0xbec2beb4,0xbf16bf10,0xbf43bf3e,0xbe55be37,0xbedebed0,0xbf23bf1d,0xbf4dbf48,
0xbcdc8000,0xbe75be5a,0xbee2bed5,0xbf1fbf1a,0xbda5bd5c,0xbe95be88,0xbefabeee,0xbf2abf25,0xbe09bddb,0xbeafbea2,0xbf09bf03,0xbf34bf2f,0xbe3fbe24,0xbec9bebc,0xbf14bf0f,0xbf3dbf39,
0xbcc38000,0xbe59be42,0xbec9bebe,0xbf0fbf0a,0xbd92bd43,0xbe84be71,0xbee0bed4,0xbf19bf14,0xbdf3bdc2,0xbe9cbe90,0xbef5beea,0xbf23bf1e,0xbe2abe12,0xbeb3bea7,0xbf05bf00,0xbf2cbf28,
0xbcaa8000,0xbe3ebe29,0xbeb1bea7,0xbefdbef4,0xbd7ebd2a,0xbe67be53,0xbec4beba,0xbf08bf03,0xbdd4bda9,0xbe88be7c,0xbed8bece,0xbf11bf0c,0xbe14bdfe,0xbe9cbe92,0xbeebbee1,0xbf19bf15,
0xbc918000,0xbe22be10,0xbe97be8f,0xbedbbed2,0xbd59bd10,0xbe45be34,0xbea8bea0,0xbeebbee3,0xbdb4bd90,0xbe69be57,0xbeb9beb1,0xbefbbef3,0xbdfcbdd8,0xbe86be7a,0xbecabec2,0xbf05bf01,
0xbc6f8000,0xbe06bdee,0xbe7bbe6d,0xbeb6beaf,0xbd33bcef,0xbe23be15,0xbe8cbe85,0xbec4bebd,0xbd95bd6f,0xbe41be32,0xbe9abe93,0xbed2becb,0xbdd1bdb3,0xbe5ebe4f,0xbea8bea1,0xbee0bed9,
0xbc3c8000,0xbdd4bdbc,0xbe47be3b,0xbe91be8c,0xbd0dbcbc,0xbe01bdeb,0xbe5ebe53,0xbe9cbe97,0xbd6bbd3c,0xbe19be0d,0xbe75be6a,0xbea8bea2,0xbda5bd8d,0xbe30be24,0xbe86be80,0xbeb3bead,
0xbc0a8000,0xbd9bbd8a,0xbe12be0a,0xbe56be4e,0xbccfbc8a,0xbdbebdad,0xbe23be1b,0xbe67be5f,0xbd2dbd0a,0xbde0bdcf,0xbe34be2c,0xbe78be70,0xbd72bd4f,0xbe01bdf1,0xbe45be3d,0xbe84be80,
0xbbb08000,0xbd46bd30,0xbdbbbdb0,0xbe09be04,0xbc84bc30,0xbd72bd5c,0xbdd1bdc6,0xbe14be0e,0xbcdcbcb0,0xbd8fbd84,0xbde6bddb,0xbe1fbe19,0xbd1abd04,0xbda5bd9a,0xbdfcbdf1,0xbe2abe24,
0xbb178000,0xbcaabc97,0xbd20bd17,0xbd6bbd62,0xbbe2bb97,0xbccfbcbc,0xbd33bd2a,0xbd7ebd75,0xbc3cbc17,0xbcf5bce2,0xbd46bd3c,0xbd89bd84,0xbc84bc62,0xbd0dbd04,0xbd59bd4f,0xbd92bd8d,
0x3a490000,0x3be23bc9,0x3c563c49,0x3c9d3c97,0x3b173ac9,0x3c0a3bfb,0x3c6f3c62,0x3caa3ca3,0x3b7b3b49,0x3c233c17,0x3c843c7b,0x3cb63cb0,0x3bb03b97,0x3c3c3c30,0x3c913c8a,0x3cc33cbc,
0x3b7b0000,0x3d0d3cfb,0x3d853d7b,0x3dc43dbc,0x3c3c3bfb,0x3d2d3d1d,0x3d953d8d,0x3dd43dcc,0x3c9d3c7b,0x3d4c3d3c,0x3da53d9d,0x3de33ddb,0x3cdc3cbc,0x3d6b3d5c,0x3db43dad,0x3df33deb,
0x3be20000,0x3d7e3d62,0x3df03de2,0x3e303e29,0x3caa3c62,0x3d9b3d8d,0x3e063dfe,0x3e3e3e37,0x3d0d3ce2,0x3db83da9,0x3e143e0d,0x3e4c3e45,0x3d463d2a,0x3dd43dc6,0x3e223e1b,0x3e593e53,
0x3c230000,0x3db83da3,0x3e2d3e23,0x3e7d3e73,0x3cf53ca3,0x3de03dcc,0x3e413e37,0x3e883e83,0x3d4c3d23,0x3e043df4,0x3e553e4b,0x3e923e8d,0x3d8f3d75,0x3e193e0e,0x3e693e5f,0x3e9c3e97,
0x3c560000,0x3df03dd5,0x3e613e54,0x3ea43e9e,0x3d203cd6,0x3e123e05,0x3e7b3e6e,0x3eb13eaa,0x3d853d56,0x3e2d3e20,0x3e8a3e84,0x3ebd3eb7,0x3dbb3da0,0x3e473e3a,0x3e973e91,0x3ec93ec3,
0x3c840000,0x3e143e04,0x3e8a3e82,0x3ec93ec1,0x3d463d04,0x3e343e24,0x3e9a3e92,0x3ed83ed0,0x3da53d84,0x3e553e45,0x3eaa3ea2,0x3ee73edf,0x3de63dc6,0x3e753e65,0x3eb93eb2,0x3ef53eee,
0x3c9d0000,0x3e303e1c,0x3ea43e9b,0x3eec3ee3,0x3d6b3d1d,0x3e563e43,0x3eb63ead,0x3efd3ef5,0x3dc43d9d,0x3e7d3e6a,0x3ec93ec0,0x3f073f03,0x3e093deb,0x3e913e88,0x3edb3ed2,0x3f0f3f0b,
0x3cb60000,0x3e4c3e35,0x3ebd3eb2,0x3f073f02,0x3d893d36,0x3e783e62,0x3ed23ec8,0x3f113f0c,0x3de33db6,0x3e923e87,0x3ee73edc,0x3f1a3f15,0x3e1f3e08,0x3ea83e9d,0x3efb3ef1,0x3f233f1e,
0x3ccf0000,0x3e673e4e,0x3ed63eca,0x3f173f12,0x3d9b3d4f,0x3e8d3e80,0x3eed3ee1,0x3f223f1d,0x3e013dcf,0x3ea53e99,0x3f023ef8,0x3f2b3f27,0x3e343e1b,0x3ebe3eb2,0x3f0d3f07,0x3f353f30,
0x3ce80000,0x3e813e66,0x3eee3ee1,0x3f273f21,0x3dae3d68,0x3e9d3e8f,0x3f033efa,0x3f323f2c,0x3e113de8,0x3eb93eab,0x3f103f0a,0x3f3c3f37,0x3e4a3e2e,0x3ed33ec6,0x3f1b3f16,0x3f453f41,
0x3d010000,0x3e8f3e7f,0x3f023ef7,0x3f353f2f,0x3dc13d81,0x3eae3e9e,0x3f103f09,0x3f403f3b,0x3e203e00,0x3ecc3ebd,0x3f1d3f17,0x3f4a3f45,0x3e603e40,0x3ee93eda,0x3f293f23,0x3f543f4f,
0x3d0d0000,0x3e9c3e8c,0x3f0e3f06,0x3f423f3d,0x3dd43d8d,0x3ebe3ead,0x3f1c3f15,0x3f4e3f48,0x3e303e0d,0x3ede3ece,0x3f2a3f23,0x3f583f53,0x3e753e53,0x3efd3eee,0x3f373f30,0x3f613f5c,
0x3d1a0000,0x3eaa3e98,0x3f193f11,0x3f4f3f49,0x3de63d9a,0x3ece3ebc,0x3f283f20,0x3f593f54,0x3e3f3e19,0x3ef03edf,0x3f363f2f,0x3f633f5e,0x3e853e65,0x3f093f01,0x3f433f3c,0x3f6b3f67,
0x3d260000,0x3eb73ea4,0x3f233f1b,0x3f5a3f54,0x3df93da6,0x3edd3eca,0x3f333f2b,0x3f643f5f,0x3e4f3e26,0x3f013ef0,0x3f413f3a,0x3f6d3f68,0x3e903e77,0x3f133f0a,0x3f4e3f48,0x3f743f70,
0x3d330000,0x3ec43eaf,0x3f2d3f25,0x3f633f5e,0x3e063db3,0x3eed3ed9,0x3f3d3f35,0x3f6d3f68,0x3e5e3e32,0x3f0a3f00,0x3f4b3f44,0x3f743f71,0x3e9a3e85,0x3f1c3f13,0x3f583f52,0x3f7a3f77,
0x3d400000,0x3ed13ebb,0x3f373f2e,0x3f6c3f67,0x3e0f3dbf,0x3efc3ee7,0x3f473f3f,0x3f743f70,0x3e6d3e3f,0x3f123f08,0x3f553f4e,0x3f7a3f77,0x3ea53e8e,0x3f253f1c,0x3f613f5b,0x3f7e3f7c
};
#define DBG_END(z)
#define TS(i)
#define TZ(z, i)

struct Params {
  alignas(64) CUtensorMap x_g1, w1_a, w1_b2, w1_b1, k, v, w1_cs, kvz, h_st, h_st2, w2, h_ld, y_ld, x_ep, out_st, f_ld, y_st;
  const bf16 *x, *shift_k, *ssm_k, *ssm_D, *b1, *b2, *w2p, *w1p;
  bf16* kvZ;
  const uint32_t* tab;
  uint2 *stats, *cs;
  unsigned* flags;
  unsigned zero;
  unsigned char cnt[72];
  uchar4 map[NCTA];
};

constexpr int G1_W = 28672, G1_X = 16384, G1_NST = 4, OFF_X = G1_NST * G1_W;
constexpr int G2_STAGE = G1_W, G2_B = 16384, G2_NST = 6;
constexpr int CS_STAGE = 57344;
constexpr int RING = G1_NST * (G1_W + G1_X);
constexpr int OFF_C = RING;
constexpr int OFF_SR = OFF_C;
constexpr int OFF_DFT = OFF_C, OFF_G = OFF_C + 8192;
constexpr int KV_SLOT = 35 * 256, KV_V = 19 * 256;
constexpr int OFF_KVS = OFF_C + 20480, OFF_KV = OFF_KVS + 4096;
constexpr int OFF_KV4 = OFF_C + 20480 - KV_SLOT;
constexpr int OFF_T0 = K4E == 4 ? OFF_C + 28672 : K4E % 3 ? OFF_KV : OFF_C + 12288, OFF_T1 = OFF_C + (K4E == 4 ? 20480 : 34816), OFF_T2 = K4E == 4 ? OFF_C + 36864 : K4E == 2 ? OFF_C + 12288 : K4E == 1 ? OFF_T0 : OFF_C + 20480, OFF_T3 = OFF_X + 57344, OFF_T4 = K4E == 2 ? OFF_T0 : OFF_C + 12288;
constexpr int OFF_Y0 = K4E == 4 ? OFF_T0 : K4E % 3 ? OFF_KVS : OFF_C + 28672;
constexpr int OFF_XT = OFF_C + (PRE == 2 ? 28672 : 20480), XT_STEP = PRE == 2 ? 10240 : 13312, OFF_YT = OFF_C;
constexpr int OFF_EXT = 224256;
constexpr int OFF_ST1 = OFF_EXT + 3584;
constexpr int OFF_ST2 = OFF_ST1 + 2048;
constexpr int OFF_MISC = OFF_ST2 + 800;
constexpr int OFF_BAR = OFF_MISC + 32;
enum { B_FULL1 = 0  , B_KV = 4  , B_STAT = 6, B_FIRST = 7, B_EMPTY1 = 7  , B_FULL2 = 11  , B_EMPTY2 = 17  , B_G1FREE = 23, B_CX = 24  , B_RD = 29  ,
       B_EPOCH = 34, B_SKEW = 35, B_TAB = 36, B_EP = 37, B_EPY = 38, B_KVS = 39  , B_GO = 42, B_DONE = 43, B_STATFREE = 44, B_HS = 45  ,
       B_KVR = 53, B_LATE = 54, B_DFT = 55, B_HB = 56, B_H1 = 57, B_VD = 58, B_RT = 59, B_KV4 = 60, B_KVC = 61, B_DBG = 62, B_BAD = 63, B_XF = 64, B_T2 = 65, B_COUNT = 66 };
constexpr int OFF_POLL = OFF_BAR + B_COUNT * 8;
constexpr int OFF_DBG = OFF_POLL + 192;
constexpr int SMEM_BYTES = OFF_DBG + (DBG_TIME ? 768 : 0);
static_assert(SMEM_BYTES <= 232448 && OFF_POLL % 16 == 0, "smem");
static_assert(OFF_XT + XT_STEP + 10240 <= (PRE == 2 ? OFF_ST2 : OFF_EXT) && (PRE != 2 || OFF_T2 + 8192 <= OFF_XT) && OFF_KV + 2 * KV_SLOT <= OFF_EXT && (K4E == 4 ? OFF_T2 + 8192 <= OFF_ST1 && OFF_T0 + 8192 <= OFF_KV + KV_SLOT + KV_V : OFF_T1 + 8192 <= OFF_EXT && OFF_T1 >= OFF_KV + KV_SLOT && OFF_T2 + 8192 <= OFF_KV + KV_SLOT) && OFF_KV4 % 128 == 0, "layout");
static_assert(OFF_EXT % 1024 == 0 && OFF_XT % 1024 == 0 && XT_STEP % 1024 == 0 && OFF_T1 % 1024 == 0 && 5 * G2_STAGE + 26624 <= OFF_T3 && 3 * CS_STAGE <= RING, "layout");

#define DEV __device__ __forceinline__
#define HD __host__ __device__ constexpr
DEV uint32_t smem_u32(const void* p) { return (uint32_t)__cvta_generic_to_shared(p); }
DEV uint64_t make_desc(uint32_t addr, uint32_t lbo, uint32_t sbo, uint32_t swz) {
  uint64_t d;
  asm volatile("mov.b64 %0, {%1, %2};" : "=l"(d) : "r"(((addr & 0x3FFFF) >> 4) | ((lbo >> 4) << 16)), "r"((sbo >> 4) | (swz << 30)));
  return d;
}
DEV void wg_fence() { asm volatile("wgmma.fence.sync.aligned;" ::: "memory"); }
DEV void wg_commit() { asm volatile("wgmma.commit_group.sync.aligned;" ::: "memory"); }
template <int n> DEV void wg_wait() { asm volatile("wgmma.wait_group.sync.aligned %0;" ::"n"(n) : "memory"); }
DEV void mbar_init(uint32_t bar, int cnt) { asm volatile("mbarrier.init.shared::cta.b64 [%0], %1;" ::"r"(bar), "r"(cnt) : "memory"); }
DEV void mbar_expect(uint32_t bar, int bytes) { asm volatile("mbarrier.arrive.expect_tx.shared::cta.b64 _, [%0], %1;" ::"r"(bar), "r"(bytes) : "memory"); }
DEV void mbar_arrive(uint32_t bar) { asm volatile("mbarrier.arrive.shared::cta.b64 _, [%0];" ::"r"(bar) : "memory"); }
DEV void mbar_wait(uint32_t bar, uint32_t parity) {
  asm volatile("{\n.reg .pred p;\nW: mbarrier.try_wait.parity.shared::cta.b64 p, [%0], %1;\n@p bra X;\nbra W;\nX:\n}" ::"r"(bar), "r"(parity) : "memory");
}
DEV bool mbar_test(uint32_t bar, uint32_t parity) {
  uint32_t r;
  asm volatile("{\n.reg .pred p;\nmbarrier.test_wait.parity.shared::cta.b64 p, [%1], %2;\nselp.u32 %0, 1, 0, p;\n}" : "=r"(r) : "r"(bar), "r"(parity) : "memory");
  return __any_sync(0xffffffffu, r);
}
DEV void mbar_wait_b(uint32_t bar, uint32_t parity) {
  asm volatile("{\n.reg .pred p;\n.reg .u32 i;\nmov.u32 i, 0;\n"
               "W: mbarrier.try_wait.parity.shared::cta.b64 p, [%0], %1;\n@p bra X;\nadd.u32 i, i, 1;\nsetp.lt.u32 p, i, 262144;\n@p bra W;\ntrap;\nX:\n}"
               ::"r"(bar), "r"(parity) : "memory");
}
template <int G> DEV void grid_wait() {
  if (G) asm volatile("{\n.reg .pred p;\n.reg .u32 a, b;\nmov.u32 a, %%clock;\nW: mov.u32 b, %%clock;\nxor.b32 b, b, a;\nsetp.lt.u32 p, b, %0;\n@p bra W;\n}" ::"n"(G) : "memory");
}
DEV void clk_wait(int n) {
  if (n) asm volatile("{\n.reg .pred p;\n.reg .u32 a, b;\nmov.u32 a, %%clock;\nW: mov.u32 b, %%clock;\nsub.u32 b, b, a;\nsetp.lt.u32 p, b, %0;\n@p bra W;\n}" ::"r"(n) : "memory");
}
DEV void trap_above(int n, int lim) { asm volatile("{\n.reg .pred p;\nsetp.gt.s32 p, %0, %1;\n@p trap;\n}" ::"r"(n), "r"(lim)); }
DEV unsigned flag_load(const unsigned* p) {
  unsigned v;
  asm volatile("ld.acquire.gpu.global.u32 %0, [%1];" : "=r"(v) : "l"(p) : "memory");
  return v;
}
template <bool BOUNDED> DEV void flag_wait(const unsigned* p, unsigned target) {
#pragma unroll 1
  for (int i = 0; !BOUNDED || i < (1 << 22); i++)
    if ((int)(flag_load(p) - target) >= 0) return;
  __trap();
}
template <bool BOUNDED> DEV void flag_poll(const unsigned* p, unsigned target, uint32_t buf) {
  asm volatile("{\n.reg .pred q;\n.reg .u32 a, t;\n"
               "cp.async.wait_group 0;\ncp.async.cg.shared.global [%5+0], [%0], 16;\ncp.async.commit_group;\nmov.u32 t, %%clock;\n"
               "W1: mov.u32 a, %%clock;\nsub.u32 a, a, t;\nsetp.lt.u32 q, a, %2;\n@q bra W1;\ncp.async.cg.shared.global [%5+16], [%0], 16;\ncp.async.commit_group;\n"
               "W2: mov.u32 a, %%clock;\nsub.u32 a, a, t;\nsetp.lt.u32 q, a, %3;\n@q bra W2;\ncp.async.cg.shared.global [%5+32], [%0], 16;\ncp.async.commit_group;\nmov.u32 t, 0;\n"
               "L: cp.async.wait_group 2;\nld.volatile.shared.u32 a, [%5+0];\nsub.u32 a, a, %1;\nsetp.ge.s32 q, a, 0;\n@q bra X;\ncp.async.cg.shared.global [%5+0], [%0], 16;\ncp.async.commit_group;\n"
               "cp.async.wait_group 2;\nld.volatile.shared.u32 a, [%5+16];\nsub.u32 a, a, %1;\nsetp.ge.s32 q, a, 0;\n@q bra X;\ncp.async.cg.shared.global [%5+16], [%0], 16;\ncp.async.commit_group;\n"
               "cp.async.wait_group 2;\nld.volatile.shared.u32 a, [%5+32];\nsub.u32 a, a, %1;\nsetp.ge.s32 q, a, 0;\n@q bra X;\ncp.async.cg.shared.global [%5+32], [%0], 16;\ncp.async.commit_group;\n"
               "add.u32 t, t, %4;\nsetp.lt.u32 q, t, 4194304;\n@q bra L;\ntrap;\nX:\n}"
               ::"l"(p), "r"(target), "n"(PD), "n"(2 * PD), "n"(BOUNDED ? 1 : 0), "r"(buf) : "memory");
}
DEV void tag_store(uint2* p, float a, float b, unsigned ep) {
  const unsigned long long v = (unsigned long long)__float_as_uint(a) | ((unsigned long long)((__float_as_uint(b) & ~255u) | (ep & 255u)) << 32);
  asm volatile("st.relaxed.gpu.global.u64 [%0], %1;" ::"l"(p), "l"(v) : "memory");
}
DEV uint2 tag_load(const uint2* p) { uint2 v; asm volatile("{\n.reg .b64 t;\nld.relaxed.gpu.global.b64 t, [%2];\nmov.b64 {%0,%1}, t;\n}" : "=r"(v.x), "=r"(v.y) : "l"(p) : "memory"); return v; }
template <int N> DEV void tag_wait(const uint2* const (&p)[N], uint2 (&v)[N], unsigned ep) {
#pragma unroll 1
  for (;;) {
    unsigned bad = 0;
#pragma unroll
    for (int j = 0; j < N; j++) bad |= v[j].y ^ ep;
    if (!__any_sync(0xffffffffu, (bad & 255u) != 0)) break;
#pragma unroll
    for (int j = 0; j < N; j++) v[j] = tag_load(p[j]);
  }
#pragma unroll
  for (int j = 0; j < N; j++) v[j].y &= ~255u;
}
template <int N> DEV void tag_wait2(const uint2* const (&p)[N], uint2 (&v)[N], unsigned ep) {
  uint2 w[N];
  clk_wait(TD);
#pragma unroll
  for (int j = 0; j < N; j++) w[j] = tag_load(p[j]);
#pragma unroll 1
  for (;;) {
    unsigned bad = 0;
#pragma unroll
    for (int j = 0; j < N; j++) bad |= v[j].y ^ ep;
    if (!__any_sync(0xffffffffu, (bad & 255u) != 0)) break;
#pragma unroll
    for (int j = 0; j < N; j++) v[j] = tag_load(p[j]);
    bad = 0;
#pragma unroll
    for (int j = 0; j < N; j++) bad |= w[j].y ^ ep;
    if (!__any_sync(0xffffffffu, (bad & 255u) != 0)) {
#pragma unroll
      for (int j = 0; j < N; j++) v[j] = w[j];
      break;
    }
#pragma unroll
    for (int j = 0; j < N; j++) w[j] = tag_load(p[j]);
  }
#pragma unroll
  for (int j = 0; j < N; j++) v[j].y &= ~255u;
}
#define REL 4
DEV void pub_fence(int bit) { if (REL & bit) asm volatile("fence.acq_rel.gpu;" ::: "memory"); }
DEV void flag_add_rlx(unsigned* p, unsigned n) { asm volatile("red.relaxed.gpu.global.add.u32 [%0], %1;" ::"l"(p), "r"(n) : "memory"); }
DEV void flag_add_all(unsigned* p, int n) {
#pragma unroll
  for (int r = 0; r < n; r++) flag_add_rlx(p + 32 * r, 1);
}
DEV void fence_async_smem() { asm volatile("fence.proxy.async.shared::cta;" ::: "memory"); }
#define RF 15
DEV void wfence(int bit) { if (!(RF & bit)) fence_async_smem(); }
DEV void rfence(int bit) { if ((RF & bit) && !(RF & 16)) fence_async_smem(); }
DEV void fence_async_global() { asm volatile("fence.proxy.async.global;" ::: "memory"); }
DEV void bar_sync(int id) { asm volatile("bar.sync %0, 128;" ::"r"(id) : "memory"); }
DEV bool elect() {
  uint32_t p;
  asm volatile("{\n.reg .pred p;\nelect.sync _|p, 0xffffffff;\nselp.u32 %0, 1, 0, p;\n}" : "=r"(p));
  return p;
}
DEV void warp_arrive(uint32_t bar) { __syncwarp(); if (elect()) mbar_arrive(bar); }
DEV void bulk_g2s(uint32_t dst, const void* src, int bytes, uint32_t bar) {
  asm volatile("cp.async.bulk.shared::cluster.global.mbarrier::complete_tx::bytes [%0], [%1], %2, [%3];" ::"r"(dst), "l"(src), "r"(bytes), "r"(bar) : "memory");
}
DEV void bulk_s2g(void* dst, uint32_t src, int bytes) { asm volatile("cp.async.bulk.global.shared::cta.bulk_group [%0], [%1], %2;" ::"l"(dst), "r"(src), "r"(bytes) : "memory"); }
DEV void bulk_prefetch(const void* src, int bytes) { asm volatile("cp.async.bulk.prefetch.L2.global [%0], %1;" ::"l"(src), "r"(bytes) : "memory"); }
DEV void tma2d(uint32_t dst, const CUtensorMap* m, int c0, int c1, uint32_t bar) {
  asm volatile("cp.async.bulk.tensor.2d.shared::cluster.global.mbarrier::complete_tx::bytes [%0], [%1, {%3, %4}], [%2];" ::"r"(dst), "l"(m), "r"(bar), "r"(c0), "r"(c1) : "memory");
}
DEV void tma3d(uint32_t dst, const CUtensorMap* m, int c0, int c1, int c2, uint32_t bar) {
  asm volatile("cp.async.bulk.tensor.3d.shared::cluster.global.mbarrier::complete_tx::bytes [%0], [%1, {%3, %4, %5}], [%2];" ::"r"(dst), "l"(m), "r"(bar), "r"(c0), "r"(c1), "r"(c2) : "memory");
}
DEV void tma2d_st(const CUtensorMap* m, int c0, int c1, uint32_t src) {
  asm volatile("cp.async.bulk.tensor.2d.global.shared::cta.bulk_group [%0, {%2, %3}], [%1];" ::"l"(m), "r"(src), "r"(c0), "r"(c1) : "memory");
}
DEV void bulk_commit() { asm volatile("cp.async.bulk.commit_group;" ::: "memory"); }
DEV void bulk_wait_read() { asm volatile("cp.async.bulk.wait_group.read 0;" ::: "memory"); }
DEV void bulk_wait_all() { asm volatile("cp.async.bulk.wait_group 0;" ::: "memory"); }
DEV void prefetch_map(const CUtensorMap* m) { asm volatile("prefetch.tensormap [%0];" ::"l"(m) : "memory"); }
DEV uint32_t lds32(uint32_t a) { uint32_t v; asm volatile("ld.shared.b32 %0, [%1];" : "=r"(v) : "r"(a) : "memory"); return v; }
DEV uint2 lds64(uint32_t a) { uint2 v; asm volatile("ld.shared.v2.b32 {%0,%1}, [%2];" : "=r"(v.x), "=r"(v.y) : "r"(a) : "memory"); return v; }
DEV uint4 lds128(uint32_t a) { uint4 v; asm volatile("ld.shared.v4.b32 {%0,%1,%2,%3}, [%4];" : "=r"(v.x), "=r"(v.y), "=r"(v.z), "=r"(v.w) : "r"(a) : "memory"); return v; }
DEV void sts32(uint32_t a, uint32_t v) { asm volatile("st.shared.b32 [%0], %1;" ::"r"(a), "r"(v) : "memory"); }
DEV void sts128(uint32_t a, uint4 v) { asm volatile("st.shared.v4.b32 [%0], {%1,%2,%3,%4};" ::"r"(a), "r"(v.x), "r"(v.y), "r"(v.z), "r"(v.w) : "memory"); }
DEV void stsm4(uint32_t a, uint32_t r0, uint32_t r1, uint32_t r2, uint32_t r3) { asm volatile("stmatrix.sync.aligned.m8n8.x4.shared.b16 [%0], {%1,%2,%3,%4};" ::"r"(a), "r"(r0), "r"(r1), "r"(r2), "r"(r3) : "memory"); }
DEV void stsm4t(uint32_t a, uint32_t r0, uint32_t r1, uint32_t r2, uint32_t r3) { asm volatile("stmatrix.sync.aligned.m8n8.x4.trans.shared.b16 [%0], {%1,%2,%3,%4};" ::"r"(a), "r"(r0), "r"(r1), "r"(r2), "r"(r3) : "memory"); }
DEV void ldsm4(uint32_t a, uint32_t (&r)[4]) { asm volatile("ldmatrix.sync.aligned.m8n8.x4.shared.b16 {%0,%1,%2,%3}, [%4];" : "=r"(r[0]), "=r"(r[1]), "=r"(r[2]), "=r"(r[3]) : "r"(a) : "memory"); }
DEV void ldsm4t(uint32_t a, uint32_t (&r)[4]) { asm volatile("ldmatrix.sync.aligned.m8n8.x4.trans.shared.b16 {%0,%1,%2,%3}, [%4];" : "=r"(r[0]), "=r"(r[1]), "=r"(r[2]), "=r"(r[3]) : "r"(a) : "memory"); }
DEV uint32_t pack2(float lo, float hi) { uint32_t r; asm("cvt.rn.bf16x2.f32 %0, %1, %2;" : "=r"(r) : "f"(hi), "f"(lo)); return r; }
DEV uint32_t pack2v(float lo, float hi) { uint32_t r; asm volatile("cvt.rn.bf16x2.f32 %0, %1, %2;" : "=r"(r) : "f"(hi), "f"(lo)); return r; }
DEV float faddv(float a, float b) { float r; asm volatile("add.rn.f32 %0, %1, %2;" : "=f"(r) : "f"(a), "f"(b)); return r; }
DEV float blo(uint32_t u) { return __uint_as_float(u << 16); }
DEV float bhi(uint32_t u) { return __uint_as_float(u & 0xffff0000u); }
DEV float rcp_fast(float x) { float y; asm("rcp.approx.ftz.f32 %0, %1;" : "=f"(y) : "f"(x)); return y; }
DEV float tanh_fast(float x) { float y; asm("tanh.approx.f32 %0, %1;" : "=f"(y) : "f"(x)); return y; }
DEV uint32_t htanh2(uint32_t a) { uint32_t r; asm("tanh.approx.bf16x2 %0, %1;" : "=r"(r) : "r"(a)); return r; }
DEV uint32_t hadd2(uint32_t a, uint32_t b) { uint32_t r; asm("add.rn.bf16x2 %0, %1, %2;" : "=r"(r) : "r"(a), "r"(b)); return r; }
DEV uint32_t hadd2v(uint32_t a, uint32_t b) { uint32_t r; asm volatile("add.rn.bf16x2 %0, %1, %2;" : "=r"(r) : "r"(a), "r"(b)); return r; }
DEV uint32_t hmul2(uint32_t a, uint32_t b) { uint32_t r; asm("mul.rn.bf16x2 %0, %1, %2;" : "=r"(r) : "r"(a), "r"(b)); return r; }
DEV uint32_t hfma2(uint32_t a, uint32_t b, uint32_t c) { uint32_t r; asm("fma.rn.bf16x2 %0, %1, %2, %3;" : "=r"(r) : "r"(a), "r"(b), "r"(c)); return r; }
DEV uint32_t hfma2v(uint32_t a, uint32_t b, uint32_t c) { uint32_t r; asm volatile("fma.rn.bf16x2 %0, %1, %2, %3;" : "=r"(r) : "r"(a), "r"(b), "r"(c)); return r; }
DEV uint32_t hfms2(uint32_t a, uint32_t b, uint32_t c) { uint32_t r; asm("{\n.reg .b32 t;\nmul.bf16x2 t, %1, %2;\nsub.bf16x2 %0, %3, t;\n}" : "=r"(r) : "r"(a), "r"(b), "r"(c)); return r; }
DEV uint4 ldg128(const void* p) { uint4 v; asm volatile("ld.global.nc.v4.b32 {%0,%1,%2,%3}, [%4];" : "=r"(v.x), "=r"(v.y), "=r"(v.z), "=r"(v.w) : "l"(p)); return v; }
DEV uint32_t ldg32(const void* p) { uint32_t v; asm volatile("ld.global.nc.b32 %0, [%1];" : "=r"(v) : "l"(p)); return v; }
DEV float ldg_bf16(const bf16* p) { unsigned short v; asm volatile("ld.global.nc.u16 %0, [%1];" : "=h"(v) : "l"(p)); return __uint_as_float((uint32_t)v << 16); }
DEV float bf_round(float v) { return __bfloat162float(__float2bfloat16(v)); }
DEV uint32_t gelu2(float a, float b, float c1, float c2) {
  const uint32_t p = pack2(a, b);
  return hfma2(p, htanh2(hmul2(p, hfma2(hmul2(p, p), __float_as_uint(c2), __float_as_uint(c1)))), p);
}

DEV void wgmma_ssp_80_10(float* d, uint64_t da, uint64_t db, int keep) {
  asm volatile("{\n.reg .pred p;\nsetp.ne.b32 p, %42, 0;\nwgmma.mma_async.sync.aligned.m64n80k16.f32.bf16.bf16 {%0, %1, %2, %3, %4, %5, %6, %7, %8, %9, %10, %11, %12, %13, %14, %15, %16, %17, %18, %19, %20, %21, %22, %23, %24, %25, %26, %27, %28, %29, %30, %31, %32, %33, %34, %35, %36, %37, %38, %39}, %40, %41, p, 1, 1, 1, 0;\n}\n"
    : "+f"(d[0]), "+f"(d[1]), "+f"(d[2]), "+f"(d[3]), "+f"(d[4]), "+f"(d[5]), "+f"(d[6]), "+f"(d[7]), "+f"(d[8]), "+f"(d[9]), "+f"(d[10]), "+f"(d[11]), "+f"(d[12]), "+f"(d[13]), "+f"(d[14]), "+f"(d[15]), "+f"(d[16]), "+f"(d[17]), "+f"(d[18]), "+f"(d[19]), "+f"(d[20]), "+f"(d[21]), "+f"(d[22]), "+f"(d[23]), "+f"(d[24]), "+f"(d[25]), "+f"(d[26]), "+f"(d[27]), "+f"(d[28]), "+f"(d[29]), "+f"(d[30]), "+f"(d[31]), "+f"(d[32]), "+f"(d[33]), "+f"(d[34]), "+f"(d[35]), "+f"(d[36]), "+f"(d[37]), "+f"(d[38]), "+f"(d[39])
    : "l"(da), "l"(db), "r"(keep));
}
DEV void wgmma_ss_128_01(float* d, uint64_t da, uint64_t db) {
  asm volatile("{\n.reg .pred p;\nsetp.ne.b32 p, 1, 0;\nwgmma.mma_async.sync.aligned.m64n128k16.f32.bf16.bf16 {%0, %1, %2, %3, %4, %5, %6, %7, %8, %9, %10, %11, %12, %13, %14, %15, %16, %17, %18, %19, %20, %21, %22, %23, %24, %25, %26, %27, %28, %29, %30, %31, %32, %33, %34, %35, %36, %37, %38, %39, %40, %41, %42, %43, %44, %45, %46, %47, %48, %49, %50, %51, %52, %53, %54, %55, %56, %57, %58, %59, %60, %61, %62, %63}, %64, %65, p, 1, 1, 0, 1;\n}\n"
    : "+f"(d[0]), "+f"(d[1]), "+f"(d[2]), "+f"(d[3]), "+f"(d[4]), "+f"(d[5]), "+f"(d[6]), "+f"(d[7]), "+f"(d[8]), "+f"(d[9]), "+f"(d[10]), "+f"(d[11]), "+f"(d[12]), "+f"(d[13]), "+f"(d[14]), "+f"(d[15]), "+f"(d[16]), "+f"(d[17]), "+f"(d[18]), "+f"(d[19]), "+f"(d[20]), "+f"(d[21]), "+f"(d[22]), "+f"(d[23]), "+f"(d[24]), "+f"(d[25]), "+f"(d[26]), "+f"(d[27]), "+f"(d[28]), "+f"(d[29]), "+f"(d[30]), "+f"(d[31]), "+f"(d[32]), "+f"(d[33]), "+f"(d[34]), "+f"(d[35]), "+f"(d[36]), "+f"(d[37]), "+f"(d[38]), "+f"(d[39]), "+f"(d[40]), "+f"(d[41]), "+f"(d[42]), "+f"(d[43]), "+f"(d[44]), "+f"(d[45]), "+f"(d[46]), "+f"(d[47]), "+f"(d[48]), "+f"(d[49]), "+f"(d[50]), "+f"(d[51]), "+f"(d[52]), "+f"(d[53]), "+f"(d[54]), "+f"(d[55]), "+f"(d[56]), "+f"(d[57]), "+f"(d[58]), "+f"(d[59]), "+f"(d[60]), "+f"(d[61]), "+f"(d[62]), "+f"(d[63])
    : "l"(da), "l"(db));
}
DEV void wgmma_ss_96_01(float* d, uint64_t da, uint64_t db) {
  asm volatile("{\n.reg .pred p;\nsetp.ne.b32 p, 1, 0;\nwgmma.mma_async.sync.aligned.m64n96k16.f32.bf16.bf16 {%0, %1, %2, %3, %4, %5, %6, %7, %8, %9, %10, %11, %12, %13, %14, %15, %16, %17, %18, %19, %20, %21, %22, %23, %24, %25, %26, %27, %28, %29, %30, %31, %32, %33, %34, %35, %36, %37, %38, %39, %40, %41, %42, %43, %44, %45, %46, %47}, %48, %49, p, 1, 1, 0, 1;\n}\n"
    : "+f"(d[0]), "+f"(d[1]), "+f"(d[2]), "+f"(d[3]), "+f"(d[4]), "+f"(d[5]), "+f"(d[6]), "+f"(d[7]), "+f"(d[8]), "+f"(d[9]), "+f"(d[10]), "+f"(d[11]), "+f"(d[12]), "+f"(d[13]), "+f"(d[14]), "+f"(d[15]), "+f"(d[16]), "+f"(d[17]), "+f"(d[18]), "+f"(d[19]), "+f"(d[20]), "+f"(d[21]), "+f"(d[22]), "+f"(d[23]), "+f"(d[24]), "+f"(d[25]), "+f"(d[26]), "+f"(d[27]), "+f"(d[28]), "+f"(d[29]), "+f"(d[30]), "+f"(d[31]), "+f"(d[32]), "+f"(d[33]), "+f"(d[34]), "+f"(d[35]), "+f"(d[36]), "+f"(d[37]), "+f"(d[38]), "+f"(d[39]), "+f"(d[40]), "+f"(d[41]), "+f"(d[42]), "+f"(d[43]), "+f"(d[44]), "+f"(d[45]), "+f"(d[46]), "+f"(d[47])
    : "l"(da), "l"(db));
}
DEV void wgmma_ss_80_10(float* d, uint64_t da, uint64_t db) {
  asm volatile("{\n.reg .pred p;\nsetp.ne.b32 p, 1, 0;\nwgmma.mma_async.sync.aligned.m64n80k16.f32.bf16.bf16 {%0, %1, %2, %3, %4, %5, %6, %7, %8, %9, %10, %11, %12, %13, %14, %15, %16, %17, %18, %19, %20, %21, %22, %23, %24, %25, %26, %27, %28, %29, %30, %31, %32, %33, %34, %35, %36, %37, %38, %39}, %40, %41, p, 1, 1, 1, 0;\n}\n"
    : "+f"(d[0]), "+f"(d[1]), "+f"(d[2]), "+f"(d[3]), "+f"(d[4]), "+f"(d[5]), "+f"(d[6]), "+f"(d[7]), "+f"(d[8]), "+f"(d[9]), "+f"(d[10]), "+f"(d[11]), "+f"(d[12]), "+f"(d[13]), "+f"(d[14]), "+f"(d[15]), "+f"(d[16]), "+f"(d[17]), "+f"(d[18]), "+f"(d[19]), "+f"(d[20]), "+f"(d[21]), "+f"(d[22]), "+f"(d[23]), "+f"(d[24]), "+f"(d[25]), "+f"(d[26]), "+f"(d[27]), "+f"(d[28]), "+f"(d[29]), "+f"(d[30]), "+f"(d[31]), "+f"(d[32]), "+f"(d[33]), "+f"(d[34]), "+f"(d[35]), "+f"(d[36]), "+f"(d[37]), "+f"(d[38]), "+f"(d[39])
    : "l"(da), "l"(db));
}
DEV void wgmma_ss_8_10(float* d, uint64_t da, uint64_t db) {
  asm volatile("{\n.reg .pred p;\nsetp.ne.b32 p, 1, 0;\nwgmma.mma_async.sync.aligned.m64n8k16.f32.bf16.bf16 {%0, %1, %2, %3}, %4, %5, p, 1, 1, 1, 0;\n}\n"
    : "+f"(d[0]), "+f"(d[1]), "+f"(d[2]), "+f"(d[3])
    : "l"(da), "l"(db));
}
DEV void wgmma_ss_32_10(float* d, uint64_t da, uint64_t db) {
  asm volatile("{\n.reg .pred p;\nsetp.ne.b32 p, 1, 0;\nwgmma.mma_async.sync.aligned.m64n32k16.f32.bf16.bf16 {%0, %1, %2, %3, %4, %5, %6, %7, %8, %9, %10, %11, %12, %13, %14, %15}, %16, %17, p, 1, 1, 1, 0;\n}\n"
    : "+f"(d[0]), "+f"(d[1]), "+f"(d[2]), "+f"(d[3]), "+f"(d[4]), "+f"(d[5]), "+f"(d[6]), "+f"(d[7]), "+f"(d[8]), "+f"(d[9]), "+f"(d[10]), "+f"(d[11]), "+f"(d[12]), "+f"(d[13]), "+f"(d[14]), "+f"(d[15])
    : "l"(da), "l"(db));
}
DEV void wgmma_ssz_32_10(float* d, uint64_t da, uint64_t db) {
  asm volatile("{\n.reg .pred p;\nsetp.ne.b32 p, 0, 0;\nwgmma.mma_async.sync.aligned.m64n32k16.f32.bf16.bf16 {%0, %1, %2, %3, %4, %5, %6, %7, %8, %9, %10, %11, %12, %13, %14, %15}, %16, %17, p, 1, 1, 1, 0;\n}\n"
    : "=f"(d[0]), "=f"(d[1]), "=f"(d[2]), "=f"(d[3]), "=f"(d[4]), "=f"(d[5]), "=f"(d[6]), "=f"(d[7]), "=f"(d[8]), "=f"(d[9]), "=f"(d[10]), "=f"(d[11]), "=f"(d[12]), "=f"(d[13]), "=f"(d[14]), "=f"(d[15])
    : "l"(da), "l"(db));
}
DEV void wgmma_rs_64_0(float* d, const uint32_t* a, uint64_t db) {
  asm volatile("{\n.reg .pred p;\nsetp.ne.b32 p, 1, 0;\nwgmma.mma_async.sync.aligned.m64n64k16.f32.bf16.bf16 {%0, %1, %2, %3, %4, %5, %6, %7, %8, %9, %10, %11, %12, %13, %14, %15, %16, %17, %18, %19, %20, %21, %22, %23, %24, %25, %26, %27, %28, %29, %30, %31}, {%32, %33, %34, %35}, %36, p, 1, 1, 0;\n}\n"
    : "+f"(d[0]), "+f"(d[1]), "+f"(d[2]), "+f"(d[3]), "+f"(d[4]), "+f"(d[5]), "+f"(d[6]), "+f"(d[7]), "+f"(d[8]), "+f"(d[9]), "+f"(d[10]), "+f"(d[11]), "+f"(d[12]), "+f"(d[13]), "+f"(d[14]), "+f"(d[15]), "+f"(d[16]), "+f"(d[17]), "+f"(d[18]), "+f"(d[19]), "+f"(d[20]), "+f"(d[21]), "+f"(d[22]), "+f"(d[23]), "+f"(d[24]), "+f"(d[25]), "+f"(d[26]), "+f"(d[27]), "+f"(d[28]), "+f"(d[29]), "+f"(d[30]), "+f"(d[31])
    : "r"(a[0]), "r"(a[1]), "r"(a[2]), "r"(a[3]), "l"(db));
}
DEV void wgmma_rsz_64_0(float* d, const uint32_t* a, uint64_t db) {
  asm volatile("{\n.reg .pred p;\nsetp.ne.b32 p, 0, 0;\nwgmma.mma_async.sync.aligned.m64n64k16.f32.bf16.bf16 {%0, %1, %2, %3, %4, %5, %6, %7, %8, %9, %10, %11, %12, %13, %14, %15, %16, %17, %18, %19, %20, %21, %22, %23, %24, %25, %26, %27, %28, %29, %30, %31}, {%32, %33, %34, %35}, %36, p, 1, 1, 0;\n}\n"
    : "=f"(d[0]), "=f"(d[1]), "=f"(d[2]), "=f"(d[3]), "=f"(d[4]), "=f"(d[5]), "=f"(d[6]), "=f"(d[7]), "=f"(d[8]), "=f"(d[9]), "=f"(d[10]), "=f"(d[11]), "=f"(d[12]), "=f"(d[13]), "=f"(d[14]), "=f"(d[15]), "=f"(d[16]), "=f"(d[17]), "=f"(d[18]), "=f"(d[19]), "=f"(d[20]), "=f"(d[21]), "=f"(d[22]), "=f"(d[23]), "=f"(d[24]), "=f"(d[25]), "=f"(d[26]), "=f"(d[27]), "=f"(d[28]), "=f"(d[29]), "=f"(d[30]), "=f"(d[31])
    : "r"(a[0]), "r"(a[1]), "r"(a[2]), "r"(a[3]), "l"(db));
}
DEV void wgmma_rs_64_1(float* d, const uint32_t* a, uint64_t db) {
  asm volatile("{\n.reg .pred p;\nsetp.ne.b32 p, 1, 0;\nwgmma.mma_async.sync.aligned.m64n64k16.f32.bf16.bf16 {%0, %1, %2, %3, %4, %5, %6, %7, %8, %9, %10, %11, %12, %13, %14, %15, %16, %17, %18, %19, %20, %21, %22, %23, %24, %25, %26, %27, %28, %29, %30, %31}, {%32, %33, %34, %35}, %36, p, 1, 1, 1;\n}\n"
    : "+f"(d[0]), "+f"(d[1]), "+f"(d[2]), "+f"(d[3]), "+f"(d[4]), "+f"(d[5]), "+f"(d[6]), "+f"(d[7]), "+f"(d[8]), "+f"(d[9]), "+f"(d[10]), "+f"(d[11]), "+f"(d[12]), "+f"(d[13]), "+f"(d[14]), "+f"(d[15]), "+f"(d[16]), "+f"(d[17]), "+f"(d[18]), "+f"(d[19]), "+f"(d[20]), "+f"(d[21]), "+f"(d[22]), "+f"(d[23]), "+f"(d[24]), "+f"(d[25]), "+f"(d[26]), "+f"(d[27]), "+f"(d[28]), "+f"(d[29]), "+f"(d[30]), "+f"(d[31])
    : "r"(a[0]), "r"(a[1]), "r"(a[2]), "r"(a[3]), "l"(db));
}
DEV void wgmma_rsz_64_1(float* d, const uint32_t* a, uint64_t db) {
  asm volatile("{\n.reg .pred p;\nsetp.ne.b32 p, 0, 0;\nwgmma.mma_async.sync.aligned.m64n64k16.f32.bf16.bf16 {%0, %1, %2, %3, %4, %5, %6, %7, %8, %9, %10, %11, %12, %13, %14, %15, %16, %17, %18, %19, %20, %21, %22, %23, %24, %25, %26, %27, %28, %29, %30, %31}, {%32, %33, %34, %35}, %36, p, 1, 1, 1;\n}\n"
    : "=f"(d[0]), "=f"(d[1]), "=f"(d[2]), "=f"(d[3]), "=f"(d[4]), "=f"(d[5]), "=f"(d[6]), "=f"(d[7]), "=f"(d[8]), "=f"(d[9]), "=f"(d[10]), "=f"(d[11]), "=f"(d[12]), "=f"(d[13]), "=f"(d[14]), "=f"(d[15]), "=f"(d[16]), "=f"(d[17]), "=f"(d[18]), "=f"(d[19]), "=f"(d[20]), "=f"(d[21]), "=f"(d[22]), "=f"(d[23]), "=f"(d[24]), "=f"(d[25]), "=f"(d[26]), "=f"(d[27]), "=f"(d[28]), "=f"(d[29]), "=f"(d[30]), "=f"(d[31])
    : "r"(a[0]), "r"(a[1]), "r"(a[2]), "r"(a[3]), "l"(db));
}
DEV void wgmma_rs_128_1(float* d, const uint32_t* a, uint64_t db) {
  asm volatile("{\n.reg .pred p;\nsetp.ne.b32 p, 1, 0;\nwgmma.mma_async.sync.aligned.m64n128k16.f32.bf16.bf16 {%0, %1, %2, %3, %4, %5, %6, %7, %8, %9, %10, %11, %12, %13, %14, %15, %16, %17, %18, %19, %20, %21, %22, %23, %24, %25, %26, %27, %28, %29, %30, %31, %32, %33, %34, %35, %36, %37, %38, %39, %40, %41, %42, %43, %44, %45, %46, %47, %48, %49, %50, %51, %52, %53, %54, %55, %56, %57, %58, %59, %60, %61, %62, %63}, {%64, %65, %66, %67}, %68, p, 1, 1, 1;\n}\n"
    : "+f"(d[0]), "+f"(d[1]), "+f"(d[2]), "+f"(d[3]), "+f"(d[4]), "+f"(d[5]), "+f"(d[6]), "+f"(d[7]), "+f"(d[8]), "+f"(d[9]), "+f"(d[10]), "+f"(d[11]), "+f"(d[12]), "+f"(d[13]), "+f"(d[14]), "+f"(d[15]), "+f"(d[16]), "+f"(d[17]), "+f"(d[18]), "+f"(d[19]), "+f"(d[20]), "+f"(d[21]), "+f"(d[22]), "+f"(d[23]), "+f"(d[24]), "+f"(d[25]), "+f"(d[26]), "+f"(d[27]), "+f"(d[28]), "+f"(d[29]), "+f"(d[30]), "+f"(d[31]), "+f"(d[32]), "+f"(d[33]), "+f"(d[34]), "+f"(d[35]), "+f"(d[36]), "+f"(d[37]), "+f"(d[38]), "+f"(d[39]), "+f"(d[40]), "+f"(d[41]), "+f"(d[42]), "+f"(d[43]), "+f"(d[44]), "+f"(d[45]), "+f"(d[46]), "+f"(d[47]), "+f"(d[48]), "+f"(d[49]), "+f"(d[50]), "+f"(d[51]), "+f"(d[52]), "+f"(d[53]), "+f"(d[54]), "+f"(d[55]), "+f"(d[56]), "+f"(d[57]), "+f"(d[58]), "+f"(d[59]), "+f"(d[60]), "+f"(d[61]), "+f"(d[62]), "+f"(d[63])
    : "r"(a[0]), "r"(a[1]), "r"(a[2]), "r"(a[3]), "l"(db));
}
DEV void wgmma_rs_96_1(float* d, const uint32_t* a, uint64_t db) {
  asm volatile("{\n.reg .pred p;\nsetp.ne.b32 p, 1, 0;\nwgmma.mma_async.sync.aligned.m64n96k16.f32.bf16.bf16 {%0, %1, %2, %3, %4, %5, %6, %7, %8, %9, %10, %11, %12, %13, %14, %15, %16, %17, %18, %19, %20, %21, %22, %23, %24, %25, %26, %27, %28, %29, %30, %31, %32, %33, %34, %35, %36, %37, %38, %39, %40, %41, %42, %43, %44, %45, %46, %47}, {%48, %49, %50, %51}, %52, p, 1, 1, 1;\n}\n"
    : "+f"(d[0]), "+f"(d[1]), "+f"(d[2]), "+f"(d[3]), "+f"(d[4]), "+f"(d[5]), "+f"(d[6]), "+f"(d[7]), "+f"(d[8]), "+f"(d[9]), "+f"(d[10]), "+f"(d[11]), "+f"(d[12]), "+f"(d[13]), "+f"(d[14]), "+f"(d[15]), "+f"(d[16]), "+f"(d[17]), "+f"(d[18]), "+f"(d[19]), "+f"(d[20]), "+f"(d[21]), "+f"(d[22]), "+f"(d[23]), "+f"(d[24]), "+f"(d[25]), "+f"(d[26]), "+f"(d[27]), "+f"(d[28]), "+f"(d[29]), "+f"(d[30]), "+f"(d[31]), "+f"(d[32]), "+f"(d[33]), "+f"(d[34]), "+f"(d[35]), "+f"(d[36]), "+f"(d[37]), "+f"(d[38]), "+f"(d[39]), "+f"(d[40]), "+f"(d[41]), "+f"(d[42]), "+f"(d[43]), "+f"(d[44]), "+f"(d[45]), "+f"(d[46]), "+f"(d[47])
    : "r"(a[0]), "r"(a[1]), "r"(a[2]), "r"(a[3]), "l"(db));
}

struct Dft { uint32_t E[8], tt[8], ts[8]; };
DEV void dft_load(Dft& k, const uint32_t* tab, int tid) {
#pragma unroll
  for (int q = 0; q < 6; q++) {
    const uint4 v = ldg128(tab + 3072 + 512 * q + 4 * tid);
    uint32_t* d = (q < 2 ? k.E : q < 4 ? k.tt : k.ts) + 4 * (q & 1);
    d[0] = v.x; d[1] = v.y; d[2] = v.z; d[3] = v.w;
  }
}
template <int SG> DEV void rotate(const float* d, const Dft& k, uint32_t* o) {
#pragma unroll
  for (int j = 0; j < 8; j++) {
    const uint32_t re = pack2(d[4 * j], d[4 * j + 1]), im = pack2(d[4 * j + 2], d[4 * j + 3]);
    uint32_t a, b;
    if (SG > 0) { a = hfms2(k.tt[j], im, re); b = hfma2(k.ts[j], a, im); a = hfms2(k.tt[j], b, a); }
    else { a = hfma2(k.tt[j], im, re); b = hfms2(k.ts[j], a, im); a = hfma2(k.tt[j], b, a); }
    o[2 * j] = a; o[2 * j + 1] = b;
  }
}
DEV void dft64(float* d, const uint32_t* a, uint64_t db) {
  wgmma_rsz_64_1(d, a, db);
#pragma unroll
  for (int kk = 1; kk < 4; kk++) wgmma_rs_64_1(d, a + 4 * kk, db + kk * (2048 >> 4));
}
DEV bool conv(const Dft& k, uint32_t sb, uint32_t t, uint32_t ty, float dv, int bar, int w, int lane, unsigned* go, uint32_t ep, uint32_t zero) {
  const uint32_t tag = KVCHK ? lds32(t + 1024 * w + 32 * lane + 4 * (lane & 4)) : ep;
  dv = __uint_as_float(__float_as_uint(dv) | (tag & zero));
  float dh[32], dx[32];
  uint32_t ah[16], ax[16];
  const uint64_t cs = make_desc(sb + OFF_DFT, 16, 1024, 1), bh = make_desc(t + 4096, 16, 1024, 1), bx = make_desc(t, 1024, 256, 3);
  wg_fence();
  wgmma_rsz_64_1(dh, k.E, bh); wgmma_rs_64_1(dh, k.E + 4, bh + (2048 >> 4)); wg_commit();
  wgmma_rsz_64_1(dx, k.E, bx); wgmma_rs_64_1(dx, k.E + 4, bx + (512 >> 4)); wg_commit();
  wg_wait<1>();
  dh[0] = fmaf(dv, blo(k.E[0]), dh[0]); dh[2] = fmaf(dv, blo(k.E[1]), dh[2]);
  rotate<1>(dh, k, ah);
  wg_fence(); dft64(dh, ah, cs); wg_commit();
  if (GO_AT == 1 && go) flag_add_rlx(go, 1);
  wg_wait<1>();
  rotate<1>(dx, k, ax);
  wg_fence(); dft64(dx, ax, cs); wg_commit();
  wg_wait<1>();
#pragma unroll
  for (int j = 0; j < 8; j++) { ah[2 * j] = pack2(dh[4 * j], dh[4 * j + 1]); ah[2 * j + 1] = pack2(dh[4 * j + 2], dh[4 * j + 3]); }
  wg_wait<0>();
#pragma unroll
  for (int j = 0; j < 4; j++) {
    const uint32_t pr = pack2(dx[4 * j], dx[4 * j + 1]), pi = pack2(dx[4 * j + 2], dx[4 * j + 3]);
    const uint32_t qr = pack2(dx[16 + 4 * j], dx[17 + 4 * j]), qi = pack2(dx[18 + 4 * j], dx[19 + 4 * j]);
    const uint32_t rr = ah[2 * j], ri = ah[2 * j + 1], sr = ah[8 + 2 * j], si = ah[9 + 2 * j];
    ax[2 * j] = hfma2(qi, si, hfms2(qr, sr, hfms2(pi, ri, hmul2(pr, rr))));
    ax[2 * j + 1] = hfms2(qi, sr, hfms2(qr, si, hfma2(pi, rr, hmul2(pr, ri))));
    ax[8 + 2 * j] = hfms2(qi, ri, hfma2(qr, rr, hfms2(pi, si, hmul2(pr, sr))));
    ax[9 + 2 * j] = hfma2(qi, rr, hfma2(qr, ri, hfma2(pi, sr, hmul2(pr, si))));
  }
  wg_fence();
  wgmma_rsz_64_0(dx, ax, cs);
#pragma unroll
  for (int kk = 1; kk < 4; kk++) wgmma_rs_64_0(dx, ax + 4 * kk, cs + 2 * kk);
  wg_commit();
  if (GO_AT == 2 && go) flag_add_rlx(go, 1);
  wg_wait<0>();
  rotate<-1>(dx, k, ah);
  const int m = lane >> 3, i = lane & 7;
  const uint32_t za = t + (16 * w + 8 * (m & 1) + i) * 128;
#pragma unroll
  for (int q = 0; q < 4; q++) stsm4(za + (((2 * q + (m >> 1)) ^ i) << 4), ah[4 * q], ah[4 * q + 1], ah[4 * q + 2], ah[4 * q + 3]);
  fence_async_smem();
  uint32_t ok;
  asm volatile("{\n.reg .pred p, q;\nsetp.eq.u32 p, %1, 0;\nbarrier.red.and.aligned.pred q, %2, 128, p;\nselp.u32 %0, 1, 0, q;\n}" : "=r"(ok) : "r"((tag ^ ep) & 1), "r"(bar) : "memory");
  const uint64_t da = make_desc(t, 16, 1024, 1), db = make_desc(sb + OFF_G, 16, 1024, 1);
  if (K4E) mbar_wait(sb + OFF_BAR + 8 * B_KVC, 0);
  wg_fence();
  wgmma_ssz_32_10(dh, da, db);
#pragma unroll
  for (int kk = 1; kk < 4; kk++) wgmma_ss_32_10(dh, da + kk * (2048 >> 4), db + 2 * kk);
  wg_commit();
  if (GO_AT == 3 && go) flag_add_rlx(go, 1);
  wg_wait<0>();
  if (!K4E) mbar_wait(sb + OFF_BAR + 8 * B_KVC, 0);
  const uint32_t ya = ty + (8 * (m >> 1) + i) * 128 + (((2 * w + (m & 1)) ^ i) << 4);
#pragma unroll
  for (int q = 0; q < 2; q++)
    stsm4t(ya + q * 2048, pack2(dh[8 * q], dh[8 * q + 1]), pack2(dh[8 * q + 2], dh[8 * q + 3]), pack2(dh[8 * q + 4], dh[8 * q + 5]), pack2(dh[8 * q + 6], dh[8 * q + 7]));
  wfence(4);
  return !KVCHK || __all_sync(0xffffffffu, ok);
}

DEV void g1_issue(const Params& P, uint32_t sb, int s, uint32_t fb, int kb, int rb, int fs) {
  const uint32_t st = sb + s * G1_W;
  mbar_expect(fb, G1_W + G1_X);
  tma2d(sb + OFF_X + s * G1_X, &P.x_g1, 64 * kb, 128 * rb, fb);
  tma3d(st, &P.w1_a, 0, 64 * kb, 3 * fs, fb);
  tma3d(st + 16384, &P.w1_b2, 0, 64 * kb, 6 * fs + 4, fb);
  tma3d(st + 24576, &P.w1_b1, 0, 64 * kb, 48 + fs, fb);
}
DEV void kv_issue(const Params& P, uint32_t dst, uint32_t bar, int r, int g1) {
  mbar_expect(bar, KV_SLOT);
  tma2d(dst, &P.k, 128 * r, 16 * g1 - 3, bar);
  tma2d(dst + 19 * 256, &P.v, 128 * r, 16 * g1, bar);
}
DEV void h_flag(const Params& P, int rb, int o) {
  const int j0 = (128 * rb) / 80;
  flag_add_rlx(P.flags + FL_H + 32 * (o + j0), 1); flag_add_rlx(P.flags + FL_H + 32 * (o + j0 + 1), 1);
  if (80 * (j0 + 2) < 128 * rb + 128) flag_add_rlx(P.flags + FL_H + 32 * (o + j0 + 2), 1);
}
DEV void h_wait(const Params& P, int tj, int o, unsigned ep, uint32_t buf) {
  const unsigned n = ep * (((80 * tj) >> 7) == (min(80 * tj + 79, S_ - 1) >> 7) ? 8 : 16);
  if (POLL & 4) flag_poll<false>(P.flags + FL_H + 32 * (o + tj), n, buf); else flag_wait<false>(P.flags + FL_H + 32 * (o + tj), n);
  if (FNC & 2) fence_async_global();
}
DEV uint32_t h_tag(uint32_t sb, int tj, int q, int lane) {
  const int r = min(q < 2 ? 32 * q + lane : 64 + (lane & 15), S_ - 1 - 80 * tj);
  return sb + G2_B + r * 128 + ((r & 7) << 4) + 4 * ((2 * tj + (r >> 3)) & 3);
}
DEV uint32_t conv_tile(uint32_t sb, int c) { return sb + (c == 1 ? OFF_T1 : c == 2 ? OFF_T2 : c == 3 ? OFF_T3 : c == 4 ? OFF_T4 : OFF_T0); }
DEV void conv_issue_f(const Params& P, uint32_t t, int ch, uint32_t bar) { mbar_expect(bar, 4096); tma2d(t + 4096, &P.f_ld, 0, 32 * ch, bar); }
DEV void conv_issue_x(const Params& P, uint32_t t, int ch, uint32_t bar) {
  mbar_expect(bar, 4096);
  tma3d(t, &P.kvz, 16 * ((ch & ~63) | ((ch & 3) << 4) | ((ch & 63) >> 2)), 0, 0, bar);
}
HD int h_slot(int j) { return SPLIT9 && j ? 3 - j : j; }
DEV int g2_slot(int s) { return !RM || s < 3 ? s : s == 5 ? 3 : s + 1; }
HD int out_piece(int j) { return j > 4 ? 9 : ((OUTP ? OUTP : 0x21100) >> (4 * j)) & 15; }
DEV int g2_block(int i) { return i < 24 ? 3 * (i & 7) + (i >> 3) : i; }
DEV int ext_col(int n, int fs) { return min(n < 192 ? 192 * fs + n : 1344 + 32 * fs + n, F_ - 2); }
DEV uint32_t ext_off(int n, int k) {
  const int m = n - 128;
  return n < 128 ? (n >> 6) * 1024 + k * 128 + ((((n & 63) >> 3) ^ k) << 4) + (n & 7) * 2
                 : 2048 + (m >> 5) * 512 + k * 64 + ((((m & 31) >> 3) ^ (k >> 1)) << 4) + (m & 7) * 2;
}
DEV uint32_t kv_elem(uint32_t k0, uint32_t k1, uint32_t k2, uint32_t k3, const uint32_t (&w)[4], uint32_t v) {
  if (MIM & 2) return hmul2(hadd2(hadd2(hadd2(hmul2(k0, w[3]), hmul2(k1, w[2])), hmul2(k2, w[1])), hmul2(k3, w[0])), v);
  return hmul2(hfma2(k3, w[0], hfma2(k2, w[1], hfma2(k1, w[2], hmul2(k0, w[3])))), v);
}
DEV void kv_store(uint32_t z, const uint32_t (&p)[8]) {
  sts128(z, make_uint4(__byte_perm(p[0], p[1], 0x5410), __byte_perm(p[2], p[3], 0x5410), __byte_perm(p[4], p[5], 0x5410), __byte_perm(p[6], p[7], 0x5410)));
  sts128(z + 512, make_uint4(__byte_perm(p[0], p[1], 0x7632), __byte_perm(p[2], p[3], 0x7632), __byte_perm(p[4], p[5], 0x7632), __byte_perm(p[6], p[7], 0x7632)));
}
DEV void kv_out(const Params& P, uint32_t src, int r, int g1) { bulk_s2g(reinterpret_cast<uint8_t*>(P.kvZ) + g1 * 20480 + r * 4096, src, 4096); }
DEV void tap_split(uint4 q, uint32_t (&w)[4]) {
  w[0] = __byte_perm(q.x, q.z, 0x5410); w[1] = __byte_perm(q.x, q.z, 0x7632); w[2] = __byte_perm(q.y, q.w, 0x5410); w[3] = __byte_perm(q.y, q.w, 0x7632);
}

}

__global__ void __launch_bounds__(512, 1) h3_fused_kernel(const __grid_constant__ Params P) {
  extern __shared__ __align__(1024) uint8_t smem_raw[];
  constexpr uint32_t sb = 1024;
#define BAR(i) (sb + OFF_BAR + 8 * (i))
  const int warp = __shfl_sync(0xffffffffu, threadIdx.x >> 5, 0);
  const int wg = warp >> 2;
  const int tid = threadIdx.x & 127, lane = threadIdx.x & 31;
  uint32_t smid, nsmid;
  asm volatile("mov.u32 %0, %%smid;" : "=r"(smid));
  asm volatile("mov.u32 %0, %%nsmid;" : "=r"(nsmid));
  const uint32_t cta = nsmid == NCTA ? smid : blockIdx.x;
  const uchar4 mp = P.map[cta];
  const int g1 = mp.x, g2 = mp.y;
  const bool has1 = g1 < 128, has2 = g2 != 255;
  const int fs = g1 & 7, rb = g1 >> 3;
  const int tj = g2 >> 3, dt = g2 & 7;

  if (warp != 12) {
    if (elect()) {
      if (smem_u32(smem_raw) != sb) __trap();
#pragma unroll 1
      for (int b = B_FIRST + warp - (warp > 12); b < B_COUNT; b += 15) mbar_init(BAR(b), P.cnt[b]);
      fence_async_smem();
    }
    __syncwarp();
    asm volatile("bar.arrive 7, 512;" ::: "memory");
    asm volatile("bar.sync 0, 512;" ::: "memory");
  }

  if (wg < 3) {
    const int w4 = warp & 3, g = lane >> 2, c = lane & 3;
    asm volatile("setmaxnreg.inc.sync.aligned.u32 %0;" ::"n"(R_G));
    Dft dft;
    uint32_t ep, dq[3];
    auto misc_load = [&]() {
      const int l = wg == 0 ? CH_W0 : wg == 1 ? CH_W1 : CH_W2;
      ep = lds32(sb + OFF_MISC);
#pragma unroll
      for (int j = 0; j < 3; j++) dq[j] = lds32(sb + OFF_MISC + 4 + 4 * ((l >> (4 * j)) & 7));
    };
    if (wg < 2) {
      if (has1) {
        float acc[112];
        const uint64_t da0 = make_desc(sb + OFF_X + wg * 8192, 16, 1024, 1), db0 = make_desc(sb, 8192, 1024, 1), dc0 = make_desc(sb + 16384, 4096, 512, 2);
        const bool lead = tid == 0;
#pragma unroll
        for (int i = 0; i < 112; i++) acc[i] = 0.f;
        auto block = [&](int kb) {
          const int s = kb & 3;
          const uint64_t o = s * (G1_W >> 4), da = da0 + s * (G1_X >> 4), db = db0 + o, dc = dc0 + o;
          mbar_wait(BAR(B_FULL1 + s), (kb >> 2) & 1);
          TZ(tid, 64 + 10 * wg + kb);
          wg_fence();
#pragma unroll
          for (int kk = 0; kk < 4; kk++) {
            wgmma_ss_128_01(acc, da + 2 * kk, db + kk * (2048 >> 4));
            wgmma_ss_96_01(acc + 64, da + 2 * kk, dc + kk * (1024 >> 4));
            if (kk == EREL - 1) {
              wg_commit(); wg_wait<1>();
              if (lead && kb && kb < 7) mbar_arrive(BAR(B_EMPTY1 + ((kb - 1) & 3)));
            }
          }
          wg_commit();
        };
#pragma unroll 1
        for (int kb = 0; kb < 10 - SPLIT9; kb++) {
          block(kb);
          if (!EREL && kb < NOW) {
            wg_wait<1>();
            if (lead && kb && kb < 7) mbar_arrive(BAR(B_EMPTY1 + ((kb - 1) & 3)));
          }
        }
        TZ(tid | (wg ^ 1), 123);
        mbar_wait(BAR(B_TAB), 0);
        TZ(tid, 8 + wg);
        const uint32_t sa = sb + OFF_ST1 + 16 * (64 * wg + 16 * w4 + g);
        const float r0 = __uint_as_float(lds32(sa + 12)), r1 = __uint_as_float(lds32(sa + 128 + 12));
        {
          uint32_t ax[4];
          ax[0] = lds32(sa + 4 * c); ax[1] = lds32(sa + 128 + 4 * c);
          if (c == 3) { ax[0] = 0; ax[1] = 0; }
          asm volatile("mov.b32 %0, 0;" : "=r"(ax[2])); asm volatile("mov.b32 %0, 0;" : "=r"(ax[3]));
          if (SPLIT9) {
            const uint64_t da = da0 + (G1_X >> 4), db = db0 + (G1_W >> 4), dc = dc0 + (G1_W >> 4);
            wg_fence();
            wgmma_rs_128_1(acc, ax, make_desc(sb + OFF_EXT, 1024, 0, 1));
            wgmma_rs_96_1(acc + 64, ax, make_desc(sb + OFF_EXT + 2048, 512, 0, 2));
            mbar_wait(BAR(B_FULL1 + 1), 0);
            TZ(tid, 64 + 10 * wg + 9);
#pragma unroll
            for (int kk = 0; kk < 4; kk++) wgmma_ss_128_01(acc, da + 2 * kk, db + kk * (2048 >> 4));
            wg_commit();
#pragma unroll
            for (int kk = 0; kk < 4; kk++) wgmma_ss_96_01(acc + 64, da + 2 * kk, dc + kk * (1024 >> 4));
            wg_commit();
          } else {
          wg_fence();
          wgmma_rs_128_1(acc, ax, make_desc(sb + OFF_EXT, 1024, 0, 1));
          wgmma_rs_96_1(acc + 64, ax, make_desc(sb + OFF_EXT + 2048, 512, 0, 2));
          wg_commit();
          }
        }
        constexpr float K1 = 0.7978845608028654f, K2 = 0.7978845608028654f * 0.044715f;
        float c10 = K1 * r0, c11 = K1 * r1, c20 = K2 * r0 * r0 * r0, c21 = K2 * r1 * r1 * r1;
        c10 = __uint_as_float(pack2(c10, c10)); c11 = __uint_as_float(pack2(c11, c11)); c20 = __uint_as_float(pack2(c20, c20)); c21 = __uint_as_float(pack2(c21, c21));
        const int hr = 16 * w4 + ((lane >> 3) & 1) * 8 + (lane & 7);
        const uint32_t hs = sb + OFF_X + wg * 8192 + hr * 128, hx = (lane >> 4) ^ (lane & 7);
        const uint32_t hs2 = sb + OFF_X + 3 * G1_X + wg * 4096 + hr * 64, hx2 = (lane >> 4) ^ ((lane >> 1) & 3);
        if (SPLIT9) wg_wait<1>(); else wg_wait<0>();
        TZ(tid, 2 + wg);
        if (!SPLIT9 && tid < 5) mbar_arrive(BAR(tid < 4 ? B_EMPTY2 + (RM && tid == 3 ? 5 : tid) : B_G1FREE));
        uint32_t zn = 0;
        misc_load();
        const uint32_t par = ep & 1;
#pragma unroll
        for (int i = 0; i < 28; i += 2) {
          if (i == 24) { if (fs >= 6) break; if (wg) mbar_wait(BAR(B_G1FREE), 0); }
          if (i && i % GELU_BF16 == 0) {
            const uint32_t z = LOOKAHEAD ? zn : lds32(sb + OFF_MISC + 24);
            c20 = __uint_as_float(__float_as_uint(c20) + z); c21 = __uint_as_float(__float_as_uint(c21) + z);
          }
          if (LOOKAHEAD && (i + LOOKAHEAD) % GELU_BF16 == 0) zn = lds32(sb + OFF_MISC + 24);
          if (SPLIT9 && i == 16) { wg_wait<0>(); if (tid < 5) mbar_arrive(BAR(tid < 4 ? B_EMPTY2 + tid : B_G1FREE)); }
          if (i == DFT_AT) dft_load(dft, P.tab, tid);
          const float* a = &acc[4 * i];
          uint32_t p0 = gelu2(a[0], a[1], c10, c20), p1 = gelu2(a[2], a[3], c11, c21);
          if (!(i & 7)) { if (c == ((2 * w4) & 3)) p0 = (p0 & ~1u) | par; if (c == ((2 * w4 + 1) & 3)) p1 = (p1 & ~1u) | par; }
          const uint32_t p2 = gelu2(a[4], a[5], c10, c20), p3 = gelu2(a[6], a[7], c11, c21);
          if (i > HS_LAG && !((i - HS_LAG) & 7)) { wfence(2); warp_arrive(BAR(B_HS + 4 * wg + (i >> 3) - 1)); }
          if (i < 24) stsm4(hs + h_slot(i >> 3) * G1_X + ((hx ^ (i & 7)) << 4), p0, p1, p2, p3);
          else stsm4(hs2 + ((hx2 ^ (i & 3)) << 4), p0, p1, p2, p3);
          if ((i == 22 && fs >= 6) || i == 26) { wfence(2); warp_arrive(BAR(B_HS + 4 * wg + (i >> 3))); }
        }
        TZ(tid, 4 + wg);
      } else if (wg == 1) {
        float cs[7][4];
#pragma unroll
        for (int j = 0; j < 7; j++) cs[j][0] = cs[j][1] = cs[j][2] = cs[j][3] = 0.f;
        if (tid < 64) sts32(sb + OFF_EXT + 4 * tid, 0x3f803f80u);
        fence_async_smem();
        bar_sync(4);
        const uint64_t da0 = make_desc(sb, 16, 1024, 1), db = make_desc(sb + OFF_EXT, 128, 128, 0);
        int s = 0, ph = 0;
#pragma unroll 1
        for (int kb = SP_FAKE ? 10 : CS_KB; kb < 10; kb++) {
          mbar_wait(BAR(B_FULL1 + s), ph);
          wg_fence();
#pragma unroll 1
          for (int kk = 0; kk < 4; kk++) {
#pragma unroll
            for (int j = 0; j < 7; j++) wgmma_ss_8_10(cs[j], da0 + (s * (CS_STAGE >> 4) + kk * (2048 >> 4)) + j * (8192 >> 4), db);
            wg_commit();
          }
          wg_wait<0>();
          if (tid < 4) mbar_arrive(BAR(B_EMPTY1 + s));
          if (++s == 3) { s = 0; ph ^= 1; }
        }
        mbar_wait(BAR(B_EPOCH), 0);
        ep = lds32(sb + OFF_MISC);
#pragma unroll
        for (int j = 0; j < 7; j++) {
          const float a = (c & 1) ? cs[j][2] : cs[j][0], b = __shfl_down_sync(0xffffffffu, a, 4);
          if (c < 2 && !(g & 1)) tag_store(P.cs + CSP + 32 * (7 * (g1 - 128) + j) + 8 * w4 + 4 * c + (g >> 1), a, b, ep);
        }
        TZ(tid, 24);
        if (tid < 2 * G2_NST + 2 * RM) mbar_arrive(BAR(tid >= 2 * G2_NST ? B_G1FREE : B_EMPTY2 + (tid >> 1)));
      }
    } else {
      if (has1) {
        const bf16* skp = P.shift_k + (128 * (w4 >> 1) + 64 * (w4 & 1) + 4 * (lane & 15)) * 4;
        uint4 tap0 = ldg128(skp), tap1 = ldg128(skp + 8);
        auto stats = [&]() {
        mbar_wait(BAR(B_STAT), 0);
        TZ(tid, 19);
        float sum = 0.f, sq = 0.f;
        const uint32_t sa = sb + OFF_SR + (tid >> 3) * 1280 + 16 * (lane & 7);
        uint4 nq[2] = {lds128(sa), lds128(sa + 128)};
#pragma unroll 1
        for (int z = 0; z < 5; z++) {
          const uint4 xq[2] = {nq[0], nq[1]};
          if (z < 4) { nq[0] = lds128(sa + 256 * z + 256); nq[1] = lds128(sa + 256 * z + 384); }
          else warp_arrive(BAR(B_STATFREE) + ((xq[0].x | xq[1].x) & P.zero));
#pragma unroll
          for (int i = 0; i < 2; i++) {
            const uint32_t u[4] = {xq[i].x, xq[i].y, xq[i].z, xq[i].w};
#pragma unroll
            for (int e = 0; e < 4; e++) { const float a = blo(u[e]), b = bhi(u[e]); sum += a + b; sq = fmaf(a, a, fmaf(b, b, sq)); }
          }
        }
#pragma unroll
        for (int o = 1; o < 8; o *= 2) { sum += __shfl_xor_sync(0xffffffffu, sum, o); sq += __shfl_xor_sync(0xffffffffu, sq, o); }
        const float mean = sum * (1.f / D_), var = fmaxf(fmaf(-mean, mean, sq * (1.f / D_)), 0.f);
        const float ve = bf_round(bf_round(var) + 1e-5f);
        if ((lane & 7) == 0) tag_store(P.stats + 16 * g1 + (tid >> 3), MIM & 1 ? bf_round(mean) : mean, MIM & 1 ? rcp_fast(bf_round(ve * rsqrtf(ve))) : rsqrtf(var + 1e-5f), ep);
        TZ(tid, 22);
        };
        const uint32_t slot = sb + OFF_KV + (w4 >> 1) * KV_SLOT;
        const uint32_t ka = slot + 8 * (lane >> 4) * 256 + 128 * (w4 & 1) + 8 * (lane & 15);
        const uint32_t zo = (64 * (w4 & 1) + (lane & 15)) * 32 + (lane >> 4) * 16;
        if (DFT_EARLY == 2) dft_load(dft, P.tab, tid);
        mbar_wait(BAR(B_EPOCH), 0);
        misc_load();
        const uint32_t hf4 = (lane >> 4) ^ (w4 >> 1);
        const uint32_t tagm = lane < 16 ? 0x00010001u : 0u, tagv = (ep & 1) ? tagm : 0u;
        auto round4 = [&](uint4 tap) {
          uint32_t wa[4], p[8], kk[11];
          tap_split(tap, wa);
          const uint32_t k4 = sb + OFF_KV4 + 8 * (lane >> 4) * 256 + 128 * (w4 & 1) + 8 * (lane & 15) + 4 * hf4;
          mbar_wait(BAR(B_KV4), 0);
          TZ(tid, 62);
#pragma unroll
          for (int j = 0; j < 11; j++) kk[j] = lds32(k4 + j * 256);
#pragma unroll
          for (int j = 0; j < 8; j++) p[j] = lds32(k4 + (19 + j) * 256);
          if (DFT_EARLY == 4) dft_load(dft, P.tab, tid);
#pragma unroll
          for (int j = 0; j < 8; j++) p[j] = kv_elem(kk[j], kk[j + 1], kk[j + 2], kk[j + 3], wa, p[j]);
          bar_sync(3 + ((p[0] | p[1] | p[2] | p[3] | p[4] | p[5] | p[6] | p[7]) & P.zero));
          p[0] = (p[0] & ~tagm) | tagv;
          kv_store(sb + OFF_KV4 + KV_V + zo + 1024 * hf4, p);
          wfence(1);
          warp_arrive(BAR(B_KVS + 2));
        };
        uint4 tap4;
        if (K4E == 3) { tap4 = ldg128(P.shift_k + (512 + 64 * (w4 & 1) + 4 * (lane & 15) + 2 * hf4) * 4); stats(); }
#pragma unroll 1
        for (int r = w4 >> 1; r < (K4E ? 4 : 5); r += 2) {
          uint32_t wa[4], wb[4], p[8], q[8];
          uint2 kk[11];
          tap_split(tap0, wa); tap_split(tap1, wb);
          if (K4E) {
            if (r < 2) { skp += 1024; tap0 = ldg128(skp); tap1 = ldg128(skp + 8); }
            else { if (K4E != 3) tap0 = ldg128(P.shift_k + (512 + 64 * (w4 & 1) + 4 * (lane & 15) + 2 * hf4) * 4); if (DFT_EARLY == 3) dft_load(dft, P.tab, tid); }
          } else {
          if (r < 3) { skp += 1024; tap0 = ldg128(skp); tap1 = ldg128(skp + 8); }
          else if (DFT_EARLY == 3) dft_load(dft, P.tab, tid);
          }
          mbar_wait(BAR(B_KV + (r & 1)), (r >> 1) & 1);
          TZ(tid & 63, 58 + r);
#pragma unroll
          for (int j = 0; j < 11; j++) kk[j] = lds64(ka + j * 256);
#pragma unroll
          for (int j = 0; j < 8; j++) { const uint2 vv = lds64(ka + (19 + j) * 256); p[j] = vv.x; q[j] = vv.y; }
#pragma unroll
          for (int j = 0; j < 8; j++) {
            p[j] = kv_elem(kk[j].x, kk[j + 1].x, kk[j + 2].x, kk[j + 3].x, wa, p[j]);
            q[j] = kv_elem(kk[j].y, kk[j + 1].y, kk[j + 2].y, kk[j + 3].y, wb, q[j]);
          }
          asm volatile("bar.sync %0, 64;" ::"r"(5 + (r & 1) + ((p[0] | p[1] | p[2] | p[3] | p[4] | p[5] | p[6] | p[7]) & P.zero)) : "memory");
          TZ(tid | (r ^ 2) | (DBG_TIME == 2), 10);
          if (r < (K4E ? 2 : 4) && w4 == 0 && elect()) kv_issue(P, slot, BAR(B_KV), r + 2, g1);
          if (r == 2) mbar_wait(BAR(B_KVR), 0);
          TZ(tid | (r ^ 2) | (DBG_TIME == 2), 45);
          const uint32_t z = zo + (r < 4 && w4 < 2 ? sb + OFF_KVS : slot + KV_V);
          p[0] = (p[0] & ~tagm) | tagv; q[0] = (q[0] & ~tagm) | tagv;
          kv_store(z, p); kv_store(z + 1024, q);
          wfence(1);
          warp_arrive(BAR(B_KVS + (r >> 1)));
          TZ(tid | (r ^ 2) | (DBG_TIME == 2), 49);
          if (r < 2) { if (K4E == 3) round4(tap4); else stats(); }
        }
        if (K4E % 3) round4(tap0);
        TZ(tid, 21);
        if (!DFT_EARLY) dft_load(dft, P.tab, tid);
      }
    }

    if (has1) {
      mbar_wait(BAR(B_DFT), 0);
      int tries = 0;
#pragma unroll 1
      for (int l = wg == 0 ? CH_W0 : wg == 1 ? CH_W1 : CH_W2; (l & 15) != 15;) {
        const int i = l & 15;
        const float dv = c == 0 ? __uint_as_float(dq[0]) : 0.f;
        TZ(tid, 31 + 4 * i);
        mbar_wait(BAR(B_CX + i), tries & 1);
        TZ(tid, 30 + 4 * i);
        if (conv(dft, sb, conv_tile(sb, i), i ? conv_tile(sb, i) : sb + OFF_Y0, dv, 1 + wg, w4, lane, tid == 0 && ((GO_WG >> wg) & 1) && (l >> 4) == 15 && !tries ? P.flags + FL_G2 + 32 * mp.z : nullptr, ep, P.zero)) {
          warp_arrive(BAR(B_RD + i));
          l >>= 4; tries = 0; dq[0] = dq[1]; dq[1] = dq[2];
        } else {
          fence_async_smem();
          bar_sync(1 + wg);
          trap_above(++tries, 100000);
          if (tid == 0) { conv_issue_f(P, conv_tile(sb, i), g1 + 128 * i, BAR(B_CX + i)); conv_issue_x(P, conv_tile(sb, i), g1 + 128 * i, BAR(B_CX + i)); }
        }
        TZ(tid, 32 + 4 * i);
      }
    }
    if (!PRE && wg == 2 && has2) {
      const uint2* const ps[1] = {P.stats + min(80 * tj + tid, S_ - 1)};
      uint2 sv[1] = {tag_load(ps[0])};
      mbar_wait(BAR(B_EPOCH), 0);
      tag_wait<1>(ps, sv, lds32(sb + OFF_MISC));
      const float r = __uint_as_float(sv[0].y), mr = -__uint_as_float(sv[0].x) * (MIM & 1 ? 1.f : r);
      const float r2 = __shfl_down_sync(0xffffffffu, r, 1), mr2 = __shfl_down_sync(0xffffffffu, mr, 1);
      if (tid < 80 && !(tid & 1)) {
        const uint32_t hi = pack2(r, r2);
        sts128(sb + OFF_ST2 + 8 * tid, make_uint4(hi, pack2(mr, mr2), __float_as_uint(0.25f * r), __float_as_uint(0.25f * r2)));
        sts32(sb + OFF_ST2 + 640 + 2 * tid, pack2(r - blo(hi), r2 - bhi(hi)));
      }
      warp_arrive(BAR(B_EP));
    }
    if ((!has2 || wg == 2) && tid == 0) mbar_arrive(BAR(B_DONE));
    if (has2 && wg < 2) {
      float acc[40];
      const uint64_t da0 = make_desc(sb + wg * 8192, 16, 1024, 1), db0 = make_desc(sb + G2_B, 16, 1024, 1);
      const float b20 = 0.5f * ldg_bf16(P.b2 + 128 * dt + 64 * wg + 16 * w4 + g), b21 = 0.5f * ldg_bf16(P.b2 + 128 * dt + 64 * wg + 16 * w4 + g + 8);
      if (threadIdx.x == 0) mbar_arrive(BAR(B_GO));
      if (!PRE) mbar_wait(BAR(B_GO), 0);
      const bool lead = tid == 0;
      const int mi = lane >> 3, rr = lane & 7;
      const uint32_t xa = sb + OFF_XT + wg * XT_STEP + ((mi >> 1) * 8 + rr) * 128 + (((2 * w4 + (mi & 1)) ^ rr) << 4);
      const uint32_t ya = sb + OFF_YT + (64 * wg + 16 * w4 + (mi & 1) * 8 + rr) * 160 + (mi >> 1) * 16;
      uint32_t xr[5][4], xn[5][4];
      uint2 rq[10];
      uint32_t va = sb + OFF_MISC + 28, ta = sb + OFF_ST2 + 16 * c, tb = sb + OFF_ST2 + 640 + 4 * c;
      asm volatile("" : "+r"(ta), "+r"(tb));
      uint4 st[10];
      uint32_t lo[10];
      auto norm = [&](int i) {
        const uint32_t d0 = hadd2v(xr[i >> 1][2 * (i & 1)], st[i].y), d1 = hadd2v(xr[i >> 1][2 * (i & 1) + 1], st[i].y);
        st[i].y = hfma2v(d1, st[i].x, hmul2(d1, lo[i])); st[i].x = hfma2v(d0, st[i].x, hmul2(d0, lo[i]));
      };
      auto piece = [&](int j) {
        if (j == 3) {
#pragma unroll
          for (int i = 0; i < 10; i += 2) ldsm4t(xa + i * 1024, xr[i >> 1]);
        } else if (j == 4) {
#pragma unroll
          for (int i = 0; i < 10; i++) norm(i);
        } else {
#pragma unroll
          for (int i = j ? 3 * j + 1 : 0; i < 3 * j + 4; i++) { st[i] = lds128(ta + 64 * i); lo[i] = lds32(tb + 16 * i); }
        }
      };
      int np = 0;
      TZ(tid | wg, 157);
      mbar_wait(BAR(B_XF), 0);
#pragma unroll
      for (int j = 0; j < 3; j++)
        if (j < NCH && np == j && !mbar_test(BAR(B_GO), 0)) { piece(j); np = j + 1; }
      if (NCH > 3 && np == 3) {
#pragma unroll 1
        while (!mbar_test(BAR(B_GO), 0))
          if (mbar_test(BAR(B_EP), 0)) { piece(3); np = 4; break; }
      }
      if (NCH > 4 && np == 4 && !mbar_test(BAR(B_GO), 0)) { piece(4); np = 5; }
      TZ(tid | wg, 158);
      mbar_wait(BAR(B_GO), 0);
      TZ(tid | wg, 159);
#pragma unroll
      for (int i = 0; i < 40; i++) acc[i] = 0.f;
#pragma unroll 1
      for (int k0 = 0; k0 < 9; k0++) {
        const int s0 = 3 * (k0 & 1);
        const uint32_t fb = BAR(B_FULL2 + s0);
#pragma unroll
        for (int u = 0; u < 3; u++) {
          const int so = (u < 2 ? (RM ? 4 : 3) * (k0 & 1) + u : 2 + (RM ? 1 : 3) * (k0 & 1)) * (G2_STAGE >> 4);
          const uint64_t da = da0 + so, db = db0 + so;
          if (u == SK2 && k0 == 8 && wg == 1) mbar_wait(BAR(B_SKEW), 0);
          mbar_wait(fb + 8 * u, (k0 >> 1) & 1);
          TZ(threadIdx.x, 64 + 32 + 3 * k0 + u);
          wg_fence();
#pragma unroll
          for (int kk = 0; kk < 4; kk++) wgmma_ss_80_10(acc, da + kk * (2048 >> 4), db + 2 * kk);
          wg_commit();
          if (SK2 > 2 || k0 < 8) wg_wait<1>();
          if (u) { if (lead) mbar_arrive(fb + 8 * (G2_NST + u - 1)); }
          else if (lead && k0) mbar_arrive(BAR(B_EMPTY2 + 5) - 8 * s0);
        }
      }
      if (SK2 <= 2 && threadIdx.x == 0) mbar_arrive(BAR(B_SKEW));
#pragma unroll
      for (int j = 0; j < 5; j++)
        if (np <= j) { if (j == 3) mbar_wait(BAR(B_EP), 0); piece(j); }
      if (RM && TAB_AT == 2) {
#pragma unroll
        for (int i = 0; i < 10; i++) { st[i] = lds128(ta + 64 * i); lo[i] = lds32(tb + 16 * i); }
      }
      if (RM && NORM_AT == 1) {
#pragma unroll
        for (int i = 0; i < 10; i++) norm(i);
      }
#pragma unroll
      for (int i = 0; i < 10; i++) { rq[i] = make_uint2(st[i].z, st[i].w); xn[i >> 1][2 * (i & 1)] = st[i].x; xn[i >> 1][2 * (i & 1) + 1] = st[i].y; }
      TZ(threadIdx.x, 155);
      uint32_t yr[5][4];
      if (YPRE == 1) {
        mbar_wait(BAR(B_EPY), 0);
#pragma unroll
        for (int i = 0; i < 5; i++) ldsm4(ya + i * 32, yr[i]);
      }
      auto repeat = [&]() {
        wg_wait<0>();
#pragma unroll 1
        for (int i = 0, n = 0; i < 4 * 27 && n < 100000;) {
          if (!(i & 3)) {
            asm volatile("bar.sync 9, 256;" ::: "memory");
            if (threadIdx.x == 0) {
              mbar_expect(BAR(B_RT), 26624);
              tma3d(sb, &P.w2, 0, 64 * g2_block(i >> 2), 2 * dt, BAR(B_RT));
              tma2d(sb + G2_B, &P.h_ld, 64 * g2_block(i >> 2), 80 * tj, BAR(B_RT));
            }
            mbar_wait(BAR(B_RT), n++ & 1);
            uint32_t bad = 0;
            ep = lds32(sb + OFF_MISC);
#pragma unroll 1
            for (int q = 0; q < 6; q++) bad |= lds32(h_tag(sb, tj, q >> 1, lane) ^ (i >= 96 && (q & 1) ? 64 : 0)) ^ ep;
            if (__any_sync(0xffffffffu, bad & 1)) continue;
          }
          wg_fence();
          wgmma_ssp_80_10(acc, da0 + (i & 3) * (2048 >> 4), db0 + 2 * (i & 3), i);
          wg_commit();
          wg_wait<0>();
          i++;
        }
      };
      uint32_t vp = 0;
      if (!SPEC) {
        mbar_wait(BAR(B_VD), 0);
        TZ(threadIdx.x, 187);
        if (FB && mbar_test(BAR(B_BAD), 0)) repeat();
      }
    again:
      wg_wait<0>();
      TZ(tid, 50 + wg);
      mbar_wait(BAR(B_EPY), 0);
      if (!(PRE && SPEC) && tid == 0) mbar_arrive(BAR(B_DONE));
      TZ(tid, 52 + wg);
      if (YPRE == 2) {
#pragma unroll
        for (int i = 0; i < 5; i++) ldsm4(ya + i * 32, yr[i]);
      }
#pragma unroll
      for (int i = 0; i < 10; i += 2) {
        uint32_t ov[4];
        if (!YPRE) ldsm4(ya + i * 16, yr[i >> 1]);
        const uint32_t* const yq = yr[i >> 1];
#pragma unroll
        for (int j = 0; j < 2; j++) {
#pragma unroll
          for (int hf = 0; hf < 2; hf++) {
            const float bb2 = hf ? b21 : b20;
            const float z0 = fmaf(acc[4 * (i + j) + 2 * hf], __uint_as_float(rq[i + j].x), bb2), z1 = fmaf(acc[4 * (i + j) + 2 * hf + 1], __uint_as_float(rq[i + j].y), bb2);
            const uint32_t gt = pack2(fmaf(z0, tanh_fast(z0), z0), fmaf(z1, tanh_fast(z1), z1));
            ov[2 * j + hf] = hfma2(hmul2(xn[i >> 1][2 * j + hf], yq[2 * j + hf]), gt, xr[i >> 1][2 * j + hf]);
          }
        }
        if (SPEC && i == 4) {
          mbar_wait(BAR(B_VD), 0);
          TZ(threadIdx.x, 187);
          if (mbar_test(BAR(B_BAD), vp)) { repeat(); vp = 1; goto again; }
          if (tid == 0) mbar_arrive(BAR(B_DONE));
        }
        if (!OUTP && (i == 4 || i == 8)) { wfence(8); warp_arrive(BAR(B_HS + 4 * wg + (i == 8))); }
        stsm4t(xa + i * 1024, ov[0], ov[1], ov[2], ov[3]);
        if (OUTP && out_piece(i >> 1) != out_piece((i >> 1) + 1)) { wfence(8); warp_arrive(BAR(B_HS + 4 * wg + out_piece(i >> 1))); }
      }
      if (!OUTP) { wfence(8); warp_arrive(BAR(B_HS + 4 * wg + 2)); }
      TZ(tid, 6 + wg);
      DBG_END(tid);
    }
  } else {
    asm volatile("setmaxnreg.dec.sync.aligned.u32 %0;" ::"n"(R_P));
#define W(b) mbar_wait_b(BAR(b), 0);
#define KV(r) kv_issue(P, sb + OFF_KV + (r) * KV_SLOT, BAR(B_KV + (r)), r, g1);
#define PUBA rfence(1); kv_out(P, sb + OFF_KVS, 0, g1); kv_out(P, sb + OFF_KV + KV_SLOT + KV_V, 1, g1); bulk_commit(); bulk_wait_read(); \
  kv_issue(P, sb + OFF_KV + KV_SLOT, BAR(B_KV + 1), 3, g1); mbar_arrive(BAR(B_KVR)); bulk_wait_all(); pub_fence(1); flag_add_all(P.flags + FL_KV, NREP); TS(56);
#define PUBB mbar_wait_b(BAR(B_KVS + 1), 0); rfence(1); kv_out(P, sb + OFF_KVS, 2, g1); kv_out(P, sb + OFF_KV + KV_SLOT + KV_V, 3, g1); bulk_commit(); bulk_wait_read();
#define FLB bulk_wait_all(); pub_fence(1); flag_add_all(P.flags + FL_KV + 256, NREP); TS(57);
#define PUBC mbar_wait_b(BAR(B_KVS + 2), 0); rfence(1); kv_out(P, sb + (K4E ? OFF_KV4 : OFF_KV) + KV_V, 4, g1); bulk_commit(); bulk_wait_read();
#define PUBC0 mbar_wait_b(BAR(B_KVS + 2), 0); rfence(1); kv_out(P, sb + OFF_KV4 + KV_V, 4, g1); bulk_commit();
#define K4 kv_issue(P, sb + OFF_KV4, BAR(B_KV4), 4, g1);
#define KG mbar_expect(BAR(B_KVC), 4096); bulk_g2s(sb + OFF_G, P.tab + 2048, 4096, BAR(B_KVC));
#define FLC bulk_wait_all(); pub_fence(1); flag_add_all(P.flags + FL_KV + 512, NREP); TS(63);
#define KC mbar_expect(BAR(B_DFT), K4E ? 8192 : 12288); bulk_g2s(sb + OFF_DFT, P.tab, K4E ? 8192 : 12288, BAR(B_DFT));
#define F(c) conv_issue_f(P, conv_tile(sb, c), g1 + 128 * (c), BAR(B_CX + (c)));
#define G(i) if ((POLL & 2) && ((i) || (POLL & 16))) flag_poll<true>(P.flags + FL_KV + 256 * (i) + 32 * (mp.z & (NREP - 1)), ep * 128, sb + OFF_POLL + 48 * (warp - 12)); else flag_wait<true>(P.flags + FL_KV + 256 * (i) + 32 * (mp.z & (NREP - 1)), ep * 128); if (FNC & 1) fence_async_global(); TS((i) == 2 ? 28 : 23 + 6 * (i));
#define X(c) conv_issue_x(P, conv_tile(sb, c), g1 + 128 * (c), BAR(B_CX + (c)));
#define Y(c) mbar_wait_b(BAR(B_RD + (c)), 0); rfence(4); tma2d_st(&P.y_st, 0, 32 * (g1 + 128 * (c)), (c) ? conv_tile(sb, c) : sb + OFF_Y0); bulk_commit();
#define XE if (!RM) { mbar_expect(BAR(B_EP), 20480); tma2d(sb + OFF_XT, &P.x_ep, 128 * dt, 80 * tj, BAR(B_EP)); tma2d(sb + OFF_XT + XT_STEP, &P.x_ep, 128 * dt + 64, 80 * tj, BAR(B_EP)); }
#define R if (!RM) bulk_wait_read();
#define A(b) mbar_arrive(BAR(b));
#define PF(c) bulk_prefetch(P.ssm_k + (g1 + 128 * (c)) * S_, 4096);
#define PW bulk_prefetch(P.w2p + g1 * (F_ * D_ / 128), F_ * D_ / 64);
    if (warp >= 14) {
      if (has1) {
        auto b1_rows = [&]() {
          const int n0 = B1E ? 2 * lane + 64 * (warp & 1) : 0;
          if (B1E) {
            const int n1 = min(128 + n0, 222);
            const uint32_t b0 = ldg32(P.b1 + ext_col(n0, fs)), b1 = ldg32(P.b1 + ext_col(n1, fs));
            const uint32_t e0 = sb + OFF_EXT + ext_off(n0, 0), e1 = sb + OFF_EXT + ext_off(n1, 0);
#pragma unroll
            for (int k = 3; k < 8; k++) { sts32((e0 + 128 * k) ^ (k << 4), k < 5 ? b0 : 0u); sts32((e1 + 64 * k) ^ ((k >> 1) << 4), k < 5 ? b1 : 0u); }
          } else
        if (warp == 15) {
#pragma unroll 1
          for (int j = 0; j < 2; j++) {
            const int n0 = 2 * lane + 64 * j, n1 = min(128 + n0, 222);
            const uint32_t b0 = ldg32(P.b1 + ext_col(n0, fs)), b1 = ldg32(P.b1 + ext_col(n1, fs));
            const uint32_t e0 = sb + OFF_EXT + ext_off(n0, 0), e1 = sb + OFF_EXT + ext_off(n1, 0);
#pragma unroll
            for (int k = 3; k < 8; k++) { sts32((e0 + 128 * k) ^ (k << 4), k < 5 ? b0 : 0u); sts32((e1 + 64 * k) ^ ((k >> 1) << 4), k < 5 ? b1 : 0u); }
          }
        }
              };
        if (B1E) b1_rows();
        {
          float cs[8];
#pragma unroll
          for (int e = 0; e < 8; e++) cs[e] = 0.f;
          const int q = min(2 * rb, 26) + (lane & 1), kr = lane >> 1;
          const uint32_t stp = rb < 8 ? 2048 : 1024;
          const uint32_t a0 = sb + (warp & 1) * 2 * stp + (rb < 8 ? (q >> 3) * 8192 + kr * 128 + (((q & 7) ^ (kr & 7)) << 4)
                                                  : 16384 + ((q - 16) >> 2) * 4096 + kr * 64 + (((q & 3) ^ ((kr >> 1) & 3)) << 4));
#pragma unroll 1
          for (int kb = 0; kb < CS_KB; kb++) {
            const uint32_t a = a0 + (kb & 3) * G1_W;
            mbar_wait(BAR(B_FULL1 + (kb & 3)), kb >> 2);
            const uint4 u = lds128(a), w = lds128(a + stp);
            warp_arrive(BAR(B_EMPTY1 + (kb & 3)) + ((u.x | w.x) & P.zero));
            cs[0] += blo(u.x) + blo(w.x); cs[1] += bhi(u.x) + bhi(w.x); cs[2] += blo(u.y) + blo(w.y); cs[3] += bhi(u.y) + bhi(w.y);
            cs[4] += blo(u.z) + blo(w.z); cs[5] += bhi(u.z) + bhi(w.z); cs[6] += blo(u.w) + blo(w.w); cs[7] += bhi(u.w) + bhi(w.w);
          }
#pragma unroll
          for (int kb = CS_KB; kb < 6; kb++) { mbar_wait(BAR(B_EMPTY1 + (kb & 3)), 0); if (elect()) mbar_arrive(BAR(B_EMPTY1 + (kb & 3))); }
#pragma unroll
          for (int e = 0; e < 4; e++) {
            const bool up = lane & 4;
            const float o = __shfl_xor_sync(0xffffffffu, up ? cs[e] : cs[e + 4], 4);
            cs[e] = (up ? cs[e + 4] : cs[e]) + o;
          }
#pragma unroll
          for (int e = 0; e < 2; e++) {
            const bool up = lane & 2;
            const float o = __shfl_xor_sync(0xffffffffu, up ? cs[e] : cs[e + 2], 2);
            cs[e] = (up ? cs[e + 2] : cs[e]) + o;
            cs[e] += __shfl_xor_sync(0xffffffffu, cs[e], 8);
            cs[e] += __shfl_xor_sync(0xffffffffu, cs[e], 16);
          }
          const uint32_t xa = sb + OFF_ST2 + 8 * (lane & 7);
          if (warp == 15 && lane < 8) { sts32(xa, __float_as_uint(cs[0])); sts32(xa + 4, __float_as_uint(cs[1])); }
          asm volatile("bar.sync 8, 64;" ::: "memory");
          if (warp == 14) {
            const uint2 o = lds64(xa);
            mbar_wait(BAR(B_EPOCH), 0);
            if (lane < 8 && rb < 14 && (rb < 12 || fs < 6))
              tag_store(P.cs + (ext_col(16 * rb, fs) >> 1) + 4 * (lane & 1) + (lane >> 1), cs[0] + __uint_as_float(o.x), cs[1] + __uint_as_float(o.y), lds32(sb + OFF_MISC));
            TZ(lane, 18);
          }
        }
        if (!B1E) b1_rows();
      }
      mbar_wait(BAR(B_EPOCH), 0);
      const unsigned ep = lds32(sb + OFF_MISC);
      if (has1) {
        const int l2 = tid - 64, n0 = 2 * l2, n1 = min(128 + 2 * l2, 222), f0 = ext_col(n0, fs), f1 = ext_col(n1, fs);
        const uint32_t e0 = sb + OFF_EXT + ext_off(n0, 0), e1 = sb + OFF_EXT + ext_off(n1, 0);
        const uint2* const pc[4] = {P.cs + (f0 >> 1), P.cs + (f1 >> 1), P.cs + CSP + (f0 >> 1), P.cs + CSP + (f1 >> 1)};
        if (warp == 14) TZ(lane, 126);
        uint2 v[4] = {tag_load(pc[0]), tag_load(pc[1]), tag_load(pc[2]), tag_load(pc[3])};
        tag_wait<4>(pc, v, ep);
#pragma unroll
        for (int i = 0; i < 2; i++) {
          const float x = __uint_as_float(v[i].x) + __uint_as_float(v[i + 2].x), y = __uint_as_float(v[i].y) + __uint_as_float(v[i + 2].y);
          const uint32_t hi = pack2(x, y), lo = pack2(x - blo(hi), y - bhi(hi));
#pragma unroll
          for (int k = 0; k < 3; k++) sts32(i ? (e1 + 64 * k) ^ ((k >> 1) << 4) : (e0 + 128 * k) ^ (k << 4), k < 2 ? hi : lo);
        }
        TZ(lane, 25);
        fence_async_smem();
        warp_arrive(BAR(B_TAB));
      }
      if (PRE && has2 && warp == 14) {
        const int q1 = 32 + (lane & 7);
        const uint2 *const p0 = P.stats + min(80 * tj + 2 * lane, S_ - 2), *const p1 = P.stats + min(80 * tj + 2 * q1, S_ - 2);
        const uint2* const ps[4] = {p0, p0 + 1, p1, p1 + 1};
        uint2 sv[4] = {tag_load(ps[0]), tag_load(ps[1]), tag_load(ps[2]), tag_load(ps[3])};
        tag_wait<4>(ps, sv, ep);
#pragma unroll
        for (int j = 0; j < 2; j++) {
          const float r = __uint_as_float(sv[2 * j].y), r2 = __uint_as_float(sv[2 * j + 1].y);
          const uint32_t hi = pack2(r, r2), q = j ? q1 : lane;
          sts128(sb + OFF_ST2 + 16 * q, make_uint4(hi, pack2(-__uint_as_float(sv[2 * j].x), -__uint_as_float(sv[2 * j + 1].x)), __float_as_uint(0.25f * r), __float_as_uint(0.25f * r2)));
          sts32(sb + OFF_ST2 + 640 + 4 * q, pack2(r - blo(hi), r2 - bhi(hi)));
        }
        warp_arrive(BAR(PRE == 2 ? B_XF : B_EP));
      }
      __syncwarp();
      if (elect()) {
        if (warp == 15) {
          if (CHK == 3) for (int s = 0; s < G2_NST; s++) mbar_arrive(BAR(B_EMPTY2 + s));
          if (has1) {
            prefetch_map(&P.h_st); prefetch_map(&P.h_st2);
#pragma unroll
            for (int j = 0; j < 4; j++) {
              mbar_wait(BAR(B_HS + 4 * (j & 1) + (j & 2)), 0); rfence(2);
              if (j & 1) TS(33 + 4 * (j & 2));
              tma2d_st(&P.h_st, 192 * fs + 64 * (j & 2), 128 * rb + 64 * (j & 1), sb + OFF_X + (j & 2) * G1_X + (j & 1) * 8192);
              if (j == 1) {
                bulk_commit();
                bulk_wait_all();
                h_flag(P, rb, 0);
                mbar_arrive(BAR(B_EMPTY2 + 4 - RM));
                TS(26);
              }
            }
            if (fs < 6) {
#pragma unroll
              for (int w = 0; w < 2; w++) {
                mbar_wait(BAR(B_HS + 4 * w + 3), 0); rfence(2);
                tma2d_st(&P.h_st2, 1536 + 32 * fs, 128 * rb + 64 * w, sb + OFF_X + 3 * G1_X + w * 4096);
              }
            }
            bulk_commit();
            bulk_wait_all();
            mbar_arrive(BAR(B_EMPTY2 + 5 - RM));
            pub_fence(2);
            h_flag(P, rb, 64);
            TS(14);
          }
          if (has2) {
            h_wait(P, tj, 64, ep, sb + OFF_POLL + 144);
            mbar_arrive(BAR(B_HB));
            TS(17);
          }
        }
      }
      __syncwarp();
      if (warp == 15 && has2) {
        uint32_t ta[3], bad = 0;
#pragma unroll
        for (int q = 0; q < 3; q++) ta[q] = h_tag(sb, tj, q, lane);
        int s = 0, ph = 0;
#pragma unroll 1
        for (int kb = 0; kb < 27; kb++) {
          mbar_wait(BAR(B_FULL2 + s), ph);
          uint32_t t = 0;
#pragma unroll
          for (int q = 0; q < 3; q++) t |= lds32(ta[q] + g2_slot(s) * G2_STAGE) ^ ep;
          if (kb >= 24) {
#pragma unroll
            for (int q = 0; q < 3; q++) t |= lds32((ta[q] ^ 64) + g2_slot(s) * G2_STAGE) ^ ep;
          }
          bad |= t;
          if (CHK == 3 && lane == 0) mbar_arrive(BAR(B_EMPTY2 + s) + (t & P.zero));
          if (++s == G2_NST) { s = 0; ph ^= 1; }
        }
        bad = __any_sync(0xffffffffu, bad & 1);
        if (lane == 0) { if (!PRE) sts32(sb + OFF_MISC + 28, bad); else if (bad) mbar_arrive(BAR(B_BAD)); mbar_arrive(BAR(B_VD)); }
      }
      if (elect()) {
        if (W14ON && warp == 14 && has1) { prefetch_map(&P.kvz); prefetch_map(&P.f_ld); W14 }
        if (warp == 14 && has2) {
          prefetch_map(&P.h_ld);
          auto x_issue = [&]() {
            mbar_expect(BAR(B_EP), 20480);
            tma2d(sb + g2_slot(5) * G2_STAGE, &P.x_ep, 128 * dt, 80 * tj, BAR(B_EP));
            tma2d(sb + g2_slot(5) * G2_STAGE + 10240, &P.x_ep, 128 * dt + 64, 80 * tj, BAR(B_EP));
          };
          if (RM) { prefetch_map(&P.x_ep); mbar_wait(BAR(B_G1FREE), 0); }
          if (RM && XE_AT == 0) x_issue();
          if (RM && XE_AT == 3) { if (has1) mbar_wait(BAR(B_HS + 1), 0); x_issue(); }
          h_wait(P, tj, 0, ep, sb + OFF_POLL + 96);
          if (RM && XE_AT == 1) x_issue();
          TS(16);
#pragma unroll 1
          for (int k0 = 0; k0 < 9; k0++) {
#pragma unroll
            for (int u = 0; u < 3; u++) {
              const int kb = 3 * k0 + u, s = 3 * (k0 & 1) + u;
              if (RM && !GO5 && u == 2 && k0 == 1) mbar_wait(BAR(B_XF), 0);
              if (RM && GO5 ? u == 2 && k0 == 1 : u == 0 && k0 == 2) {
                if (POLL & 1) flag_poll<false>(P.flags + FL_G2 + 32 * mp.z, ep * mp.w * GO_N, sb + OFF_POLL + 96); else flag_wait<false>(P.flags + FL_G2 + 32 * mp.z, ep * mp.w * GO_N);
                mbar_arrive(BAR(B_GO));
                TS(20);
              }
              if (RM && XE_AT == 2 && u == 0 && k0 == 1) x_issue();
              if (RM && GO5 && u == 2 && k0 == 1) mbar_wait(BAR(B_XF), 0);
              if (u == 2 && k0 == 2) mbar_wait(BAR(B_H1), 0);
              if (u == 1 && k0 == 5) mbar_wait(BAR(B_HB), 0);
              mbar_wait(BAR(B_EMPTY2 + s), (k0 >> 1) & 1);
              TS(64 + 96 + kb);
              mbar_expect(BAR(B_FULL2 + s), 10240);
              tma2d(sb + (u < 2 ? (RM ? 4 : 3) * (k0 & 1) + u : 2 + (RM ? 1 : 3) * (k0 & 1)) * G2_STAGE + G2_B, &P.h_ld, 64 * g2_block(kb), 80 * tj, BAR(B_FULL2 + s));
              if (u == YK % 3 && k0 == YK / 3) mbar_arrive(BAR(B_LATE));
            }
          }
        }
        if (has2) {
          const int w = 15 - warp;
          prefetch_map(&P.out_st);
#pragma unroll
          for (int j = 0; j < 5; j++) {
            if (!j || out_piece(j) != out_piece(j - 1)) { mbar_wait(BAR(B_HS + 4 * w + out_piece(j)), has1 && (out_piece(j) < 3 || fs < 6)); rfence(8); }
            tma2d_st(&P.out_st, 128 * dt + 64 * w, 80 * tj + 16 * j, sb + OFF_XT + w * XT_STEP + j * 2048);
          }
          bulk_commit();
        }
        mbar_arrive(BAR(B_DONE));
        bulk_wait_read();
        TS(54 + 15 - warp);
        DBG_END(0);
      }
    } else if (warp == 13) {
      unsigned ep;
      asm volatile("ld.relaxed.gpu.global.u32 %0, [%1];" : "=r"(ep) : "l"(P.flags + FL_EPOCH) : "memory");
      if (has1 && lane < 5) sts32(sb + OFF_MISC + 4 + 4 * lane, __float_as_uint(ldg_bf16(P.ssm_D + g1 + 128 * lane)));
      ep += 1;
      __syncwarp();
      if (elect()) {
        sts32(sb + OFF_MISC, ep); sts32(sb + OFF_MISC + 24, 0);
        mbar_arrive(BAR(B_EPOCH));
        if (PFW && has1) bulk_prefetch(P.w1p + 256 * F_ + g1 * (PFW * F_ / 2), PFW * F_);
        flag_add_rlx(P.flags + FL_START, 1);
        if (!has1 && has2) flag_add_rlx(P.flags + FL_G2 + 32 * mp.z, GO_N);
        if (has1) {
          prefetch_map(&P.kvz); prefetch_map(&P.f_ld); prefetch_map(&P.y_st);
          AUX_SEQ
          bulk_wait_all(); pub_fence(4);
          flag_add_all(P.flags + FL_Y, NREPY);
          TS(12);
          if (g1 == 0) { flag_wait<true>(P.flags + FL_START, ep * NCTA); P.flags[FL_EPOCH] = ep; }
        }
        if (has2) {
          mbar_expect(BAR(B_EPY), 20480);
          prefetch_map(&P.y_ld);
          if (!RM && !has1) {
            if (PRE) mbar_wait_b(BAR(B_EMPTY2), 0);
            mbar_expect(BAR(B_EP), 20480);
            tma2d(sb + OFF_XT, &P.x_ep, 128 * dt, 80 * tj, BAR(B_EP));
            tma2d(sb + OFF_XT + XT_STEP, &P.x_ep, 128 * dt + 64, 80 * tj, BAR(B_EP));
          }
          flag_wait<true>(P.flags + FL_Y + 32 * (mp.z & (NREPY - 1)), ep * 128);
          fence_async_global();
          mbar_wait_b(BAR(B_LATE), 0);
          TS(13);
          tma2d(sb + OFF_YT, &P.y_ld, 80 * tj, 128 * dt, BAR(B_EPY));
        }
        mbar_wait_b(BAR(B_DONE), 0);
      }
    } else {
      const bool lead = elect();
      if (lead) {
        mbar_init(BAR(B_FULL1), 1);
        fence_async_smem();
        grid_wait<GRIDS>();
        if (has1) g1_issue(P, sb, 0, BAR(B_FULL1), 0, rb, fs);
        else if (!SP_D0 && !SP_FAKE) { mbar_expect(BAR(B_FULL1), CS_STAGE); tma3d(sb, &P.w1_cs, 0, 64 * CS_KB, 7 * (g1 - 128), BAR(B_FULL1)); }
#pragma unroll
        for (int b = 1; b < B_FIRST; b++) mbar_init(BAR(b), 1);
        fence_async_smem();
      }
      __syncwarp();
      asm volatile("bar.arrive 0, 512;" ::: "memory");
      if (lead) {
        if (has1) {
#define S(kb) g1_issue(P, sb, kb, BAR(B_FULL1 + (kb)), kb, rb, fs);
#define K(r) kv_issue(P, sb + OFF_KV + (r) * KV_SLOT, BAR(B_KV + (r)), r, g1);
#define T mbar_expect(BAR(B_STAT), 20480); bulk_g2s(sb + OFF_SR, P.x + g1 * 16 * D_, 20480, BAR(B_STAT));
          grid_wait<GRID0>();
          INIT_SEQ
          TS(64 + 20 + 3);
        } else {
#pragma unroll
          for (int kb = SP_FAKE ? 3 : SP_D0 ? 0 : 1; kb < 3; kb++) { clk_wait(kb ? SP_D1 : SP_D0); mbar_expect(BAR(B_FULL1 + kb), CS_STAGE); tma3d(sb + kb * CS_STAGE, &P.w1_cs, 0, 64 * (CS_KB + kb), 7 * (g1 - 128), BAR(B_FULL1 + kb)); }
        }
      }
      __syncwarp();
      asm volatile("bar.sync 7, 512;" ::: "memory");
      if (lead) {
        if (has1) {
#pragma unroll 1
          for (int kb = G1_NST; kb < STE; kb++) {
            const int s = kb & 3;
            mbar_wait(BAR(B_EMPTY1 + s), ((kb >> 2) - 1) & 1);
            grid_wait<GRID1>();
            TS(64 + 20 + kb);
            g1_issue(P, sb, s, BAR(B_FULL1 + s), kb, rb, fs);
          }
        }
      }
      __syncwarp();
      if (has1) {
        const uint2* const p0 = P.stats + 128 * rb + lane;
        const uint2* const ps[4] = {p0, p0 + 32, p0 + 64, p0 + 96};
        TZ(lane, 124);
        uint2 sv[4] = {tag_load(ps[0]), tag_load(ps[1]), tag_load(ps[2]), tag_load(ps[3])};
        if (lead) {
#pragma unroll
          for (int kb = STE; kb < 10; kb++) {
            const int s = kb & 3;
            mbar_wait(BAR(B_EMPTY1 + s), ((kb >> 2) - 1) & 1);
            TS(64 + 20 + kb);
            g1_issue(P, sb, s, BAR(B_FULL1 + s), kb, rb, fs);
          }
        }
        __syncwarp();
        mbar_wait(BAR(B_EPOCH), 0);
        if (POLL & 8) tag_wait2<4>(ps, sv, lds32(sb + OFF_MISC)); else tag_wait<4>(ps, sv, lds32(sb + OFF_MISC));
#pragma unroll
        for (int j = 0; j < 4; j++) {
          const float mn = -__uint_as_float(sv[j].x), mh = bf_round(mn), sd = rcp_fast(__uint_as_float(sv[j].y)), sh = bf_round(sd);
          sts128(sb + OFF_ST1 + 16 * (lane + 32 * j), make_uint4(pack2(mh, mn - mh), pack2(mh, sh), pack2(sd - sh, 0.f), sv[j].y));
        }
        warp_arrive(BAR(B_TAB));
        TZ(lane, 11);
      }
      if (lead) {
        if (!has1) {
#pragma unroll
          for (int kb = SP_FAKE ? 10 : CS_KB + 3; kb < 10; kb++) {
            const int s = kb - CS_KB - 3;
            mbar_wait(BAR(B_EMPTY1 + s), 0);
            clk_wait(SP_D1);
            mbar_expect(BAR(B_FULL1 + s), CS_STAGE);
            tma3d(sb + s * CS_STAGE, &P.w1_cs, 0, 64 * kb, 7 * (g1 - 128), BAR(B_FULL1 + s));
          }
        }
        auto h_second = [&]() {
#pragma unroll
          for (int w = 0; w < 2; w++) {
            mbar_wait(BAR(B_HS + 4 * w + 1), 0); rfence(2);
            tma2d_st(&P.h_st, 192 * fs + 64, 128 * rb + 64 * w, sb + OFF_X + G1_X + w * 8192);
          }
          TS(37);
          bulk_commit();
          bulk_wait_all();
          mbar_arrive(BAR(B_EMPTY2 + 4 - RM)); mbar_arrive(BAR(B_EMPTY2 + 5 - RM));
          pub_fence(2);
          h_flag(P, rb, 32);
          TS(27);
        };
        if (has2) {
          prefetch_map(&P.w2);
#pragma unroll 1
          for (int k0 = 0; k0 < 9; k0++) {
#pragma unroll
            for (int u = 0; u < 3; u++) {
              const int kb = 3 * k0 + u, s = 3 * (k0 & 1) + u;
              if (u == 1 - RM && k0 == 1 && has1) h_second();
              if (RM && u == 2 && k0 == 1) mbar_wait(BAR(B_XF), 0);
              if (u == 0 && k0 == 2) { mbar_wait(BAR(B_EPOCH), 0); h_wait(P, tj, 32, lds32(sb + OFF_MISC), sb + OFF_POLL); mbar_arrive(BAR(B_H1)); TS(15); }
              mbar_wait(BAR(B_EMPTY2 + s), (k0 >> 1) & 1);
              mbar_expect(BAR(B_FULL2 + s), 16384);
              tma3d(sb + (u < 2 ? (RM ? 4 : 3) * (k0 & 1) + u : 2 + (RM ? 1 : 3) * (k0 & 1)) * G2_STAGE, &P.w2, 0, 64 * g2_block(kb), 2 * dt, BAR(B_FULL2 + s));
            }
          }
        }
        mbar_arrive(BAR(B_DONE));
      }
    }
  }

#undef BAR
}

typedef CUresult (*EncodeFn)(CUtensorMap*, CUtensorMapDataType, cuuint32_t, void*, const cuuint64_t*, const cuuint64_t*, const cuuint32_t*,
                             const cuuint32_t*, CUtensorMapInterleave, CUtensorMapSwizzle, CUtensorMapL2promotion, CUtensorMapFloatOOBfill);

static void enc(EncodeFn f, CUtensorMap* m, const void* base, int rank, const cuuint64_t* dims, const cuuint64_t* strides, const cuuint32_t* box, CUtensorMapSwizzle sw) {
  const cuuint32_t es[5] = {1, 1, 1, 1, 1};
  f(m, CU_TENSOR_MAP_DATA_TYPE_BFLOAT16, rank, const_cast<void*>(base), dims, strides, box, es, CU_TENSOR_MAP_INTERLEAVE_NONE, sw,
    CU_TENSOR_MAP_L2_PROMOTION_L2_128B, CU_TENSOR_MAP_FLOAT_OOB_FILL_NONE);
}
static void enc2(EncodeFn f, CUtensorMap* m, const void* base, uint64_t d0, uint64_t d1, uint32_t b0, uint32_t b1, CUtensorMapSwizzle sw) {
  const cuuint64_t dims[2] = {d0, d1}, strides[1] = {d0 * 2};
  const cuuint32_t box[2] = {b0, b1};
  enc(f, m, base, 2, dims, strides, box, sw);
}

extern "C" void kernel_launch(void* const* d_in, const int* in_sizes, int n_in, void* d_out, int out_size) {
  (void)in_sizes; (void)n_in; (void)out_size;
  static EncodeFn fn = nullptr;
  static void *p_h, *p_kvZ, *p_yT, *p_stats, *p_cs, *p_flags, *p_tab;
  if (!fn) {
    cudaDriverEntryPointQueryResult qr;
    void* f = nullptr;
    cudaGetDriverEntryPoint("cuTensorMapEncodeTiled", &f, cudaEnableDefault, &qr);
    fn = (EncodeFn)f;
    cudaFuncSetAttribute(h3_fused_kernel, cudaFuncAttributeMaxDynamicSharedMemorySize, SMEM_BYTES);
    cudaGetSymbolAddress(&p_h, g_h); cudaGetSymbolAddress(&p_kvZ, g_kvZ); cudaGetSymbolAddress(&p_yT, g_yT);
    cudaGetSymbolAddress(&p_stats, g_stats); cudaGetSymbolAddress(&p_cs, g_cs); cudaGetSymbolAddress(&p_flags, g_flags); cudaGetSymbolAddress(&p_tab, g_tab);
  }
  Params P;
  const bf16 *x = (const bf16*)d_in[0], *k = (const bf16*)d_in[1], *v = (const bf16*)d_in[2];
  const bf16 *w1 = (const bf16*)d_in[7], *w2 = (const bf16*)d_in[9];
  P.x = x; P.shift_k = (const bf16*)d_in[3]; P.ssm_k = (const bf16*)d_in[4]; P.ssm_D = (const bf16*)d_in[5];
  P.b1 = (const bf16*)d_in[8]; P.b2 = (const bf16*)d_in[10]; P.w2p = w2; P.w1p = w1;
  P.zero = 0; P.kvZ = (bf16*)p_kvZ; P.tab = (const uint32_t*)p_tab; P.stats = (uint2*)p_stats; P.cs = (uint2*)p_cs; P.flags = (unsigned*)p_flags;
  enc2(fn, &P.x_g1, x, D_, S_, 64, 128, CU_TENSOR_MAP_SWIZZLE_128B);
  {
    const cuuint64_t dims[3] = {64, D_, 27}, strides[2] = {F_ * 2, 128};
    const cuuint32_t box[3] = {64, 64, 2};
    enc(fn, &P.w1_a, w1, 3, dims, strides, box, CU_TENSOR_MAP_SWIZZLE_128B);
    const cuuint32_t box7[3] = {64, 64, 7};
    enc(fn, &P.w1_cs, w1, 3, dims, strides, box7, CU_TENSOR_MAP_SWIZZLE_128B);
    const cuuint64_t dims2[3] = {32, D_, 54}, strides2[2] = {F_ * 2, 64};
    const cuuint32_t box2[3] = {32, 64, 2}, box1[3] = {32, 64, 1};
    enc(fn, &P.w1_b2, w1, 3, dims2, strides2, box2, CU_TENSOR_MAP_SWIZZLE_64B);
    enc(fn, &P.w1_b1, w1, 3, dims2, strides2, box1, CU_TENSOR_MAP_SWIZZLE_64B);
  }
  enc2(fn, &P.h_ld, p_h, F_, S_, 64, 80, CU_TENSOR_MAP_SWIZZLE_128B);
  {
    const cuuint64_t dims[3] = {64, F_, 10}, strides[2] = {D_ * 2, 128};
    const cuuint32_t box[3] = {64, 64, 2};
    enc(fn, &P.w2, w2, 3, dims, strides, box, CU_TENSOR_MAP_SWIZZLE_128B);
  }
  enc2(fn, &P.h_st, p_h, F_, S_, 64, 64, CU_TENSOR_MAP_SWIZZLE_128B);
  enc2(fn, &P.h_st2, p_h, F_, S_, 32, 64, CU_TENSOR_MAP_SWIZZLE_64B);
  enc2(fn, &P.k, k, D_, S_, 128, 19, CU_TENSOR_MAP_SWIZZLE_NONE);
  enc2(fn, &P.v, v, D_, S_, 128, 16, CU_TENSOR_MAP_SWIZZLE_NONE);
  {
    const cuuint64_t dims[3] = {D_ * 16, 32, 4}, strides[2] = {D_ * 128, D_ * 32};
    const cuuint32_t box[3] = {16, 32, 4};
    enc(fn, &P.kvz, p_kvZ, 3, dims, strides, box, CU_TENSOR_MAP_SWIZZLE_32B);
  }
  enc2(fn, &P.f_ld, P.ssm_k, 64, D_ * 32, 64, 32, CU_TENSOR_MAP_SWIZZLE_128B);
  enc2(fn, &P.y_st, p_yT, 64, D_ * 32, 64, 32, CU_TENSOR_MAP_SWIZZLE_128B);
  enc2(fn, &P.y_ld, p_yT, S_, D_, 80, 128, CU_TENSOR_MAP_SWIZZLE_NONE);
  enc2(fn, &P.x_ep, x, D_, S_, 64, 80, CU_TENSOR_MAP_SWIZZLE_128B);
  enc2(fn, &P.out_st, d_out, D_, S_, 64, 16, CU_TENSOR_MAP_SWIZZLE_128B);
  for (int b = 0; b < 72; b++) P.cnt[b] = 1;
  P.cnt[B_XF] = PRE == 2 ? 1 : 8;
  for (int b = 0; b < 5; b++) { P.cnt[B_CX + b] = 2; P.cnt[B_RD + b] = 4; }
  for (int b = 0; b < 4; b++) P.cnt[B_EMPTY1 + b] = 4;
  for (int b = 0; b < 2 * G2_NST; b++) P.cnt[B_FULL2 + b] = CHK == 3 && b >= G2_NST ? 3 : 2;
  P.cnt[B_DBG] = 4;
  P.cnt[B_G1FREE] = P.cnt[B_GO] = 2; P.cnt[B_TAB] = 3; P.cnt[B_EP] = PRE == 2 ? 1 : PRE ? 2 : 5; P.cnt[B_DONE] = 6;
  for (int b = 0; b < 8; b++) P.cnt[B_HS + b] = 4;
  P.cnt[B_KVS] = P.cnt[B_KVS + 1] = P.cnt[B_STATFREE] = 4; P.cnt[B_KVS + 2] = K4E ? 4 : 2;
  {
    const char *g1s = G1MAP, *g2s = G2MAP, *gos = GOMAP;
    int mem[10][18], cnt[10] = {0}, used[10] = {0}, gn[9] = {0};
    for (int b = 0; b < NCTA; b++) {
      const int tpc = b >> 1;
      const int gp = tpc < 32 ? tpc % 8 : tpc < 60 ? 1 + (tpc - 32) % 7 : tpc < 62 ? tpc - 54 : tpc == 63 ? 8 : tpc == 64 ? 9 : 0;
      mem[gp][cnt[gp]++] = b;
      P.map[b] = make_uchar4(255, 255, gos[gp] - '0', 0);
    }
    auto tile = [&](int gp, int i) { const int q = g1s[gp] - '0'; return (4 * (q >> 1) + (i & 3)) * 8 + 4 * (q & 1) + (i >> 2); };
    for (int gp = 0; gp < 8; gp++)
      for (int i = 0; i < (gp ? 16 : 8); i++) P.map[mem[gp][i]].x = tile(gp, i);
    for (int i = 0; i < 4; i++) {
      P.map[mem[8 + (i >> 1)][i & 1]].x = tile(0, 8 + i);
      P.map[mem[0][8 + i]].x = tile(0, 12 + i);
      P.map[mem[6 + (i >> 1)][16 + (i & 1)]].x = 128 + i;
    }
    for (int n = 0; *g2s; g2s++) {
      if (*g2s == ' ') continue;
      const int gp = *g2s < 'a' ? *g2s - 'A' : *g2s - 's' + 8;
      P.map[mem[gp][used[gp]++]].y = n / 5 * 8 + n % 5;
      gn[gos[gp] - '0']++;
      n++;
    }
    for (int b = 0; b < NCTA; b++) P.map[b].w = gn[P.map[b].z];
  }
  h3_fused_kernel<<<NCTA, 512, SMEM_BYTES, cudaStreamPerThread>>>(P);
}
```

```cpp
#include <cuda_runtime.h>
#include <cuda_bf16.h>
#include <cuda.h>
#include <stdint.h>
#include <stdlib.h>

#define K4E 0
#define INIT_SEQ S(1) S(2) S(3) K(0) K(1) T
#define AUX_PRE
#define W14ON (K4E == 4)
#define W14 W(B_G1FREE) F(3) W(B_T2) F(2) G(1) X(3) X(2)
#define AUX_SEQ AUX_PRE W(B_KVS) PUBA W(B_STATFREE) KC F(0) PF(1) G(0) X(0) PF(2) PF(3) PUBB X(1) F(1) FLB PF(4) PW PUBC A(B_KVC) F(2) FLC W(B_G1FREE) F(3) G(1) X(3) X(2) G(2) W(B_RD) X(4) F(4) AUX_END
#define G1MAP "70123465"
#define G2MAP "BBBBB BBBBB BBBBB BCCCC CCCCC CCCCC CCDDD DDDDD DDDDD DDDGG GGGGG GGGGG GGGGG HHHHH HHHHH HHHHH HHEEE EEEEE EEEEE EEssE AAAAA AAAAA AAttF FFFFF FFFFF FFFFF"
#define GOMAP "0123456745"
#define SP_FAKE 0
#define POLL 0
#define PD 200
#define TD 450
#define NREP 1
#define NREPY 1
#define FNC 3
#define OUTP 0x32210
#define STU 0
#define GRID0 0
#define GRID1 0
#define GRIDS 0
#define MC 2
#define MC1 4
#define MCX 0
#define MCW 0
#define MCV 2
#define MC0 4
#define BOUND 0
#define HOLD 0
#define EXPECT(x) (x)
#define EPP 0
#define SP_D0 0
#define SP_D1 0
#define PRE 2
#define RM (PRE == 1)
#define AUX_END Y(0) Y(1) R XE Y(2) Y(3) Y(4)
#define SPEC 0
#define NCH 3
#define TAB_AT 0
#define NORM_AT 1
#define GO5 1
#define XE_AT 1
#define YPRE 0
#define B1E 1
#define STE 10
#define NOW 10
#define CH_W0 0xf2
#define CH_W1 0xf3
#define CH_W2 0xf410
#define CS_KB 5
#define CHK 3
#define MIM 1
#define KVCHK 1
#define FB 1
#define DFT_EARLY 3
#define GO_WG 4
#define EREL 0
#define PFW 0
#define SK2 2
#define YK 26
#define DFT_AT 16
#define USE_GO 1
#define GO_AT 2
#define HS_LAG 0
#define LOOKAHEAD 2
#define SPLIT9 0
#define GELU_BF16 4
#define R_G 160
#define R_P 32
#define DBG_TIME 0

namespace {

constexpr int GO_N = (GO_WG & 1) + ((GO_WG >> 1) & 1) + (GO_WG >> 2);
constexpr int S_ = 2048, D_ = 640, F_ = 1728;
constexpr int NCTA = 132;
typedef __nv_bfloat16 bf16;

__device__ __align__(1024) bf16 g_h[S_ * F_];
__device__ __align__(1024) bf16 g_kvZ[D_ * S_];
__device__ __align__(1024) bf16 g_yT[D_ * S_];
__device__ __align__(128) uint2 g_stats[S_];
constexpr int CSP = F_ / 2 + 32;
__device__ __align__(128) uint2 g_cs[2 * CSP];
constexpr int FL_EPOCH = 0, FL_START = 32, FL_KV = 64  , FL_Y = FL_KV + 3 * 256  , FL_H = FL_Y + 256  , FL_G2 = FL_H + 96 * 32  , FL_COUNT = FL_G2 + 9 * 32;
__device__ __align__(128) unsigned g_flags[FL_COUNT];
__device__ __align__(128) const uint32_t g_tab[6144] = {
0x3f803f80,0x3f803f80,0x3f803f80,0x3f803f80,0x3f803f80,0x3f803f80,0x3f803f80,0x3f803f80,0x3f803f80,0x3f803f80,0x3f803f80,0x3f803f80,0x3f803f80,0x3f803f80,0x3f803f80,0x3f803f80,
0x0,0x0,0x0,0x0,0x0,0x0,0x0,0x0,0x0,0x0,0x0,0x0,0x0,0x0,0x0,0x0,
0x3f183f2c,0x3edb3f04,0x3e793eac,0x3d493e16,0x3f7d3f80,0x3f713f78,0x3f5c3f67,0x3f3e3f4e,0xbf4ebf3e,0xbf67bf5c,0xbf78bf71,0xbf80bf7d,0xbe16bd49,0xbeacbe79,0xbf04bedb,0xbf2cbf18,
0x3f4e3f3e,0x3f673f5c,0x3f783f71,0x3f803f7d,0x3e163d49,0x3eac3e79,0x3f043edb,0x3f2c3f18,0x3f183f2c,0x3edb3f04,0x3e793eac,0x3d493e16,0x3f7d3f80,0x3f713f78,0x3f5c3f67,0x3f3e3f4e,
0xbf75bf7f,0xbf46bf62,0xbef1bf22,0xbdc9be95,0x3e953dc9,0x3f223ef1,0x3f623f46,0x3f7f3f75,0x3f753f7f,0x3f463f62,0x3ef13f22,0x3dc93e95,0xbe95bdc9,0xbf22bef1,0xbf62bf46,0xbf7fbf75,
0xbe95bdc9,0xbf22bef1,0xbf62bf46,0xbf7fbf75,0xbf75bf7f,0xbf46bf62,0xbef1bf22,0xbdc9be95,0x3e953dc9,0x3f223ef1,0x3f623f46,0x3f7f3f75,0x3f753f7f,0x3f463f62,0x3ef13f22,0x3dc93e95,
0x3eac3f18,0xbe793d49,0xbf3ebf04,0xbf7dbf67,0x3edb3e16,0x3f5c3f2c,0x3f803f78,0x3f4e3f71,0xbf71bf4e,0xbf78bf80,0xbf2cbf5c,0xbe16bedb,0x3f673f7d,0x3f043f3e,0xbd493e79,0xbf18beac,
0x3f713f4e,0x3f783f80,0x3f2c3f5c,0x3e163edb,0xbf67bf7d,0xbf04bf3e,0x3d49be79,0x3f183eac,0x3eac3f18,0xbe793d49,0xbf3ebf04,0xbf7dbf67,0x3edb3e16,0x3f5c3f2c,0x3f803f78,0x3f4e3f71,
0x3f0e3e48,0x3f7b3f55,0x3f553f7b,0x3e483f0e,0xbf0ebe48,0xbf7bbf55,0xbf55bf7b,0xbe48bf0e,0x3f0e3e48,0x3f7b3f55,0x3f553f7b,0x3e483f0e,0xbf0ebe48,0xbf7bbf55,0xbf55bf7b,0xbe48bf0e,
0x3f553f7b,0x3e483f0e,0xbf0ebe48,0xbf7bbf55,0xbf55bf7b,0xbe48bf0e,0x3f0e3e48,0x3f7b3f55,0x3f553f7b,0x3e483f0e,0xbf0ebe48,0xbf7bbf55,0xbf55bf7b,0xbe48bf0e,0x3f0e3e48,0x3f7b3f55,
0xbf80bf5c,0xbf18bf67,0x3eacbe16,0x3f783f3e,0x3f2c3e79,0x3f7d3f71,0x3edb3f4e,0xbf04bd49,0xbd49bf04,0x3f4e3edb,0x3f713f7d,0x3e793f2c,0x3f3e3f78,0xbe163eac,0xbf67bf18,0xbf5cbf80,
0xbd49bf04,0x3f4e3edb,0x3f713f7d,0x3e793f2c,0x3f3e3f78,0xbe163eac,0xbf67bf18,0xbf5cbf80,0x3f803f5c,0x3f183f67,0xbeac3e16,0xbf78bf3e,0xbf2cbe79,0xbf7dbf71,0xbedbbf4e,0x3f043d49,
0xbf46be95,0xbf62bf7f,0x3dc9bef1,0x3f753f22,0x3f223f75,0xbef13dc9,0xbf7fbf62,0xbe95bf46,0x3f463e95,0x3f623f7f,0xbdc93ef1,0xbf75bf22,0xbf22bf75,0x3ef1bdc9,0x3f7f3f62,0x3e953f46,
0xbf22bf75,0x3ef1bdc9,0x3f7f3f62,0x3e953f46,0xbf46be95,0xbf62bf7f,0x3dc9bef1,0x3f753f22,0x3f223f75,0xbef13dc9,0xbf7fbf62,0xbe95bf46,0x3f463e95,0x3f623f7f,0xbdc93ef1,0xbf75bf22,
0xbf78bf67,0x3d49bf18,0x3f7d3f2c,0x3eac3f5c,0xbf04bf71,0x3f3e3e16,0x3f4e3f80,0xbedb3e79,0x3e79bedb,0x3f803f4e,0x3e163f3e,0xbf71bf04,0x3f5c3eac,0x3f2c3f7d,0xbf183d49,0xbf67bf78,
0x3e79bedb,0x3f803f4e,0x3e163f3e,0xbf71bf04,0x3f5c3eac,0x3f2c3f7d,0xbf183d49,0xbf67bf78,0x3f783f67,0xbd493f18,0xbf7dbf2c,0xbeacbf5c,0x3f043f71,0xbf3ebe16,0xbf4ebf80,0x3edbbe79,
0x3ec43f6d,0xbf6dbec4,0xbec4bf6d,0x3f6d3ec4,0x3ec43f6d,0xbf6dbec4,0xbec4bf6d,0x3f6d3ec4,0x3ec43f6d,0xbf6dbec4,0xbec4bf6d,0x3f6d3ec4,0x3ec43f6d,0xbf6dbec4,0xbec4bf6d,0x3f6d3ec4,
0x3f6d3ec4,0x3ec43f6d,0xbf6dbec4,0xbec4bf6d,0x3f6d3ec4,0x3ec43f6d,0xbf6dbec4,0xbec4bf6d,0x3f6d3ec4,0x3ec43f6d,0xbf6dbec4,0xbec4bf6d,0x3f6d3ec4,0x3ec43f6d,0xbf6dbec4,0xbec4bf6d,
0xbf043eac,0xbf3ebf7d,0x3f4e3d49,0x3edb3f78,0x3e793f67,0xbf80bf18,0x3e16bf2c,0x3f713f5c,0xbf5cbf71,0x3f2cbe16,0x3f183f80,0xbf67be79,0xbf78bedb,0xbd49bf4e,0x3f7d3f3e,0xbeac3f04,
0x3f5c3f71,0xbf2c3e16,0xbf18bf80,0x3f673e79,0x3f783edb,0x3d493f4e,0xbf7dbf3e,0x3eacbf04,0xbf043eac,0xbf3ebf7d,0x3f4e3d49,0x3edb3f78,0x3e793f67,0xbf80bf18,0x3e16bf2c,0x3f713f5c,
0xbdc9bf62,0x3f753f46,0xbf223e95,0xbef1bf7f,0x3f7f3ef1,0xbe953f22,0xbf46bf75,0x3f623dc9,0x3dc93f62,0xbf75bf46,0x3f22be95,0x3ef13f7f,0xbf7fbef1,0x3e95bf22,0x3f463f75,0xbf62bdc9,
0xbf7fbef1,0x3e95bf22,0x3f463f75,0xbf62bdc9,0xbdc9bf62,0x3f753f46,0xbf223e95,0xbef1bf7f,0x3f7f3ef1,0xbe953f22,0xbf46bf75,0x3f623dc9,0x3dc93f62,0xbf75bf46,0x3f22be95,0x3ef13f7f,
0xbf3e3e79,0xbe16bf71,0x3f673f4e,0xbf5c3d49,0x3f803f04,0xbf183edb,0xbeacbf7d,0x3f783f2c,0xbf2cbf78,0x3f7d3eac,0xbedb3f18,0xbf04bf80,0xbd493f5c,0xbf4ebf67,0x3f713e16,0xbe793f3e,
0x3f2c3f78,0xbf7dbeac,0x3edbbf18,0x3f043f80,0x3d49bf5c,0x3f4e3f67,0xbf71be16,0x3e79bf3e,0xbf3e3e79,0xbe16bf71,0x3f673f4e,0xbf5c3d49,0x3f803f04,0xbf183edb,0xbeacbf7d,0x3f783f2c,
0x3f7b3f0e,0xbf553e48,0x3e48bf55,0x3f0e3f7b,0xbf7bbf0e,0x3f55be48,0xbe483f55,0xbf0ebf7b,0x3f7b3f0e,0xbf553e48,0x3e48bf55,0x3f0e3f7b,0xbf7bbf0e,0x3f55be48,0xbe483f55,0xbf0ebf7b,
0xbe483f55,0xbf0ebf7b,0x3f7b3f0e,0xbf553e48,0x3e48bf55,0x3f0e3f7b,0xbf7bbf0e,0x3f55be48,0xbe483f55,0xbf0ebf7b,0x3f7b3f0e,0xbf553e48,0x3e48bf55,0x3f0e3f7b,0xbf7bbf0e,0x3f55be48,
0xbedbbf7d,0x3f5c3f3e,0xbf80be79,0x3f4ebeac,0x3f713f18,0xbf78bd49,0x3f2cbf04,0xbe163f67,0x3f67be16,0xbf043f2c,0xbd49bf78,0x3f183f71,0xbeac3f4e,0xbe79bf80,0x3f3e3f5c,0xbf7dbedb,
0x3f67be16,0xbf043f2c,0xbd49bf78,0x3f183f71,0xbeac3f4e,0xbe79bf80,0x3f3e3f5c,0xbf7dbedb,0x3edb3f7d,0xbf5cbf3e,0x3f803e79,0xbf4e3eac,0xbf71bf18,0x3f783d49,0xbf2c3f04,0x3e16bf67,
0xbf62bf22,0x3f7f3e95,0xbf753dc9,0x3f46bef1,0xbef13f46,0x3dc9bf75,0x3e953f7f,0xbf22bf62,0x3f623f22,0xbf7fbe95,0x3f75bdc9,0xbf463ef1,0x3ef1bf46,0xbdc93f75,0xbe95bf7f,0x3f223f62,
0x3ef1bf46,0xbdc93f75,0xbe95bf7f,0x3f223f62,0xbf62bf22,0x3f7f3e95,0xbf753dc9,0x3f46bef1,0xbef13f46,0x3dc9bf75,0x3e953f7f,0xbf22bf62,0x3f623f22,0xbf7fbe95,0x3f75bdc9,0xbf463ef1,
0xbe16bf80,0x3eac3f78,0xbf04bf67,0x3f2c3f4e,0x3f18bf3e,0xbedb3f5c,0x3e79bf71,0xbd493f7d,0x3f7dbd49,0xbf713e79,0x3f5cbedb,0xbf3e3f18,0x3f4e3f2c,0xbf67bf04,0x3f783eac,0xbf80be16,
0x3f7dbd49,0xbf713e79,0x3f5cbedb,0xbf3e3f18,0x3f4e3f2c,0xbf67bf04,0x3f783eac,0xbf80be16,0x3e163f80,0xbeacbf78,0x3f043f67,0xbf2cbf4e,0xbf183f3e,0x3edbbf5c,0xbe793f71,0x3d49bf7d,
0xbf353f35,0x3f35bf35,0xbf353f35,0x3f35bf35,0xbf353f35,0x3f35bf35,0xbf353f35,0x3f35bf35,0xbf353f35,0x3f35bf35,0xbf353f35,0x3f35bf35,0xbf353f35,0x3f35bf35,0xbf353f35,0x3f35bf35,
0x3f353f35,0xbf35bf35,0x3f353f35,0xbf35bf35,0x3f353f35,0xbf35bf35,0x3f353f35,0xbf35bf35,0x3f353f35,0xbf35bf35,0x3f353f35,0xbf35bf35,0x3f353f35,0xbf35bf35,0x3f353f35,0xbf35bf35,
0xbf7dbd49,0x3f713e79,0xbf5cbedb,0x3f3e3f18,0xbf4e3f2c,0x3f67bf04,0xbf783eac,0x3f80be16,0x3e16bf80,0xbeac3f78,0x3f04bf67,0xbf2c3f4e,0xbf18bf3e,0x3edb3f5c,0xbe79bf71,0x3d493f7d,
0xbe163f80,0x3eacbf78,0xbf043f67,0x3f2cbf4e,0x3f183f3e,0xbedbbf5c,0x3e793f71,0xbd49bf7d,0xbf7dbd49,0x3f713e79,0xbf5cbedb,0x3f3e3f18,0xbf4e3f2c,0x3f67bf04,0xbf783eac,0x3f80be16,
0x3f62bf22,0xbf7f3e95,0x3f753dc9,0xbf46bef1,0x3ef13f46,0xbdc9bf75,0xbe953f7f,0x3f22bf62,0xbf623f22,0x3f7fbe95,0xbf75bdc9,0x3f463ef1,0xbef1bf46,0x3dc93f75,0x3e95bf7f,0xbf223f62,
0xbef1bf46,0x3dc93f75,0x3e95bf7f,0xbf223f62,0x3f62bf22,0xbf7f3e95,0x3f753dc9,0xbf46bef1,0x3ef13f46,0xbdc9bf75,0xbe953f7f,0x3f22bf62,0xbf623f22,0x3f7fbe95,0xbf75bdc9,0x3f463ef1,
0xbf67be16,0x3f043f2c,0x3d49bf78,0xbf183f71,0x3eac3f4e,0x3e79bf80,0xbf3e3f5c,0x3f7dbedb,0x3edbbf7d,0xbf5c3f3e,0x3f80be79,0xbf4ebeac,0xbf713f18,0x3f78bd49,0xbf2cbf04,0x3e163f67,
0xbedb3f7d,0x3f5cbf3e,0xbf803e79,0x3f4e3eac,0x3f71bf18,0xbf783d49,0x3f2c3f04,0xbe16bf67,0xbf67be16,0x3f043f2c,0x3d49bf78,0xbf183f71,0x3eac3f4e,0x3e79bf80,0xbf3e3f5c,0x3f7dbedb,
0x3e483f55,0x3f0ebf7b,0xbf7b3f0e,0x3f553e48,0xbe48bf55,0xbf0e3f7b,0x3f7bbf0e,0xbf55be48,0x3e483f55,0x3f0ebf7b,0xbf7b3f0e,0x3f553e48,0xbe48bf55,0xbf0e3f7b,0x3f7bbf0e,0xbf55be48,
0xbf7b3f0e,0x3f553e48,0xbe48bf55,0xbf0e3f7b,0x3f7bbf0e,0xbf55be48,0x3e483f55,0x3f0ebf7b,0xbf7b3f0e,0x3f553e48,0xbe48bf55,0xbf0e3f7b,0x3f7bbf0e,0xbf55be48,0x3e483f55,0x3f0ebf7b,
0x3f2cbf78,0xbf7d3eac,0x3edb3f18,0x3f04bf80,0x3d493f5c,0x3f4ebf67,0xbf713e16,0x3e793f3e,0x3f3e3e79,0x3e16bf71,0xbf673f4e,0x3f5c3d49,0xbf803f04,0x3f183edb,0x3eacbf7d,0xbf783f2c,
0x3f3e3e79,0x3e16bf71,0xbf673f4e,0x3f5c3d49,0xbf803f04,0x3f183edb,0x3eacbf7d,0xbf783f2c,0xbf2c3f78,0x3f7dbeac,0xbedbbf18,0xbf043f80,0xbd49bf5c,0xbf4e3f67,0x3f71be16,0xbe79bf3e,
0x3dc9bf62,0xbf753f46,0x3f223e95,0x3ef1bf7f,0xbf7f3ef1,0x3e953f22,0x3f46bf75,0xbf623dc9,0xbdc93f62,0x3f75bf46,0xbf22be95,0xbef13f7f,0x3f7fbef1,0xbe95bf22,0xbf463f75,0x3f62bdc9,
0x3f7fbef1,0xbe95bf22,0xbf463f75,0x3f62bdc9,0x3dc9bf62,0xbf753f46,0x3f223e95,0x3ef1bf7f,0xbf7f3ef1,0x3e953f22,0x3f46bf75,0xbf623dc9,0xbdc93f62,0x3f75bf46,0xbf22be95,0xbef13f7f,
0x3f5cbf71,0xbf2cbe16,0xbf183f80,0x3f67be79,0x3f78bedb,0x3d49bf4e,0xbf7d3f3e,0x3eac3f04,0x3f043eac,0x3f3ebf7d,0xbf4e3d49,0xbedb3f78,0xbe793f67,0x3f80bf18,0xbe16bf2c,0xbf713f5c,
0x3f043eac,0x3f3ebf7d,0xbf4e3d49,0xbedb3f78,0xbe793f67,0x3f80bf18,0xbe16bf2c,0xbf713f5c,0xbf5c3f71,0x3f2c3e16,0x3f18bf80,0xbf673e79,0xbf783edb,0xbd493f4e,0x3f7dbf3e,0xbeacbf04,
0xbf6d3ec4,0xbec43f6d,0x3f6dbec4,0x3ec4bf6d,0xbf6d3ec4,0xbec43f6d,0x3f6dbec4,0x3ec4bf6d,0xbf6d3ec4,0xbec43f6d,0x3f6dbec4,0x3ec4bf6d,0xbf6d3ec4,0xbec43f6d,0x3f6dbec4,0x3ec4bf6d,
0xbec43f6d,0x3f6dbec4,0x3ec4bf6d,0xbf6d3ec4,0xbec43f6d,0x3f6dbec4,0x3ec4bf6d,0xbf6d3ec4,0xbec43f6d,0x3f6dbec4,0x3ec4bf6d,0xbf6d3ec4,0xbec43f6d,0x3f6dbec4,0x3ec4bf6d,0xbf6d3ec4,
0xbe79bedb,0xbf803f4e,0xbe163f3e,0x3f71bf04,0xbf5c3eac,0xbf2c3f7d,0x3f183d49,0x3f67bf78,0x3f78bf67,0xbd49bf18,0xbf7d3f2c,0xbeac3f5c,0x3f04bf71,0xbf3e3e16,0xbf4e3f80,0x3edb3e79,
0xbf783f67,0x3d493f18,0x3f7dbf2c,0x3eacbf5c,0xbf043f71,0x3f3ebe16,0x3f4ebf80,0xbedbbe79,0xbe79bedb,0xbf803f4e,0xbe163f3e,0x3f71bf04,0xbf5c3eac,0xbf2c3f7d,0x3f183d49,0x3f67bf78,
0x3f46be95,0x3f62bf7f,0xbdc9bef1,0xbf753f22,0xbf223f75,0x3ef13dc9,0x3f7fbf62,0x3e95bf46,0xbf463e95,0xbf623f7f,0x3dc93ef1,0x3f75bf22,0x3f22bf75,0xbef1bdc9,0xbf7f3f62,0xbe953f46,
0x3f22bf75,0xbef1bdc9,0xbf7f3f62,0xbe953f46,0x3f46be95,0x3f62bf7f,0xbdc9bef1,0xbf753f22,0xbf223f75,0x3ef13dc9,0x3f7fbf62,0x3e95bf46,0xbf463e95,0xbf623f7f,0x3dc93ef1,0x3f75bf22,
0x3d49bf04,0xbf4e3edb,0xbf713f7d,0xbe793f2c,0xbf3e3f78,0x3e163eac,0x3f67bf18,0x3f5cbf80,0x3f80bf5c,0x3f18bf67,0xbeacbe16,0xbf783f3e,0xbf2c3e79,0xbf7d3f71,0xbedb3f4e,0x3f04bd49,
0xbf803f5c,0xbf183f67,0x3eac3e16,0x3f78bf3e,0x3f2cbe79,0x3f7dbf71,0x3edbbf4e,0xbf043d49,0x3d49bf04,0xbf4e3edb,0xbf713f7d,0xbe793f2c,0xbf3e3f78,0x3e163eac,0x3f67bf18,0x3f5cbf80,
0xbf553f7b,0xbe483f0e,0x3f0ebe48,0x3f7bbf55,0x3f55bf7b,0x3e48bf0e,0xbf0e3e48,0xbf7b3f55,0xbf553f7b,0xbe483f0e,0x3f0ebe48,0x3f7bbf55,0x3f55bf7b,0x3e48bf0e,0xbf0e3e48,0xbf7b3f55,
0xbf0e3e48,0xbf7b3f55,0xbf553f7b,0xbe483f0e,0x3f0ebe48,0x3f7bbf55,0x3f55bf7b,0x3e48bf0e,0xbf0e3e48,0xbf7b3f55,0xbf553f7b,0xbe483f0e,0x3f0ebe48,0x3f7bbf55,0x3f55bf7b,0x3e48bf0e,
0x3f71bf4e,0x3f78bf80,0x3f2cbf5c,0x3e16bedb,0xbf673f7d,0xbf043f3e,0x3d493e79,0x3f18beac,0xbeac3f18,0x3e793d49,0x3f3ebf04,0x3f7dbf67,0xbedb3e16,0xbf5c3f2c,0xbf803f78,0xbf4e3f71,
0xbeac3f18,0x3e793d49,0x3f3ebf04,0x3f7dbf67,0xbedb3e16,0xbf5c3f2c,0xbf803f78,0xbf4e3f71,0xbf713f4e,0xbf783f80,0xbf2c3f5c,0xbe163edb,0x3f67bf7d,0x3f04bf3e,0xbd49be79,0xbf183eac,
0x3f75bf7f,0x3f46bf62,0x3ef1bf22,0x3dc9be95,0xbe953dc9,0xbf223ef1,0xbf623f46,0xbf7f3f75,0xbf753f7f,0xbf463f62,0xbef13f22,0xbdc93e95,0x3e95bdc9,0x3f22bef1,0x3f62bf46,0x3f7fbf75,
0x3e95bdc9,0x3f22bef1,0x3f62bf46,0x3f7fbf75,0x3f75bf7f,0x3f46bf62,0x3ef1bf22,0x3dc9be95,0xbe953dc9,0xbf223ef1,0xbf623f46,0xbf7f3f75,0xbf753f7f,0xbf463f62,0xbef13f22,0xbdc93e95,
0x3f4ebf3e,0x3f67bf5c,0x3f78bf71,0x3f80bf7d,0x3e16bd49,0x3eacbe79,0x3f04bedb,0x3f2cbf18,0xbf183f2c,0xbedb3f04,0xbe793eac,0xbd493e16,0xbf7d3f80,0xbf713f78,0xbf5c3f67,0xbf3e3f4e,
0xbf183f2c,0xbedb3f04,0xbe793eac,0xbd493e16,0xbf7d3f80,0xbf713f78,0xbf5c3f67,0xbf3e3f4e,0xbf4e3f3e,0xbf673f5c,0xbf783f71,0xbf803f7d,0xbe163d49,0xbeac3e79,0xbf043edb,0xbf2c3f18,
0xa554248d,0xa5f725b0,0xa731261f,0xa742a68d,0xa754a654,0xa765a60d,0xa777a58e,0xa784a137,0xa78d258d,0xa796260d,0xa79f280d,0x2731268d,0xa7b12816,0x270d26d4,0xa7c2281f,0x26d4270d,
0xbf803f80,0xbf803f80,0xbf803f80,0xbf803f80,0xbf803f80,0xbf803f80,0xbf803f80,0xbf803f80,0xbf803f80,0xbf803f80,0xbf803f80,0xbf803f80,0xbf803f80,0xbf803f80,0xbf803f80,0xbf803f80,
0x3f4ebf3e,0x3f67bf5c,0x3f78bf71,0x3f80bf7d,0x3e16bd49,0x3eacbe79,0x3f04bedb,0x3f2cbf18,0x3f18bf2c,0x3edbbf04,0x3e79beac,0x3d49be16,0x3f7dbf80,0x3f71bf78,0x3f5cbf67,0x3f3ebf4e,
0xbf183f2c,0xbedb3f04,0xbe793eac,0xbd493e16,0xbf7d3f80,0xbf713f78,0xbf5c3f67,0xbf3e3f4e,0x3f4ebf3e,0x3f67bf5c,0x3f78bf71,0x3f80bf7d,0x3e16bd49,0x3eacbe79,0x3f04bedb,0x3f2cbf18,
0xbe953dc9,0xbf223ef1,0xbf623f46,0xbf7f3f75,0xbf753f7f,0xbf463f62,0xbef13f22,0xbdc93e95,0x3e95bdc9,0x3f22bef1,0x3f62bf46,0x3f7fbf75,0x3f75bf7f,0x3f46bf62,0x3ef1bf22,0x3dc9be95,
0x3f75bf7f,0x3f46bf62,0x3ef1bf22,0x3dc9be95,0xbe953dc9,0xbf223ef1,0xbf623f46,0xbf7f3f75,0xbf753f7f,0xbf463f62,0xbef13f22,0xbdc93e95,0x3e95bdc9,0x3f22bef1,0x3f62bf46,0x3f7fbf75,
0x3f71bf4e,0x3f78bf80,0x3f2cbf5c,0x3e16bedb,0xbf673f7d,0xbf043f3e,0x3d493e79,0x3f18beac,0x3eacbf18,0xbe79bd49,0xbf3e3f04,0xbf7d3f67,0x3edbbe16,0x3f5cbf2c,0x3f80bf78,0x3f4ebf71,
0xbeac3f18,0x3e793d49,0x3f3ebf04,0x3f7dbf67,0xbedb3e16,0xbf5c3f2c,0xbf803f78,0xbf4e3f71,0x3f71bf4e,0x3f78bf80,0x3f2cbf5c,0x3e16bedb,0xbf673f7d,0xbf043f3e,0x3d493e79,0x3f18beac,
0xbf553f7b,0xbe483f0e,0x3f0ebe48,0x3f7bbf55,0x3f55bf7b,0x3e48bf0e,0xbf0e3e48,0xbf7b3f55,0xbf553f7b,0xbe483f0e,0x3f0ebe48,0x3f7bbf55,0x3f55bf7b,0x3e48bf0e,0xbf0e3e48,0xbf7b3f55,
0x3f0ebe48,0x3f7bbf55,0x3f55bf7b,0x3e48bf0e,0xbf0e3e48,0xbf7b3f55,0xbf553f7b,0xbe483f0e,0x3f0ebe48,0x3f7bbf55,0x3f55bf7b,0x3e48bf0e,0xbf0e3e48,0xbf7b3f55,0xbf553f7b,0xbe483f0e,
0x3d49bf04,0xbf4e3edb,0xbf713f7d,0xbe793f2c,0xbf3e3f78,0x3e163eac,0x3f67bf18,0x3f5cbf80,0xbf803f5c,0xbf183f67,0x3eac3e16,0x3f78bf3e,0x3f2cbe79,0x3f7dbf71,0x3edbbf4e,0xbf043d49,
0xbf803f5c,0xbf183f67,0x3eac3e16,0x3f78bf3e,0x3f2cbe79,0x3f7dbf71,0x3edbbf4e,0xbf043d49,0xbd493f04,0x3f4ebedb,0x3f71bf7d,0x3e79bf2c,0x3f3ebf78,0xbe16beac,0xbf673f18,0xbf5c3f80,
0x3f22bf75,0xbef1bdc9,0xbf7f3f62,0xbe953f46,0x3f46be95,0x3f62bf7f,0xbdc9bef1,0xbf753f22,0xbf223f75,0x3ef13dc9,0x3f7fbf62,0x3e95bf46,0xbf463e95,0xbf623f7f,0x3dc93ef1,0x3f75bf22,
0xbf463e95,0xbf623f7f,0x3dc93ef1,0x3f75bf22,0x3f22bf75,0xbef1bdc9,0xbf7f3f62,0xbe953f46,0x3f46be95,0x3f62bf7f,0xbdc9bef1,0xbf753f22,0xbf223f75,0x3ef13dc9,0x3f7fbf62,0x3e95bf46,
0xbe79bedb,0xbf803f4e,0xbe163f3e,0x3f71bf04,0xbf5c3eac,0xbf2c3f7d,0x3f183d49,0x3f67bf78,0xbf783f67,0x3d493f18,0x3f7dbf2c,0x3eacbf5c,0xbf043f71,0x3f3ebe16,0x3f4ebf80,0xbedbbe79,
0xbf783f67,0x3d493f18,0x3f7dbf2c,0x3eacbf5c,0xbf043f71,0x3f3ebe16,0x3f4ebf80,0xbedbbe79,0x3e793edb,0x3f80bf4e,0x3e16bf3e,0xbf713f04,0x3f5cbeac,0x3f2cbf7d,0xbf18bd49,0xbf673f78,
0x3f6dbec4,0x3ec4bf6d,0xbf6d3ec4,0xbec43f6d,0x3f6dbec4,0x3ec4bf6d,0xbf6d3ec4,0xbec43f6d,0x3f6dbec4,0x3ec4bf6d,0xbf6d3ec4,0xbec43f6d,0x3f6dbec4,0x3ec4bf6d,0xbf6d3ec4,0xbec43f6d,
0xbec43f6d,0x3f6dbec4,0x3ec4bf6d,0xbf6d3ec4,0xbec43f6d,0x3f6dbec4,0x3ec4bf6d,0xbf6d3ec4,0xbec43f6d,0x3f6dbec4,0x3ec4bf6d,0xbf6d3ec4,0xbec43f6d,0x3f6dbec4,0x3ec4bf6d,0xbf6d3ec4,
0x3f5cbf71,0xbf2cbe16,0xbf183f80,0x3f67be79,0x3f78bedb,0x3d49bf4e,0xbf7d3f3e,0x3eac3f04,0xbf04beac,0xbf3e3f7d,0x3f4ebd49,0x3edbbf78,0x3e79bf67,0xbf803f18,0x3e163f2c,0x3f71bf5c,
0x3f043eac,0x3f3ebf7d,0xbf4e3d49,0xbedb3f78,0xbe793f67,0x3f80bf18,0xbe16bf2c,0xbf713f5c,0x3f5cbf71,0xbf2cbe16,0xbf183f80,0x3f67be79,0x3f78bedb,0x3d49bf4e,0xbf7d3f3e,0x3eac3f04,
0xbf7f3ef1,0x3e953f22,0x3f46bf75,0xbf623dc9,0xbdc93f62,0x3f75bf46,0xbf22be95,0xbef13f7f,0x3f7fbef1,0xbe95bf22,0xbf463f75,0x3f62bdc9,0x3dc9bf62,0xbf753f46,0x3f223e95,0x3ef1bf7f,
0x3dc9bf62,0xbf753f46,0x3f223e95,0x3ef1bf7f,0xbf7f3ef1,0x3e953f22,0x3f46bf75,0xbf623dc9,0xbdc93f62,0x3f75bf46,0xbf22be95,0xbef13f7f,0x3f7fbef1,0xbe95bf22,0xbf463f75,0x3f62bdc9,
0x3f2cbf78,0xbf7d3eac,0x3edb3f18,0x3f04bf80,0x3d493f5c,0x3f4ebf67,0xbf713e16,0x3e793f3e,0xbf3ebe79,0xbe163f71,0x3f67bf4e,0xbf5cbd49,0x3f80bf04,0xbf18bedb,0xbeac3f7d,0x3f78bf2c,
0x3f3e3e79,0x3e16bf71,0xbf673f4e,0x3f5c3d49,0xbf803f04,0x3f183edb,0x3eacbf7d,0xbf783f2c,0x3f2cbf78,0xbf7d3eac,0x3edb3f18,0x3f04bf80,0x3d493f5c,0x3f4ebf67,0xbf713e16,0x3e793f3e,
0x3e483f55,0x3f0ebf7b,0xbf7b3f0e,0x3f553e48,0xbe48bf55,0xbf0e3f7b,0x3f7bbf0e,0xbf55be48,0x3e483f55,0x3f0ebf7b,0xbf7b3f0e,0x3f553e48,0xbe48bf55,0xbf0e3f7b,0x3f7bbf0e,0xbf55be48,
0x3f7bbf0e,0xbf55be48,0x3e483f55,0x3f0ebf7b,0xbf7b3f0e,0x3f553e48,0xbe48bf55,0xbf0e3f7b,0x3f7bbf0e,0xbf55be48,0x3e483f55,0x3f0ebf7b,0xbf7b3f0e,0x3f553e48,0xbe48bf55,0xbf0e3f7b,
0xbf67be16,0x3f043f2c,0x3d49bf78,0xbf183f71,0x3eac3f4e,0x3e79bf80,0xbf3e3f5c,0x3f7dbedb,0xbedb3f7d,0x3f5cbf3e,0xbf803e79,0x3f4e3eac,0x3f71bf18,0xbf783d49,0x3f2c3f04,0xbe16bf67,
0xbedb3f7d,0x3f5cbf3e,0xbf803e79,0x3f4e3eac,0x3f71bf18,0xbf783d49,0x3f2c3f04,0xbe16bf67,0x3f673e16,0xbf04bf2c,0xbd493f78,0x3f18bf71,0xbeacbf4e,0xbe793f80,0x3f3ebf5c,0xbf7d3edb,
0xbef1bf46,0x3dc93f75,0x3e95bf7f,0xbf223f62,0x3f62bf22,0xbf7f3e95,0x3f753dc9,0xbf46bef1,0x3ef13f46,0xbdc9bf75,0xbe953f7f,0x3f22bf62,0xbf623f22,0x3f7fbe95,0xbf75bdc9,0x3f463ef1,
0xbf623f22,0x3f7fbe95,0xbf75bdc9,0x3f463ef1,0xbef1bf46,0x3dc93f75,0x3e95bf7f,0xbf223f62,0x3f62bf22,0xbf7f3e95,0x3f753dc9,0xbf46bef1,0x3ef13f46,0xbdc9bf75,0xbe953f7f,0x3f22bf62,
0xbf7dbd49,0x3f713e79,0xbf5cbedb,0x3f3e3f18,0xbf4e3f2c,0x3f67bf04,0xbf783eac,0x3f80be16,0xbe163f80,0x3eacbf78,0xbf043f67,0x3f2cbf4e,0x3f183f3e,0xbedbbf5c,0x3e793f71,0xbd49bf7d,
0xbe163f80,0x3eacbf78,0xbf043f67,0x3f2cbf4e,0x3f183f3e,0xbedbbf5c,0x3e793f71,0xbd49bf7d,0x3f7d3d49,0xbf71be79,0x3f5c3edb,0xbf3ebf18,0x3f4ebf2c,0xbf673f04,0x3f78beac,0xbf803e16,
0x3f35bf35,0xbf353f35,0x3f35bf35,0xbf353f35,0x3f35bf35,0xbf353f35,0x3f35bf35,0xbf353f35,0x3f35bf35,0xbf353f35,0x3f35bf35,0xbf353f35,0x3f35bf35,0xbf353f35,0x3f35bf35,0xbf353f35,
0x3f353f35,0xbf35bf35,0x3f353f35,0xbf35bf35,0x3f353f35,0xbf35bf35,0x3f353f35,0xbf35bf35,0x3f353f35,0xbf35bf35,0x3f353f35,0xbf35bf35,0x3f353f35,0xbf35bf35,0x3f353f35,0xbf35bf35,
0xbe16bf80,0x3eac3f78,0xbf04bf67,0x3f2c3f4e,0x3f18bf3e,0xbedb3f5c,0x3e79bf71,0xbd493f7d,0xbf7d3d49,0x3f71be79,0xbf5c3edb,0x3f3ebf18,0xbf4ebf2c,0x3f673f04,0xbf78beac,0x3f803e16,
0x3f7dbd49,0xbf713e79,0x3f5cbedb,0xbf3e3f18,0x3f4e3f2c,0xbf67bf04,0x3f783eac,0xbf80be16,0xbe16bf80,0x3eac3f78,0xbf04bf67,0x3f2c3f4e,0x3f18bf3e,0xbedb3f5c,0x3e79bf71,0xbd493f7d,
0xbef13f46,0x3dc9bf75,0x3e953f7f,0xbf22bf62,0x3f623f22,0xbf7fbe95,0x3f75bdc9,0xbf463ef1,0x3ef1bf46,0xbdc93f75,0xbe95bf7f,0x3f223f62,0xbf62bf22,0x3f7f3e95,0xbf753dc9,0x3f46bef1,
0xbf62bf22,0x3f7f3e95,0xbf753dc9,0x3f46bef1,0xbef13f46,0x3dc9bf75,0x3e953f7f,0xbf22bf62,0x3f623f22,0xbf7fbe95,0x3f75bdc9,0xbf463ef1,0x3ef1bf46,0xbdc93f75,0xbe95bf7f,0x3f223f62,
0xbedbbf7d,0x3f5c3f3e,0xbf80be79,0x3f4ebeac,0x3f713f18,0xbf78bd49,0x3f2cbf04,0xbe163f67,0xbf673e16,0x3f04bf2c,0x3d493f78,0xbf18bf71,0x3eacbf4e,0x3e793f80,0xbf3ebf5c,0x3f7d3edb,
0x3f67be16,0xbf043f2c,0xbd49bf78,0x3f183f71,0xbeac3f4e,0xbe79bf80,0x3f3e3f5c,0xbf7dbedb,0xbedbbf7d,0x3f5c3f3e,0xbf80be79,0x3f4ebeac,0x3f713f18,0xbf78bd49,0x3f2cbf04,0xbe163f67,
0x3f7b3f0e,0xbf553e48,0x3e48bf55,0x3f0e3f7b,0xbf7bbf0e,0x3f55be48,0xbe483f55,0xbf0ebf7b,0x3f7b3f0e,0xbf553e48,0x3e48bf55,0x3f0e3f7b,0xbf7bbf0e,0x3f55be48,0xbe483f55,0xbf0ebf7b,
0x3e48bf55,0x3f0e3f7b,0xbf7bbf0e,0x3f55be48,0xbe483f55,0xbf0ebf7b,0x3f7b3f0e,0xbf553e48,0x3e48bf55,0x3f0e3f7b,0xbf7bbf0e,0x3f55be48,0xbe483f55,0xbf0ebf7b,0x3f7b3f0e,0xbf553e48,
0xbf3e3e79,0xbe16bf71,0x3f673f4e,0xbf5c3d49,0x3f803f04,0xbf183edb,0xbeacbf7d,0x3f783f2c,0x3f2c3f78,0xbf7dbeac,0x3edbbf18,0x3f043f80,0x3d49bf5c,0x3f4e3f67,0xbf71be16,0x3e79bf3e,
0x3f2c3f78,0xbf7dbeac,0x3edbbf18,0x3f043f80,0x3d49bf5c,0x3f4e3f67,0xbf71be16,0x3e79bf3e,0x3f3ebe79,0x3e163f71,0xbf67bf4e,0x3f5cbd49,0xbf80bf04,0x3f18bedb,0x3eac3f7d,0xbf78bf2c,
0xbf7fbef1,0x3e95bf22,0x3f463f75,0xbf62bdc9,0xbdc9bf62,0x3f753f46,0xbf223e95,0xbef1bf7f,0x3f7f3ef1,0xbe953f22,0xbf46bf75,0x3f623dc9,0x3dc93f62,0xbf75bf46,0x3f22be95,0x3ef13f7f,
0x3dc93f62,0xbf75bf46,0x3f22be95,0x3ef13f7f,0xbf7fbef1,0x3e95bf22,0x3f463f75,0xbf62bdc9,0xbdc9bf62,0x3f753f46,0xbf223e95,0xbef1bf7f,0x3f7f3ef1,0xbe953f22,0xbf46bf75,0x3f623dc9,
0xbf043eac,0xbf3ebf7d,0x3f4e3d49,0x3edb3f78,0x3e793f67,0xbf80bf18,0x3e16bf2c,0x3f713f5c,0x3f5c3f71,0xbf2c3e16,0xbf18bf80,0x3f673e79,0x3f783edb,0x3d493f4e,0xbf7dbf3e,0x3eacbf04,
0x3f5c3f71,0xbf2c3e16,0xbf18bf80,0x3f673e79,0x3f783edb,0x3d493f4e,0xbf7dbf3e,0x3eacbf04,0x3f04beac,0x3f3e3f7d,0xbf4ebd49,0xbedbbf78,0xbe79bf67,0x3f803f18,0xbe163f2c,0xbf71bf5c,
0xbec4bf6d,0x3f6d3ec4,0x3ec43f6d,0xbf6dbec4,0xbec4bf6d,0x3f6d3ec4,0x3ec43f6d,0xbf6dbec4,0xbec4bf6d,0x3f6d3ec4,0x3ec43f6d,0xbf6dbec4,0xbec4bf6d,0x3f6d3ec4,0x3ec43f6d,0xbf6dbec4,
0x3f6d3ec4,0x3ec43f6d,0xbf6dbec4,0xbec4bf6d,0x3f6d3ec4,0x3ec43f6d,0xbf6dbec4,0xbec4bf6d,0x3f6d3ec4,0x3ec43f6d,0xbf6dbec4,0xbec4bf6d,0x3f6d3ec4,0x3ec43f6d,0xbf6dbec4,0xbec4bf6d,
0xbf78bf67,0x3d49bf18,0x3f7d3f2c,0x3eac3f5c,0xbf04bf71,0x3f3e3e16,0x3f4e3f80,0xbedb3e79,0xbe793edb,0xbf80bf4e,0xbe16bf3e,0x3f713f04,0xbf5cbeac,0xbf2cbf7d,0x3f18bd49,0x3f673f78,
0x3e79bedb,0x3f803f4e,0x3e163f3e,0xbf71bf04,0x3f5c3eac,0x3f2c3f7d,0xbf183d49,0xbf67bf78,0xbf78bf67,0x3d49bf18,0x3f7d3f2c,0x3eac3f5c,0xbf04bf71,0x3f3e3e16,0x3f4e3f80,0xbedb3e79,
0x3f223f75,0xbef13dc9,0xbf7fbf62,0xbe95bf46,0x3f463e95,0x3f623f7f,0xbdc93ef1,0xbf75bf22,0xbf22bf75,0x3ef1bdc9,0x3f7f3f62,0x3e953f46,0xbf46be95,0xbf62bf7f,0x3dc9bef1,0x3f753f22,
0xbf46be95,0xbf62bf7f,0x3dc9bef1,0x3f753f22,0x3f223f75,0xbef13dc9,0xbf7fbf62,0xbe95bf46,0x3f463e95,0x3f623f7f,0xbdc93ef1,0xbf75bf22,0xbf22bf75,0x3ef1bdc9,0x3f7f3f62,0x3e953f46,
0xbf80bf5c,0xbf18bf67,0x3eacbe16,0x3f783f3e,0x3f2c3e79,0x3f7d3f71,0x3edb3f4e,0xbf04bd49,0x3d493f04,0xbf4ebedb,0xbf71bf7d,0xbe79bf2c,0xbf3ebf78,0x3e16beac,0x3f673f18,0x3f5c3f80,
0xbd49bf04,0x3f4e3edb,0x3f713f7d,0x3e793f2c,0x3f3e3f78,0xbe163eac,0xbf67bf18,0xbf5cbf80,0xbf80bf5c,0xbf18bf67,0x3eacbe16,0x3f783f3e,0x3f2c3e79,0x3f7d3f71,0x3edb3f4e,0xbf04bd49,
0x3f0e3e48,0x3f7b3f55,0x3f553f7b,0x3e483f0e,0xbf0ebe48,0xbf7bbf55,0xbf55bf7b,0xbe48bf0e,0x3f0e3e48,0x3f7b3f55,0x3f553f7b,0x3e483f0e,0xbf0ebe48,0xbf7bbf55,0xbf55bf7b,0xbe48bf0e,
0xbf55bf7b,0xbe48bf0e,0x3f0e3e48,0x3f7b3f55,0x3f553f7b,0x3e483f0e,0xbf0ebe48,0xbf7bbf55,0xbf55bf7b,0xbe48bf0e,0x3f0e3e48,0x3f7b3f55,0x3f553f7b,0x3e483f0e,0xbf0ebe48,0xbf7bbf55,
0x3eac3f18,0xbe793d49,0xbf3ebf04,0xbf7dbf67,0x3edb3e16,0x3f5c3f2c,0x3f803f78,0x3f4e3f71,0x3f713f4e,0x3f783f80,0x3f2c3f5c,0x3e163edb,0xbf67bf7d,0xbf04bf3e,0x3d49be79,0x3f183eac,
0x3f713f4e,0x3f783f80,0x3f2c3f5c,0x3e163edb,0xbf67bf7d,0xbf04bf3e,0x3d49be79,0x3f183eac,0xbeacbf18,0x3e79bd49,0x3f3e3f04,0x3f7d3f67,0xbedbbe16,0xbf5cbf2c,0xbf80bf78,0xbf4ebf71,
0xbe95bdc9,0xbf22bef1,0xbf62bf46,0xbf7fbf75,0xbf75bf7f,0xbf46bf62,0xbef1bf22,0xbdc9be95,0x3e953dc9,0x3f223ef1,0x3f623f46,0x3f7f3f75,0x3f753f7f,0x3f463f62,0x3ef13f22,0x3dc93e95,
0x3f753f7f,0x3f463f62,0x3ef13f22,0x3dc93e95,0xbe95bdc9,0xbf22bef1,0xbf62bf46,0xbf7fbf75,0xbf75bf7f,0xbf46bf62,0xbef1bf22,0xbdc9be95,0x3e953dc9,0x3f223ef1,0x3f623f46,0x3f7f3f75,
0x3f183f2c,0x3edb3f04,0x3e793eac,0x3d493e16,0x3f7d3f80,0x3f713f78,0x3f5c3f67,0x3f3e3f4e,0x3f4e3f3e,0x3f673f5c,0x3f783f71,0x3f803f7d,0x3e163d49,0x3eac3e79,0x3f043edb,0x3f2c3f18,
0x3f4e3f3e,0x3f673f5c,0x3f783f71,0x3f803f7d,0x3e163d49,0x3eac3e79,0x3f043edb,0x3f2c3f18,0xbf18bf2c,0xbedbbf04,0xbe79beac,0xbd49be16,0xbf7dbf80,0xbf71bf78,0xbf5cbf67,0xbf3ebf4e,
0x38fb37c9,0x39a13960,0x39fc39cf,0x3a273a13,0xba7eba80,0xba73ba7a,0xba5fba6a,0xba42ba51,0x3a4a3a39,0x3a653a58,0x3a773a6f,0x3a7f3a7c,0xba1dba31,0xb9e6ba09,0xb989b9b8,0xb897b92f,
0x3a7e3a80,0x3a733a7a,0x3a5f3a6a,0x3a423a51,0x38fb37c9,0x39a13960,0x39fc39cf,0x3a273a13,0x3a1d3a31,0x39e63a09,0x398939b8,0x3897392f,0x3a4a3a39,0x3a653a58,0x3a773a6f,0x3a7f3a7c,
0xba6fba7f,0xba13ba4a,0xb7c9b9a1,0x3a093989,0x39b83897,0x3a513a1d,0x3a803a73,0x3a583a77,0x3a6a3a42,0x3a7c3a7e,0x3a393a65,0x396039fc,0x39cf3a27,0xb92f38fb,0xba31b9e6,0xba7aba5f,
0xb9b8b897,0xba51ba1d,0xba80ba73,0xba58ba77,0xba6fba7f,0xba13ba4a,0xb7c9b9a1,0x3a093989,0xb9cfba27,0x392fb8fb,0x3a3139e6,0x3a7a3a5f,0x3a6a3a42,0x3a7c3a7e,0x3a393a65,0x396039fc,
0xba7cba4a,0xba31ba73,0x3960b989,0x3a6f3a27,0x392f3a1d,0xba39b9a1,0xba7aba77,0xb9b8ba42,0x3a1338fb,0x3a803a65,0x3a093a5f,0xb9cf3897,0xba51ba7e,0x37c9b9e6,0x3a5839fc,0x3a6a3a7f,
0xb92fba1d,0x3a3939a1,0x3a7a3a77,0x39b83a42,0xba7cba4a,0xba31ba73,0x3960b989,0x3a6f3a27,0x3a513a7e,0xb7c939e6,0xba58b9fc,0xba6aba7f,0x3a1338fb,0x3a803a65,0x3a093a5f,0xb9cf3897,
0xba7fba51,0xb8fbba39,0x3a733a09,0x39fc3a6f,0x3897ba13,0x3a7e3a31,0x39a13a58,0xba5fb9b8,0xba27ba7c,0x3a1db7c9,0x3a653a7a,0xb98939cf,0x3a42392f,0x3a4a3a80,0xb9e63960,0xba77ba6a,
0xb8973a13,0xba7eba31,0xb9a1ba58,0x3a5f39b8,0xba7fba51,0xb8fbba39,0x3a733a09,0x39fc3a6f,0xba42b92f,0xba4aba80,0x39e6b960,0x3a773a6a,0xba27ba7c,0x3a1db7c9,0x3a653a7a,0xb98939cf,
0x39e63a7a,0xba77b9cf,0xb897ba51,0x3a7e3a39,0x3a653960,0x39893a6a,0xba7fba13,0x38fbba31,0xb9a13a09,0xba5fba6f,0x3a27b92f,0x3a1d3a80,0x3a733a58,0xb9fc39b8,0xba42ba7c,0x3a4a37c9,
0x3a653960,0x39893a6a,0xba7fba13,0x38fbba31,0xb9e6ba7a,0x3a7739cf,0x38973a51,0xba7eba39,0x3a733a58,0xb9fc39b8,0xba42ba7c,0x3a4a37c9,0x39a1ba09,0x3a5f3a6f,0xba27392f,0xba1dba80,
0xba7ab989,0x39b8ba27,0x3a133a7e,0xba80b9e6,0xb960ba77,0x3a6f3a42,0xba5138fb,0xb7c9ba65,0x3a09b9fc,0x39cf3a7f,0xba7cba1d,0x3a31b9a1,0x3a583a5f,0xba6ab897,0x392fba4a,0x3a393a73,
0xb960ba77,0x3a6f3a42,0xba5138fb,0xb7c9ba65,0x3a7a3989,0xb9b83a27,0xba13ba7e,0x3a8039e6,0x3a583a5f,0xba6ab897,0x392fba4a,0x3a393a73,0xba0939fc,0xb9cfba7f,0x3a7c3a1d,0xba3139a1,
0x3a39b9e6,0xb9603a5f,0xb9b8ba7f,0x3a513a4a,0xba31ba65,0x3a7a39fc,0xba6f3897,0x3a13ba1d,0xb7c93a73,0xba09ba77,0x3a6a3a27,0xba7cb8fb,0x3a8039a1,0xba583989,0x39cfba42,0x392f3a7e,
0xba31ba65,0x3a7a39fc,0xba6f3897,0x3a13ba1d,0xba3939e6,0x3960ba5f,0x39b83a7f,0xba51ba4a,0x3a8039a1,0xba583989,0x39cfba42,0x392f3a7e,0x37c9ba73,0x3a093a77,0xba6aba27,0x3a7c38fb,
0xba5f39cf,0x3a42ba13,0xba1d3a39,0x39e6ba58,0xb9fcba6a,0x3a273a51,0xba4aba31,0x3a653a09,0xba77b9b8,0x3a7f392f,0xba7e37c9,0x3a73b960,0x3989ba6f,0xb8973a7c,0xb8fbba80,0x39a13a7a,
0xb9fcba6a,0x3a273a51,0xba4aba31,0x3a653a09,0x3a5fb9cf,0xba423a13,0x3a1dba39,0xb9e63a58,0x3989ba6f,0xb8973a7c,0xb8fbba80,0x39a13a7a,0x3a7739b8,0xba7fb92f,0x3a7eb7c9,0xba733960,
0x3a5f39cf,0xba42ba13,0x3a1d3a39,0xb9e6ba58,0x39fcba6a,0xba273a51,0x3a4aba31,0xba653a09,0x39893a6f,0xb897ba7c,0xb8fb3a80,0x39a1ba7a,0x3a77b9b8,0xba7f392f,0x3a7e37c9,0xba73b960,
0xb9fc3a6a,0x3a27ba51,0xba4a3a31,0x3a65ba09,0x3a5f39cf,0xba42ba13,0x3a1d3a39,0xb9e6ba58,0xba7739b8,0x3a7fb92f,0xba7eb7c9,0x3a733960,0x39893a6f,0xb897ba7c,0xb8fb3a80,0x39a1ba7a,
0x3a31ba65,0xba7a39fc,0x3a6f3897,0xba13ba1d,0x3a3939e6,0xb960ba5f,0xb9b83a7f,0x3a51ba4a,0x37c93a73,0x3a09ba77,0xba6a3a27,0x3a7cb8fb,0xba8039a1,0x3a583989,0xb9cfba42,0xb92f3a7e,
0xba39b9e6,0x39603a5f,0x39b8ba7f,0xba513a4a,0x3a31ba65,0xba7a39fc,0x3a6f3897,0xba13ba1d,0x3a80b9a1,0xba58b989,0x39cf3a42,0x392fba7e,0x37c93a73,0x3a09ba77,0xba6a3a27,0x3a7cb8fb,
0x3960ba77,0xba6f3a42,0x3a5138fb,0x37c9ba65,0xba7a3989,0x39b83a27,0x3a13ba7e,0xba8039e6,0x3a0939fc,0x39cfba7f,0xba7c3a1d,0x3a3139a1,0x3a58ba5f,0xba6a3897,0x392f3a4a,0x3a39ba73,
0x3a7ab989,0xb9b8ba27,0xba133a7e,0x3a80b9e6,0x3960ba77,0xba6f3a42,0x3a5138fb,0x37c9ba65,0xba583a5f,0x3a6ab897,0xb92fba4a,0xba393a73,0x3a0939fc,0x39cfba7f,0xba7c3a1d,0x3a3139a1,
0x39e6ba7a,0xba7739cf,0xb8973a51,0x3a7eba39,0x3a65b960,0x3989ba6a,0xba7f3a13,0x38fb3a31,0x3a73ba58,0xb9fcb9b8,0xba423a7c,0x3a4ab7c9,0x39a13a09,0x3a5fba6f,0xba27b92f,0xba1d3a80,
0xba653960,0xb9893a6a,0x3a7fba13,0xb8fbba31,0x39e6ba7a,0xba7739cf,0xb8973a51,0x3a7eba39,0xb9a1ba09,0xba5f3a6f,0x3a27392f,0x3a1dba80,0x3a73ba58,0xb9fcb9b8,0xba423a7c,0x3a4ab7c9,
0xba7f3a51,0xb8fb3a39,0x3a73ba09,0x39fcba6f,0x38973a13,0x3a7eba31,0x39a1ba58,0xba5f39b8,0xba42392f,0xba4a3a80,0x39e63960,0x3a77ba6a,0xba273a7c,0x3a1d37c9,0x3a65ba7a,0xb989b9cf,
0x38973a13,0x3a7eba31,0x39a1ba58,0xba5f39b8,0x3a7fba51,0x38fbba39,0xba733a09,0xb9fc3a6f,0xba273a7c,0x3a1d37c9,0x3a65ba7a,0xb989b9cf,0x3a42b92f,0x3a4aba80,0xb9e6b960,0xba773a6a,
0x392fba1d,0xba3939a1,0xba7a3a77,0xb9b83a42,0x3a7cba4a,0x3a31ba73,0xb960b989,0xba6f3a27,0x3a13b8fb,0x3a80ba65,0x3a09ba5f,0xb9cfb897,0xba513a7e,0x37c939e6,0x3a58b9fc,0x3a6aba7f,
0x3a7cba4a,0x3a31ba73,0xb960b989,0xba6f3a27,0xb92f3a1d,0x3a39b9a1,0x3a7aba77,0x39b8ba42,0xba513a7e,0x37c939e6,0x3a58b9fc,0x3a6aba7f,0xba1338fb,0xba803a65,0xba093a5f,0x39cf3897,
0x39b8b897,0x3a51ba1d,0x3a80ba73,0x3a58ba77,0x3a6fba7f,0x3a13ba4a,0x37c9b9a1,0xba093989,0xba6a3a42,0xba7c3a7e,0xba393a65,0xb96039fc,0xb9cf3a27,0x392f38fb,0x3a31b9e6,0x3a7aba5f,
0x3a6fba7f,0x3a13ba4a,0x37c9b9a1,0xba093989,0xb9b83897,0xba513a1d,0xba803a73,0xba583a77,0xb9cf3a27,0x392f38fb,0x3a31b9e6,0x3a7aba5f,0x3a6aba42,0x3a7cba7e,0x3a39ba65,0x3960b9fc,
0xb8fb37c9,0xb9a13960,0xb9fc39cf,0xba273a13,0x3a7eba80,0x3a73ba7a,0x3a5fba6a,0x3a42ba51,0x3a1dba31,0x39e6ba09,0x3989b9b8,0x3897b92f,0x3a4aba39,0x3a65ba58,0x3a77ba6f,0x3a7fba7c,
0x3a7eba80,0x3a73ba7a,0x3a5fba6a,0x3a42ba51,0x38fbb7c9,0x39a1b960,0x39fcb9cf,0x3a27ba13,0x3a4aba39,0x3a65ba58,0x3a77ba6f,0x3a7fba7c,0xba1d3a31,0xb9e63a09,0xb98939b8,0xb897392f,
0xba4a3a39,0xba653a58,0xba773a6f,0xba7f3a7c,0x3a1dba31,0x39e6ba09,0x3989b9b8,0x3897b92f,0xba7e3a80,0xba733a7a,0xba5f3a6a,0xba423a51,0xb8fb37c9,0xb9a13960,0xb9fc39cf,0xba273a13,
0xba1d3a31,0xb9e63a09,0xb98939b8,0xb897392f,0xba4a3a39,0xba653a58,0xba773a6f,0xba7f3a7c,0x38fbb7c9,0x39a1b960,0x39fcb9cf,0x3a27ba13,0xba7e3a80,0xba733a7a,0xba5f3a6a,0xba423a51,
0x39cfba27,0xb92fb8fb,0xba3139e6,0xba7a3a5f,0xba6a3a42,0xba7c3a7e,0xba393a65,0xb96039fc,0xba6f3a7f,0xba133a4a,0xb7c939a1,0x3a09b989,0x39b8b897,0x3a51ba1d,0x3a80ba73,0x3a58ba77,
0x3a6aba42,0x3a7cba7e,0x3a39ba65,0x3960b9fc,0x39cfba27,0xb92fb8fb,0xba3139e6,0xba7a3a5f,0xb9b83897,0xba513a1d,0xba803a73,0xba583a77,0xba6f3a7f,0xba133a4a,0xb7c939a1,0x3a09b989,
0x3a51ba7e,0xb7c9b9e6,0xba5839fc,0xba6a3a7f,0x3a13b8fb,0x3a80ba65,0x3a09ba5f,0xb9cfb897,0xba7c3a4a,0xba313a73,0x39603989,0x3a6fba27,0x392fba1d,0xba3939a1,0xba7a3a77,0xb9b83a42,
0xba1338fb,0xba803a65,0xba093a5f,0x39cf3897,0x3a51ba7e,0xb7c9b9e6,0xba5839fc,0xba6a3a7f,0xb92f3a1d,0x3a39b9a1,0x3a7aba77,0x39b8ba42,0xba7c3a4a,0xba313a73,0x39603989,0x3a6fba27,
0x3a27ba7c,0xba1db7c9,0xba653a7a,0x398939cf,0xba42392f,0xba4a3a80,0x39e63960,0x3a77ba6a,0xb897ba13,0xba7e3a31,0xb9a13a58,0x3a5fb9b8,0xba7f3a51,0xb8fb3a39,0x3a73ba09,0x39fcba6f,
0x3a42b92f,0x3a4aba80,0xb9e6b960,0xba773a6a,0x3a27ba7c,0xba1db7c9,0xba653a7a,0x398939cf,0x3a7fba51,0x38fbba39,0xba733a09,0xb9fc3a6f,0xb897ba13,0xba7e3a31,0xb9a13a58,0x3a5fb9b8,
0x39a13a09,0x3a5fba6f,0xba27b92f,0xba1d3a80,0xba733a58,0x39fc39b8,0x3a42ba7c,0xba4a37c9,0x3a65b960,0x3989ba6a,0xba7f3a13,0x38fb3a31,0xb9e63a7a,0x3a77b9cf,0x3897ba51,0xba7e3a39,
0xba733a58,0x39fc39b8,0x3a42ba7c,0xba4a37c9,0xb9a1ba09,0xba5f3a6f,0x3a27392f,0x3a1dba80,0xb9e63a7a,0x3a77b9cf,0x3897ba51,0xba7e3a39,0xba653960,0xb9893a6a,0x3a7fba13,0xb8fbba31,
0x3a58ba5f,0xba6a3897,0x392f3a4a,0x3a39ba73,0xba09b9fc,0xb9cf3a7f,0x3a7cba1d,0xba31b9a1,0xba7a3989,0x39b83a27,0x3a13ba7e,0xba8039e6,0xb9603a77,0x3a6fba42,0xba51b8fb,0xb7c93a65,
0xba09b9fc,0xb9cf3a7f,0x3a7cba1d,0xba31b9a1,0xba583a5f,0x3a6ab897,0xb92fba4a,0xba393a73,0xb9603a77,0x3a6fba42,0xba51b8fb,0xb7c93a65,0x3a7ab989,0xb9b8ba27,0xba133a7e,0x3a80b9e6,
0xba8039a1,0x3a583989,0xb9cfba42,0xb92f3a7e,0xb7c9ba73,0xba093a77,0x3a6aba27,0xba7c38fb,0x3a3939e6,0xb960ba5f,0xb9b83a7f,0x3a51ba4a,0xba313a65,0x3a7ab9fc,0xba6fb897,0x3a133a1d,
0xb7c9ba73,0xba093a77,0x3a6aba27,0xba7c38fb,0x3a80b9a1,0xba58b989,0x39cf3a42,0x392fba7e,0xba313a65,0x3a7ab9fc,0xba6fb897,0x3a133a1d,0xba39b9e6,0x39603a5f,0x39b8ba7f,0xba513a4a,
0x3a77b9b8,0xba7f392f,0x3a7e37c9,0xba73b960,0xb989ba6f,0x38973a7c,0x38fbba80,0xb9a13a7a,0x39fcba6a,0xba273a51,0x3a4aba31,0xba653a09,0xba5fb9cf,0x3a423a13,0xba1dba39,0x39e63a58,
0xb989ba6f,0x38973a7c,0x38fbba80,0xb9a13a7a,0xba7739b8,0x3a7fb92f,0xba7eb7c9,0x3a733960,0xba5fb9cf,0x3a423a13,0xba1dba39,0x39e63a58,0xb9fc3a6a,0x3a27ba51,0xba4a3a31,0x3a65ba09,
0xb9893a6f,0x3897ba7c,0x38fb3a80,0xb9a1ba7a,0xba77b9b8,0x3a7f392f,0xba7e37c9,0x3a73b960,0x39fc3a6a,0xba27ba51,0x3a4a3a31,0xba65ba09,0xba5f39cf,0x3a42ba13,0xba1d3a39,0x39e6ba58,
0x3a7739b8,0xba7fb92f,0x3a7eb7c9,0xba733960,0xb9893a6f,0x3897ba7c,0x38fb3a80,0xb9a1ba7a,0x3a5fb9cf,0xba423a13,0x3a1dba39,0xb9e63a58,0x39fc3a6a,0xba27ba51,0x3a4a3a31,0xba65ba09,
0xba80b9a1,0x3a58b989,0xb9cf3a42,0xb92fba7e,0xb7c93a73,0xba09ba77,0x3a6a3a27,0xba7cb8fb,0x3a313a65,0xba7ab9fc,0x3a6fb897,0xba133a1d,0x3a39b9e6,0xb9603a5f,0xb9b8ba7f,0x3a513a4a,
0x37c9ba73,0x3a093a77,0xba6aba27,0x3a7c38fb,0xba80b9a1,0x3a58b989,0xb9cf3a42,0xb92fba7e,0xba3939e6,0x3960ba5f,0x39b83a7f,0xba51ba4a,0x3a313a65,0xba7ab9fc,0x3a6fb897,0xba133a1d,
0xba58ba5f,0x3a6a3897,0xb92f3a4a,0xba39ba73,0x3a09b9fc,0x39cf3a7f,0xba7cba1d,0x3a31b9a1,0x39603a77,0xba6fba42,0x3a51b8fb,0x37c93a65,0xba7ab989,0x39b8ba27,0x3a133a7e,0xba80b9e6,
0xba0939fc,0xb9cfba7f,0x3a7c3a1d,0xba3139a1,0xba58ba5f,0x3a6a3897,0xb92f3a4a,0xba39ba73,0x3a7a3989,0xb9b83a27,0xba13ba7e,0x3a8039e6,0x39603a77,0xba6fba42,0x3a51b8fb,0x37c93a65,
0xba73ba58,0x39fcb9b8,0x3a423a7c,0xba4ab7c9,0xb9a13a09,0xba5fba6f,0x3a27b92f,0x3a1d3a80,0xba65b960,0xb989ba6a,0x3a7f3a13,0xb8fb3a31,0x39e63a7a,0xba77b9cf,0xb897ba51,0x3a7e3a39,
0x39a1ba09,0x3a5f3a6f,0xba27392f,0xba1dba80,0xba73ba58,0x39fcb9b8,0x3a423a7c,0xba4ab7c9,0xb9e6ba7a,0x3a7739cf,0x38973a51,0xba7eba39,0xba65b960,0xb989ba6a,0x3a7f3a13,0xb8fb3a31,
0x3a42392f,0x3a4a3a80,0xb9e63960,0xba77ba6a,0x3a273a7c,0xba1d37c9,0xba65ba7a,0x3989b9cf,0x3897ba13,0x3a7e3a31,0x39a13a58,0xba5fb9b8,0x3a7f3a51,0x38fb3a39,0xba73ba09,0xb9fcba6f,
0x3a273a7c,0xba1d37c9,0xba65ba7a,0x3989b9cf,0xba42b92f,0xba4aba80,0x39e6b960,0x3a773a6a,0x3a7f3a51,0x38fb3a39,0xba73ba09,0xb9fcba6f,0xb8973a13,0xba7eba31,0xb9a1ba58,0x3a5f39b8,
0xba51ba7e,0x37c9b9e6,0x3a5839fc,0x3a6a3a7f,0xba13b8fb,0xba80ba65,0xba09ba5f,0x39cfb897,0x392f3a1d,0xba39b9a1,0xba7aba77,0xb9b8ba42,0x3a7c3a4a,0x3a313a73,0xb9603989,0xba6fba27,
0xba13b8fb,0xba80ba65,0xba09ba5f,0x39cfb897,0x3a513a7e,0xb7c939e6,0xba58b9fc,0xba6aba7f,0x3a7c3a4a,0x3a313a73,0xb9603989,0xba6fba27,0xb92fba1d,0x3a3939a1,0x3a7a3a77,0x39b83a42,
0x39cf3a27,0xb92f38fb,0xba31b9e6,0xba7aba5f,0xba6aba42,0xba7cba7e,0xba39ba65,0xb960b9fc,0x39b83897,0x3a513a1d,0x3a803a73,0x3a583a77,0x3a6f3a7f,0x3a133a4a,0x37c939a1,0xba09b989,
0xba6aba42,0xba7cba7e,0xba39ba65,0xb960b9fc,0xb9cfba27,0x392fb8fb,0x3a3139e6,0x3a7a3a5f,0x3a6f3a7f,0x3a133a4a,0x37c939a1,0xba09b989,0xb9b8b897,0xba51ba1d,0xba80ba73,0xba58ba77,
0xba1dba31,0xb9e6ba09,0xb989b9b8,0xb897b92f,0xba4aba39,0xba65ba58,0xba77ba6f,0xba7fba7c,0xba7eba80,0xba73ba7a,0xba5fba6a,0xba42ba51,0xb8fbb7c9,0xb9a1b960,0xb9fcb9cf,0xba27ba13,
0xba4aba39,0xba65ba58,0xba77ba6f,0xba7fba7c,0x3a1d3a31,0x39e63a09,0x398939b8,0x3897392f,0xb8fbb7c9,0xb9a1b960,0xb9fcb9cf,0xba27ba13,0x3a7e3a80,0x3a733a7a,0x3a5f3a6a,0x3a423a51,
0x3d973cc9,0xbf7fbf80,0x3ee63ecf,0xbf65bf6a,0x3e2f3dfb,0xbf7cbf7e,0x3f093efc,0xbf58bf5f,0x3e893e60,0xbf77bf7a,0x3f1d3f13,0xbf4abf51,0x3eb83ea1,0xbf6fbf73,0x3f313f27,0xbf39bf42,
0x3eb83dfb,0xbf6fbf7e,0x3f393f5f,0x3f313efc,0x3f423f13,0xbf27bf51,0x3ea13f09,0x3f733f58,0x3f7a3f65,0xbe60bee6,0xbe2f3d97,0x3f7c3f7f,0x3f773f80,0x3e893cc9,0xbf1dbecf,0x3f4a3f6a,
0x3f1d3e60,0xbf4abf7a,0xbf5fbf13,0x3efc3f51,0x3f803f65,0xbcc9bee6,0xbf6fbf7f,0xbeb83d97,0x3f273f6a,0x3f423ecf,0xbea1bf31,0xbf73bf39,0xbe2f3e89,0x3f7c3f77,0x3f093dfb,0xbf58bf7e,
0x3f513ea1,0xbf13bf73,0xbe60bf42,0xbf7abf27,0x3f4a3f80,0x3f1d3cc9,0x3f5f3ecf,0xbefcbf6a,0xbeb83e89,0x3f6f3f77,0x3f393f7e,0x3f313dfb,0xbf7fbf58,0xbd973f09,0xbee63e2f,0x3f653f7c,
0x3f733ecf,0xbea1bf6a,0x3f7f3f39,0x3d97bf31,0x3e603f5f,0x3f7a3efc,0xbe2f3f1d,0x3f7c3f4a,0xbf7ebf13,0x3dfb3f51,0xbf77bf58,0xbe893f09,0xbcc9bf42,0xbf80bf27,0x3eb8bee6,0xbf6fbf65,
0x3f803efc,0xbcc9bf5f,0xbeb83f1d,0x3f6f3f4a,0xbee63f09,0x3f653f58,0xbf27bf7c,0xbf423e2f,0xbf13bf7f,0xbf513d97,0x3f7a3ea1,0xbe60bf73,0x3f7e3ecf,0xbdfbbf6a,0xbe893f31,0x3f773f39,
0x3f773f13,0x3e89bf51,0xbf4abf58,0xbf1d3f09,0xbf6a3d97,0x3ecf3f7f,0x3f803ea1,0xbcc9bf73,0x3ee6bf31,0xbf65bf39,0xbf423eb8,0x3f273f6f,0x3e603f7e,0x3f7a3dfb,0x3e2fbf5f,0xbf7cbefc,
0x3f583f27,0x3f09bf42,0x3f51bee6,0xbf13bf65,0xbf77becf,0xbe893f6a,0xbf1d3f31,0x3f4a3f39,0x3f803dfb,0xbcc9bf7e,0x3eb8bf5f,0xbf6fbefc,0xbf733e2f,0x3ea13f7c,0xbd973f7a,0x3f7f3e60,
0x3f273f39,0x3f42bf31,0x3ea13f6f,0x3f73beb8,0xbf13bf4a,0xbf513f1d,0xbe60bf77,0xbf7a3e89,0x3efc3f58,0x3f5fbf09,0x3dfb3f7c,0x3f7ebe2f,0xbecfbf65,0xbf6a3ee6,0xbcc9bf7f,0xbf803d97,
0x3ecf3f4a,0x3f6abf1d,0xbf803e89,0x3cc93f77,0x3d97bf7c,0xbf7f3e2f,0x3f653e60,0x3ee6bf7a,0xbf093f73,0x3f583ea1,0xbf13bf27,0xbf513f42,0x3f5fbf31,0xbefcbf39,0x3dfb3f6f,0x3f7ebeb8,
0x3dfb3f58,0x3f7ebf09,0x3e89bf7c,0xbf773e2f,0x3f31bf73,0xbf39bea1,0xbf6a3f42,0x3ecf3f27,0xbf7f3eb8,0xbd973f6f,0x3f653cc9,0x3ee6bf80,0x3f133efc,0x3f51bf5f,0xbe60bf4a,0xbf7a3f1d,
0xbe2f3f65,0x3f7cbee6,0x3f58bd97,0x3f09bf7f,0x3f7ebf31,0xbdfbbf39,0x3e89bf6f,0xbf773eb8,0xbecfbefc,0xbf6a3f5f,0xbf803f1d,0x3cc93f4a,0xbf423f7a,0x3f273e60,0x3ea13f13,0x3f73bf51,
0xbee63f6f,0x3f65beb8,0xbf423f80,0x3f273cc9,0x3f58be89,0x3f09bf77,0x3f133dfb,0x3f51bf7e,0x3f1dbf7c,0xbf4a3e2f,0x3f5fbf7a,0xbefcbe60,0xbf393d97,0xbf313f7f,0xbecfbea1,0xbf6a3f73,
0xbf313f77,0x3f39be89,0xbecfbdfb,0xbf6a3f7e,0x3ea13e60,0x3f73bf7a,0xbf7f3f51,0xbd973f13,0x3f7cbf42,0x3e2fbf27,0xbf093f65,0x3f58bee6,0x3f1dbf6f,0xbf4a3eb8,0x3efc3cc9,0x3f5fbf80,
0xbf5f3f7c,0x3efcbe2f,0x3f7ebf7a,0xbdfbbe60,0xbeb83f27,0x3f6fbf42,0x3f31bf65,0xbf393ee6,0x3ea13cc9,0x3f73bf80,0x3d97becf,0xbf7f3f6a,0x3f58bf1d,0x3f09bf4a,0xbf133e89,0xbf513f77,
0xbf7a3f7f,0x3e60bd97,0xbe2f3ea1,0x3f7cbf73,0xbf5f3f6f,0x3efcbeb8,0x3dfb3cc9,0x3f7ebf80,0xbf313f4a,0x3f39bf1d,0x3ecfbe89,0x3f6abf77,0xbee63f13,0x3f65bf51,0x3f27bf09,0x3f42bf58,
0xbf7f3f80,0xbd973cc9,0xbf653f6a,0xbee63ecf,0xbf7c3f7e,0xbe2f3dfb,0xbf583f5f,0xbf093efc,0xbf773f7a,0xbe893e60,0xbf4a3f51,0xbf1d3f13,0xbf6f3f73,0xbeb83ea1,0xbf393f42,0xbf313f27,
0xbf6f3f7e,0xbeb83dfb,0x3f31befc,0xbf393f5f,0xbf273f51,0xbf423f13,0x3f73bf58,0xbea13f09,0xbe603ee6,0xbf7a3f65,0x3f7cbf7f,0x3e2f3d97,0x3e89bcc9,0xbf773f80,0x3f4abf6a,0x3f1dbecf,
0xbf4a3f7a,0xbf1d3e60,0x3efcbf51,0x3f5fbf13,0xbcc93ee6,0xbf803f65,0xbeb8bd97,0x3f6fbf7f,0x3f42becf,0xbf273f6a,0xbf733f39,0x3ea1bf31,0x3f7cbf77,0x3e2f3e89,0xbf583f7e,0xbf093dfb,
0xbf133f73,0xbf513ea1,0xbf7a3f27,0x3e60bf42,0x3f1dbcc9,0xbf4a3f80,0xbefc3f6a,0xbf5f3ecf,0x3f6fbf77,0x3eb83e89,0x3f31bdfb,0xbf393f7e,0xbd97bf09,0x3f7fbf58,0x3f65bf7c,0x3ee63e2f,
0xbea13f6a,0xbf733ecf,0x3d973f31,0xbf7f3f39,0x3f7abefc,0xbe603f5f,0x3f7cbf4a,0x3e2f3f1d,0x3dfbbf51,0x3f7ebf13,0xbe89bf09,0x3f77bf58,0xbf803f27,0x3cc9bf42,0xbf6f3f65,0xbeb8bee6,
0xbcc93f5f,0xbf803efc,0x3f6fbf4a,0x3eb83f1d,0x3f65bf58,0x3ee63f09,0xbf42be2f,0x3f27bf7c,0xbf51bd97,0x3f13bf7f,0xbe603f73,0xbf7a3ea1,0xbdfb3f6a,0xbf7e3ecf,0x3f77bf39,0x3e893f31,
0x3e893f51,0xbf773f13,0xbf1dbf09,0x3f4abf58,0x3ecfbf7f,0x3f6a3d97,0xbcc93f73,0xbf803ea1,0xbf653f39,0xbee6bf31,0x3f27bf6f,0x3f423eb8,0x3f7abdfb,0xbe603f7e,0xbf7c3efc,0xbe2fbf5f,
0x3f093f42,0xbf583f27,0xbf133f65,0xbf51bee6,0xbe89bf6a,0x3f77becf,0x3f4abf39,0x3f1d3f31,0xbcc93f7e,0xbf803dfb,0xbf6f3efc,0xbeb8bf5f,0x3ea1bf7c,0x3f733e2f,0x3f7fbe60,0x3d973f7a,
0x3f423f31,0xbf273f39,0x3f733eb8,0xbea13f6f,0xbf51bf1d,0x3f13bf4a,0xbf7abe89,0x3e60bf77,0x3f5f3f09,0xbefc3f58,0x3f7e3e2f,0xbdfb3f7c,0xbf6abee6,0x3ecfbf65,0xbf80bd97,0x3cc9bf7f,
0x3f6a3f1d,0xbecf3f4a,0x3cc9bf77,0x3f803e89,0xbf7fbe2f,0xbd97bf7c,0x3ee63f7a,0xbf653e60,0x3f58bea1,0x3f093f73,0xbf51bf42,0x3f13bf27,0xbefc3f39,0xbf5fbf31,0x3f7e3eb8,0xbdfb3f6f,
0x3f7e3f09,0xbdfb3f58,0xbf77be2f,0xbe89bf7c,0xbf393ea1,0xbf31bf73,0x3ecfbf27,0x3f6a3f42,0xbd97bf6f,0x3f7f3eb8,0x3ee63f80,0xbf653cc9,0x3f513f5f,0xbf133efc,0xbf7abf1d,0x3e60bf4a,
0x3f7c3ee6,0x3e2f3f65,0x3f093f7f,0xbf58bd97,0xbdfb3f39,0xbf7ebf31,0xbf77beb8,0xbe89bf6f,0xbf6abf5f,0x3ecfbefc,0x3cc9bf4a,0x3f803f1d,0x3f27be60,0x3f423f7a,0x3f733f51,0xbea13f13,
0x3f653eb8,0x3ee63f6f,0x3f27bcc9,0x3f423f80,0x3f093f77,0xbf58be89,0x3f513f7e,0xbf133dfb,0xbf4abe2f,0xbf1dbf7c,0xbefc3e60,0xbf5fbf7a,0xbf31bf7f,0x3f393d97,0xbf6abf73,0x3ecfbea1,
0x3f393e89,0x3f313f77,0xbf6abf7e,0x3ecfbdfb,0x3f733f7a,0xbea13e60,0xbd97bf13,0x3f7f3f51,0x3e2f3f27,0xbf7cbf42,0x3f583ee6,0x3f093f65,0xbf4abeb8,0xbf1dbf6f,0x3f5f3f80,0xbefc3cc9,
0x3efc3e2f,0x3f5f3f7c,0xbdfb3e60,0xbf7ebf7a,0x3f6f3f42,0x3eb83f27,0xbf39bee6,0xbf31bf65,0x3f733f80,0xbea13cc9,0xbf7fbf6a,0xbd97becf,0x3f093f4a,0xbf58bf1d,0xbf51bf77,0x3f133e89,
0x3e603d97,0x3f7a3f7f,0x3f7c3f73,0x3e2f3ea1,0x3efc3eb8,0x3f5f3f6f,0x3f7e3f80,0xbdfb3cc9,0x3f393f1d,0x3f313f4a,0x3f6a3f77,0xbecfbe89,0x3f653f51,0x3ee63f13,0x3f423f58,0xbf27bf09,
0x3f423f39,0xbf27bf31,0x3f733f6f,0xbea1beb8,0x3f513f4a,0xbf13bf1d,0x3f7a3f77,0xbe60be89,0x3f5f3f58,0xbefcbf09,0x3f7e3f7c,0xbdfbbe2f,0x3f6a3f65,0xbecfbee6,0x3f803f7f,0xbcc9bd97,
0xbf6abf4a,0x3ecf3f1d,0xbcc9be89,0xbf80bf77,0xbf7fbf7c,0xbd973e2f,0x3ee63e60,0xbf65bf7a,0xbf58bf73,0xbf09bea1,0x3f513f27,0xbf13bf42,0xbefcbf31,0xbf5fbf39,0x3f7e3f6f,0xbdfbbeb8,
0x3f7e3f58,0xbdfbbf09,0xbf77bf7c,0xbe893e2f,0x3f393f73,0x3f313ea1,0xbecfbf42,0xbf6abf27,0xbd973eb8,0x3f7f3f6f,0x3ee63cc9,0xbf65bf80,0xbf51befc,0x3f133f5f,0x3f7a3f4a,0xbe60bf1d,
0xbf7cbf65,0xbe2f3ee6,0xbf093d97,0x3f583f7f,0xbdfbbf31,0xbf7ebf39,0xbf77bf6f,0xbe893eb8,0x3f6a3efc,0xbecfbf5f,0xbcc9bf1d,0xbf80bf4a,0x3f273f7a,0x3f423e60,0x3f733f13,0xbea1bf51,
0x3f653f6f,0x3ee6beb8,0x3f273f80,0x3f423cc9,0xbf093e89,0x3f583f77,0xbf51bdfb,0x3f133f7e,0xbf4abf7c,0xbf1d3e2f,0xbefcbf7a,0xbf5fbe60,0x3f31bd97,0xbf39bf7f,0x3f6a3ea1,0xbecfbf73,
0xbf39bf77,0xbf313e89,0x3f6a3dfb,0xbecfbf7e,0x3f733e60,0xbea1bf7a,0xbd973f51,0x3f7f3f13,0xbe2f3f42,0x3f7c3f27,0xbf58bf65,0xbf093ee6,0xbf4abf6f,0xbf1d3eb8,0x3f5f3cc9,0xbefcbf80,
0x3efc3f7c,0x3f5fbe2f,0xbdfbbf7a,0xbf7ebe60,0xbf6fbf27,0xbeb83f42,0x3f393f65,0x3f31bee6,0x3f733cc9,0xbea1bf80,0xbf7fbecf,0xbd973f6a,0xbf093f1d,0x3f583f4a,0x3f51be89,0xbf13bf77,
0xbe60bf7f,0xbf7a3d97,0xbf7cbea1,0xbe2f3f73,0x3efc3f6f,0x3f5fbeb8,0x3f7e3cc9,0xbdfbbf80,0xbf39bf4a,0xbf313f1d,0xbf6a3e89,0x3ecf3f77,0x3f653f13,0x3ee6bf51,0x3f42bf09,0xbf27bf58,
0xbd973f80,0x3f7f3cc9,0xbee63f6a,0x3f653ecf,0x3e2fbf7e,0xbf7cbdfb,0x3f09bf5f,0xbf58befc,0xbe893f7a,0x3f773e60,0xbf1d3f51,0x3f4a3f13,0x3eb8bf73,0xbf6fbea1,0x3f31bf42,0xbf39bf27,
0x3eb8bf7e,0xbf6fbdfb,0x3f393efc,0x3f31bf5f,0xbf423f51,0x3f273f13,0xbea1bf58,0xbf733f09,0x3f7abee6,0xbe60bf65,0xbe2f3f7f,0x3f7cbd97,0xbf77bcc9,0xbe893f80,0x3f1dbf6a,0xbf4abecf,
0xbf1d3f7a,0x3f4a3e60,0x3f5fbf51,0xbefcbf13,0x3f80bee6,0xbcc9bf65,0xbf6f3d97,0xbeb83f7f,0xbf27becf,0xbf423f6a,0x3ea13f39,0x3f73bf31,0xbe2f3f77,0x3f7cbe89,0x3f09bf7e,0xbf58bdfb,
0x3f51bf73,0xbf13bea1,0xbe60bf27,0xbf7a3f42,0xbf4abcc9,0xbf1d3f80,0xbf5f3f6a,0x3efc3ecf,0xbeb83f77,0x3f6fbe89,0x3f393dfb,0x3f31bf7e,0x3f7fbf09,0x3d97bf58,0x3ee6bf7c,0xbf653e2f,
0xbf733f6a,0x3ea13ecf,0xbf7f3f31,0xbd973f39,0x3e603efc,0x3f7abf5f,0xbe2f3f4a,0x3f7cbf1d,0x3f7ebf51,0xbdfbbf13,0x3f77bf09,0x3e89bf58,0xbcc9bf27,0xbf803f42,0x3eb8bf65,0xbf6f3ee6,
0x3f80bf5f,0xbcc9befc,0xbeb83f4a,0x3f6fbf1d,0x3ee6bf58,0xbf653f09,0x3f27be2f,0x3f42bf7c,0xbf133d97,0xbf513f7f,0x3f7abf73,0xbe60bea1,0xbf7e3f6a,0x3dfb3ecf,0x3e89bf39,0xbf773f31,
0xbf773f51,0xbe893f13,0x3f4abf09,0x3f1dbf58,0xbf6a3f7f,0x3ecfbd97,0x3f80bf73,0xbcc9bea1,0xbee63f39,0x3f65bf31,0x3f42bf6f,0xbf273eb8,0x3e603dfb,0x3f7abf7e,0x3e2fbefc,0xbf7c3f5f,
0x3f58bf42,0x3f09bf27,0x3f51bf65,0xbf133ee6,0x3f77bf6a,0x3e89becf,0x3f1dbf39,0xbf4a3f31,0x3f80bf7e,0xbcc9bdfb,0x3eb8befc,0xbf6f3f5f,0x3f73bf7c,0xbea13e2f,0x3d97be60,0xbf7f3f7a,
0xbf273f31,0xbf423f39,0xbea13eb8,0xbf733f6f,0xbf133f1d,0xbf513f4a,0xbe603e89,0xbf7a3f77,0xbefc3f09,0xbf5f3f58,0xbdfb3e2f,0xbf7e3f7c,0xbecf3ee6,0xbf6a3f65,0xbcc93d97,0xbf803f7f,
0x3ecfbf1d,0x3f6abf4a,0xbf803f77,0x3cc9be89,0xbd97be2f,0x3f7fbf7c,0xbf653f7a,0xbee63e60,0xbf093ea1,0x3f58bf73,0xbf133f42,0xbf513f27,0xbf5f3f39,0x3efcbf31,0xbdfb3eb8,0xbf7e3f6f,
0xbdfb3f09,0xbf7e3f58,0xbe89be2f,0x3f77bf7c,0x3f31bea1,0xbf393f73,0xbf6a3f27,0x3ecfbf42,0x3f7fbf6f,0x3d973eb8,0xbf653f80,0xbee63cc9,0x3f13bf5f,0x3f51befc,0xbe603f1d,0xbf7a3f4a,
0xbe2fbee6,0x3f7cbf65,0x3f58bf7f,0x3f093d97,0xbf7e3f39,0x3dfbbf31,0xbe89beb8,0x3f77bf6f,0xbecf3f5f,0xbf6a3efc,0xbf803f4a,0x3cc9bf1d,0x3f42be60,0xbf273f7a,0xbea13f51,0xbf733f13,
0x3ee63eb8,0xbf653f6f,0x3f42bcc9,0xbf273f80,0x3f58bf77,0x3f093e89,0x3f13bf7e,0x3f51bdfb,0xbf1dbe2f,0x3f4abf7c,0xbf5f3e60,0x3efcbf7a,0xbf393f7f,0xbf31bd97,0xbecf3f73,0xbf6a3ea1,
0xbf31be89,0x3f39bf77,0xbecf3f7e,0xbf6a3dfb,0xbea13f7a,0xbf733e60,0x3f7fbf13,0x3d973f51,0x3f7cbf27,0x3e2f3f42,0xbf09bee6,0x3f58bf65,0xbf1dbeb8,0x3f4abf6f,0xbefc3f80,0xbf5f3cc9,
0x3f5f3e2f,0xbefc3f7c,0xbf7e3e60,0x3dfbbf7a,0xbeb8bf42,0x3f6fbf27,0x3f313ee6,0xbf393f65,0xbea13f80,0xbf733cc9,0xbd97bf6a,0x3f7fbecf,0x3f58bf4a,0x3f093f1d,0xbf133f77,0xbf51be89,
0xbf7abd97,0x3e60bf7f,0xbe2fbf73,0x3f7cbea1,0x3f5f3eb8,0xbefc3f6f,0xbdfb3f80,0xbf7e3cc9,0xbf31bf1d,0x3f39bf4a,0x3ecfbf77,0x3f6a3e89,0x3ee63f51,0xbf653f13,0xbf273f58,0xbf42bf09,
0x3f7fbcc9,0x3d973f80,0x3f65becf,0x3ee63f6a,0xbf7c3dfb,0xbe2fbf7e,0xbf583efc,0xbf09bf5f,0x3f77be60,0x3e893f7a,0x3f4abf13,0x3f1d3f51,0xbf6f3ea1,0xbeb8bf73,0xbf393f27,0xbf31bf42,
0xbf6f3dfb,0xbeb8bf7e,0x3f313f5f,0xbf393efc,0x3f27bf13,0x3f423f51,0xbf73bf09,0x3ea1bf58,0xbe603f65,0xbf7abee6,0x3f7c3d97,0x3e2f3f7f,0xbe89bf80,0x3f77bcc9,0xbf4a3ecf,0xbf1dbf6a,
0x3f4abe60,0x3f1d3f7a,0xbefc3f13,0xbf5fbf51,0xbcc93f65,0xbf80bee6,0xbeb8bf7f,0x3f6f3d97,0xbf42bf6a,0x3f27becf,0x3f733f31,0xbea13f39,0x3f7c3e89,0x3e2f3f77,0xbf583dfb,0xbf09bf7e,
0xbf133ea1,0xbf51bf73,0xbf7abf42,0x3e60bf27,0xbf1dbf80,0x3f4abcc9,0x3efcbecf,0x3f5f3f6a,0x3f6f3e89,0x3eb83f77,0x3f313f7e,0xbf393dfb,0x3d973f58,0xbf7fbf09,0xbf65be2f,0xbee6bf7c,
0x3ea1becf,0x3f733f6a,0xbd97bf39,0x3f7f3f31,0x3f7a3f5f,0xbe603efc,0x3f7c3f1d,0x3e2f3f4a,0xbdfb3f13,0xbf7ebf51,0x3e893f58,0xbf77bf09,0xbf80bf42,0x3cc9bf27,0xbf6fbee6,0xbeb8bf65,
0xbcc93efc,0xbf80bf5f,0x3f6f3f1d,0x3eb83f4a,0xbf65bf09,0xbee6bf58,0x3f423f7c,0xbf27be2f,0xbf51bf7f,0x3f133d97,0xbe603ea1,0xbf7abf73,0x3dfbbecf,0x3f7e3f6a,0xbf77bf31,0xbe89bf39,
0xbe89bf13,0x3f773f51,0x3f1d3f58,0xbf4abf09,0x3ecf3d97,0x3f6a3f7f,0xbcc93ea1,0xbf80bf73,0x3f653f31,0x3ee63f39,0xbf27beb8,0xbf42bf6f,0x3f7a3f7e,0xbe603dfb,0xbf7cbf5f,0xbe2fbefc,
0x3f093f27,0xbf58bf42,0xbf13bee6,0xbf51bf65,0x3e893ecf,0xbf77bf6a,0xbf4abf31,0xbf1dbf39,0xbcc93dfb,0xbf80bf7e,0xbf6fbf5f,0xbeb8befc,0xbea1be2f,0xbf73bf7c,0xbf7fbf7a,0xbd97be60,
0x3f6e3f7a,0x3f1f3f28,0x3ec23ed0,0x3e2f3e48,0x3f583f63,0x3f0e3f17,0x3ea63eb4,0x3df93e15,0x3f443f4e,0x3efd3f06,0x3e8b3e99,0x3d953dc7,0x3f313f3a,0x3edf3eee,0x3e623e7c,0x3cc63d46,
0x3f583f62,0x3f133f1b,0x3eb53ec2,0x3e243e3b,0x3f453f4f,0x3f043f0b,0x3e9b3ea8,0x3de93e0c,0x3f333f3c,0x3eeb3ef9,0x3e823e8f,0x3d8b3dba,0x3f233f2b,0x3ecf3edd,0x3e533e6c,0x3cb93d39,
0x3f443f4d,0x3f073f0e,0x3ea83eb4,0x3e183e2e,0x3f343f3c,0x3ef33f00,0x3e903e9c,0x3dd93e02,0x3f243f2c,0x3ed93ee6,0x3e723e84,0x3d823dad,0x3f153f1c,0x3ec03ecc,0x3e453e5b,0x3cad3d2d,
0x3f323f39,0x3ef73f02,0x3e9b3ea6,0x3e0d3e22,0x3f233f2a,0x3edf3eeb,0x3e853e90,0x3dc93df1,0x3f153f1c,0x3ec83ed3,0x3e603e75,0x3d713da1,0x3f083f0f,0x3eb13ebc,0x3e363e4b,0x3ca03d20,
0x3f203f27,0x3ee13eec,0x3e8e3e98,0x3e023e15,0x3f133f1a,0x3ecc3ed6,0x3e743e84,0x3db93dde,0x3f073f0d,0x3eb73ec1,0x3e4e3e61,0x3d5e3d94,0x3ef83f02,0x3ea23eac,0x3e283e3b,0x3c943d14,
0x3f103f15,0x3ecc3ed6,0x3e813e8a,0x3ded3e08,0x3f053f0a,0x3eb93ec2,0x3e5f3e71,0x3da93dcb,0x3ef43eff,0x3ea63eaf,0x3e3c3e4d,0x3d4b3d87,0x3ee03eea,0x3e933e9d,0x3e193e2a,0x3c873d07,
0x3f003f05,0x3eb73ec0,0x3e6a3e7a,0x3dd73df6,0x3eed3ef6,0x3ea63eaf,0x3e4a3e5a,0x3d993db8,0x3edb3ee4,0x3e963e9e,0x3e2a3e3a,0x3d383d75,0x3ec93ed2,0x3e853e8d,0x3e0b3e1a,0x3c753cf5,
0x3ee23eeb,0x3ea33eab,0x3e513e5f,0x3dc13ddd,0x3ed23eda,0x3e943e9c,0x3e353e43,0x3d8a3da5,0x3ec23eca,0x3e853e8d,0x3e183e26,0x3d253d5c,0x3eb33eba,0x3e6e3e7c,0x3df93e0a,0x3c5c3cdc,
0x3ec63ecd,0x3e903e96,0x3e393e45,0x3dab3dc3,0x3eb83ebf,0x3e833e89,0x3e203e2c,0x3d743d92,0x3eaa3eb1,0x3e6b3e78,0x3e073e13,0x3d123d43,0x3e9d3ea3,0x3e523e5f,0x3ddc3df5,0x3c433cc3,
0x3eaa3eb0,0x3e793e82,0x3e203e2b,0x3d953daa,0x3e9f3ea4,0x3e623e6d,0x3e0b3e15,0x3d543d7f,0x3e933e99,0x3e4c3e57,0x3dea3e00,0x3cff3d2a,0x3e883e8d,0x3e363e41,0x3dbf3dd5,0x3c2a3caa,
0x3e903e94,0x3e533e5c,0x3e083e11,0x3d7d3d91,0x3e863e8b,0x3e403e49,0x3dec3dfe,0x3d353d59,0x3e793e81,0x3e2d3e37,0x3dc73dda,0x3cd93d11,0x3e663e6f,0x3e1b3e24,0x3da33db5,0x3c113c91,
0x3e6b3e73,0x3e2d3e35,0x3de13df0,0x3d513d6f,0x3e5c3e63,0x3e1e3e26,0x3dc33dd2,0x3d153d33,0x3e4c3e54,0x3e0f3e16,0x3da53db4,0x3cb33cef,0x3e3d3e44,0x3dff3e07,0x3d863d95,0x3bef3c6f,
0x3e393e3f,0x3e083e0e,0x3db13dbd,0x3d253d3d,0x3e2c3e32,0x3df93e02,0x3d993da5,0x3cec3d0d,0x3e203e26,0x3de13ded,0x3d823d8e,0x3c8d3cbd,0x3e143e1a,0x3dc93dd5,0x3d543d6c,0x3bbc3c3d,
0x3e073e0b,0x3dc73dd0,0x3d823d8a,0x3cf23d0a,0x3dfc3e02,0x3db63dbf,0x3d613d72,0x3cad3ccf,0x3dea3df3,0x3da53dad,0x3d3e3d50,0x3c4f3c8a,0x3dd93de2,0x3d933d9c,0x3d1c3d2d,0x3b8a3c0a,
0x3dab3db0,0x3d7d3d84,0x3d253d30,0x3c9a3cb0,0x3da03da5,0x3d673d72,0x3d0f3d1a,0x3c5c3c84,0x3d953d9a,0x3d513d5c,0x3cf23d04,0x3c043c30,0x3d8a3d8f,0x3d3b3d46,0x3cc63cdc,0x3b303bb0,
0x3d123d17,0x3cd93ce2,0x3c8d3c97,0x3c043c17,0x3d093d0d,0x3cc63ccf,0x3c753c84,0x3bbc3be2,0x3cff3d04,0x3cb33cbd,0x3c4f3c62,0x3b623b97,0x3cec3cf5,0x3ca03caa,0x3c2a3c3d,0x3a973b17,
0xbc43bc49,0xbc11bc17,0xbbbcbbc9,0xbb30bb49,0xbc36bc3d,0xbc04bc0a,0xbba3bbb0,0xbafbbb17,0xbc2abc30,0xbbefbbfb,0xbb8abb97,0xba97bac9,0xbc1dbc23,0xbbd6bbe2,0xbb62bb7b,0xb9c9ba49,
0xbd74bd7c,0xbd35bd3d,0xbcecbcfb,0xbc5cbc7b,0xbd64bd6c,0xbd25bd2d,0xbcccbcdc,0xbc1dbc3d,0xbd54bd5c,0xbd15bd1d,0xbcadbcbd,0xbbbcbbfb,0xbd45bd4c,0xbd06bd0d,0xbc8dbc9d,0xbafbbb7b,
0xbddcbde3,0xbda3bdaa,0xbd54bd62,0xbcc6bce2,0xbdcebdd5,0xbd95bd9c,0xbd38bd46,0xbc8dbcaa,0xbdbfbdc7,0xbd86bd8e,0xbd1cbd2a,0xbc2abc62,0xbdb1bdb8,0xbd71bd7f,0xbcffbd0d,0xbb62bbe2,
0xbe20be25,0xbdecbdf6,0xbd99bda4,0xbd0fbd23,0xbe15be1a,0xbdd7bde2,0xbd85bd8f,0xbcccbcf5,0xbe0bbe10,0xbdc3bdcd,0xbd61bd75,0xbc75bca3,0xbe00be05,0xbdaebdb8,0xbd38bd4c,0xbba3bc23,
0xbe52be59,0xbe1bbe22,0xbdc9bdd6,0xbd3bbd56,0xbe44be4b,0xbe0dbe14,0xbdaebdbb,0xbd06bd20,0xbe36be3d,0xbdffbe06,0xbd93bda1,0xbca0bcd6,0xbe28be2f,0xbde4bdf1,0xbd71bd86,0xbbd6bc56,
0xbe83be87,0xbe40be48,0xbdf9be05,0xbd67bd84,0xbe74be7c,0xbe2fbe37,0xbdd7bde8,0xbd25bd46,0xbe62be6b,0xbe1ebe26,0xbdb6bdc7,0xbcc6bd04,0xbe51be5a,0xbe0dbe15,0xbd95bda5,0xbc04bc84,
0xbe9dbea2,0xbe66be70,0xbe14be1e,0xbd8abd9d,0xbe92be97,0xbe51be5b,0xbe00be0a,0xbd45bd6c,0xbe88be8d,0xbe3dbe47,0xbdd9bded,0xbcecbd1d,0xbe7abe82,0xbe28be32,0xbdb1bdc5,0xbc1dbc9d,
0xbeb8bebe,0xbe86be8c,0xbe2cbe38,0xbda0bdb7,0xbeabbeb1,0xbe74be80,0xbe15be21,0xbd64bd89,0xbe9fbea5,0xbe5cbe68,0xbdfcbe09,0xbd09bd36,0xbe92be98,0xbe44be50,0xbdcebde5,0xbc36bcb6,
0xbed4bedb,0xbe99bea0,0xbe45be52,0xbdb6bdd0,0xbec5becc,0xbe8bbe92,0xbe2abe37,0xbd82bd9c,0xbeb6bebd,0xbe7bbe84,0xbe0fbe1d,0xbd1cbd50,0xbea8beaf,0xbe60be6d,0xbdeabe02,0xbc4fbccf,
0xbef1befa,0xbeadbeb5,0xbe5dbe6d,0xbdccbde9,0xbedfbee8,0xbe9dbea5,0xbe3fbe4e,0xbd92bdaf,0xbecebed7,0xbe8dbe95,0xbe21be30,0xbd2ebd69,0xbebebec6,0xbe7cbe86,0xbe03be12,0xbc68bce9,
0xbf08bf0d,0xbec2becb,0xbe76be84,0xbde2be01,0xbefbbf03,0xbeafbeb9,0xbe54be65,0xbda1bdc2,0xbee7bef1,0xbe9ebea7,0xbe33be44,0xbd41bd81,0xbed4bede,0xbe8cbe95,0xbe12be22,0xbc81bd01,
0xbf18bf1e,0xbed7bee1,0xbe88be91,0xbdf9be0e,0xbf0cbf12,0xbec2becc,0xbe6abe7c,0xbdb1bdd5,0xbf01bf06,0xbeaebeb8,0xbe45be57,0xbd54bd8e,0xbeecbef6,0xbe9bbea4,0xbe20be32,0xbc8dbd0d,
0xbf29bf30,0xbeecbef8,0xbe94be9f,0xbe07be1b,0xbf1bbf22,0xbed5bee1,0xbe7fbe8a,0xbdc1bde8,0xbf0ebf15,0xbebfbeca,0xbe57be6b,0xbd67bd9a,0xbf02bf08,0xbea9beb4,0xbe2fbe43,0xbc9abd1a,
0xbf3bbf43,0xbf01bf08,0xbea1bead,0xbe13be28,0xbf2bbf33,0xbee9bef6,0xbe8bbe96,0xbdd1bdfb,0xbf1dbf24,0xbed0bedc,0xbe69be7f,0xbd7abda7,0xbf0fbf15,0xbeb8bec4,0xbe3dbe53,0xbca7bd27,
0xbf4ebf57,0xbf0dbf14,0xbeaebebb,0xbe1ebe35,0xbf3cbf45,0xbefdbf06,0xbe96bea2,0xbde1be07,0xbf2bbf34,0xbee2beef,0xbe7bbe89,0xbd86bdb4,0xbf1cbf23,0xbec8bed5,0xbe4cbe63,0xbcb3bd33,
0xbf63bf6e,0xbf19bf21,0xbebbbec9,0xbe29be42,0xbf4ebf58,0xbf09bf11,0xbea1beae,0xbdf1be11,0xbf3bbf45,0xbef4bf01,0xbe87be94,0xbd90bdc0,0xbf29bf32,0xbed7bee5,0xbe5bbe74,0xbcc0bd40,
0xbcc68000,0xbe62be48,0xbedfbed0,0xbf31bf28,0xbd95bd46,0xbe8bbe7c,0xbefdbeee,0xbf44bf3a,0xbdf9bdc7,0xbea6be99,0xbf0ebf06,0xbf58bf4e,0xbe2fbe15,0xbec2beb4,0xbf1fbf17,0xbf6ebf63,
0xbcb98000,0xbe53be3b,0xbecfbec2,0xbf23bf1b,0xbd8bbd39,0xbe82be6c,0xbeebbedd,0xbf33bf2b,0xbde9bdba,0xbe9bbe8f,0xbf04bef9,0xbf45bf3c,0xbe24be0c,0xbeb5bea8,0xbf13bf0b,0xbf58bf4f,
0xbcad8000,0xbe45be2e,0xbec0beb4,0xbf15bf0e,0xbd82bd2d,0xbe72be5b,0xbed9becc,0xbf24bf1c,0xbdd9bdad,0xbe90be84,0xbef3bee6,0xbf34bf2c,0xbe18be02,0xbea8be9c,0xbf07bf00,0xbf44bf3c,
0xbca08000,0xbe36be22,0xbeb1bea6,0xbf08bf02,0xbd71bd20,0xbe60be4b,0xbec8bebc,0xbf15bf0f,0xbdc9bda1,0xbe85be75,0xbedfbed3,0xbf23bf1c,0xbe0dbdf1,0xbe9bbe90,0xbef7beeb,0xbf32bf2a,
0xbc948000,0xbe28be15,0xbea2be98,0xbef8beec,0xbd5ebd14,0xbe4ebe3b,0xbeb7beac,0xbf07bf02,0xbdb9bd94,0xbe74be61,0xbeccbec1,0xbf13bf0d,0xbe02bdde,0xbe8ebe84,0xbee1bed6,0xbf20bf1a,
0xbc878000,0xbe19be08,0xbe93be8a,0xbee0bed6,0xbd4bbd07,0xbe3cbe2a,0xbea6be9d,0xbef4beea,0xbda9bd87,0xbe5fbe4d,0xbeb9beaf,0xbf05beff,0xbdedbdcb,0xbe81be71,0xbeccbec2,0xbf10bf0a,
0xbc758000,0xbe0bbdf6,0xbe85be7a,0xbec9bec0,0xbd38bcf5,0xbe2abe1a,0xbe96be8d,0xbedbbed2,0xbd99bd75,0xbe4abe3a,0xbea6be9e,0xbeedbee4,0xbdd7bdb8,0xbe6abe5a,0xbeb7beaf,0xbf00bef6,
0xbc5c8000,0xbdf9bddd,0xbe6ebe5f,0xbeb3beab,0xbd25bcdc,0xbe18be0a,0xbe85be7c,0xbec2beba,0xbd8abd5c,0xbe35be26,0xbe94be8d,0xbed2beca,0xbdc1bda5,0xbe51be43,0xbea3be9c,0xbee2beda,
0xbc438000,0xbddcbdc3,0xbe52be45,0xbe9dbe96,0xbd12bcc3,0xbe07bdf5,0xbe6bbe5f,0xbeaabea3,0xbd74bd43,0xbe20be13,0xbe83be78,0xbeb8beb1,0xbdabbd92,0xbe39be2c,0xbe90be89,0xbec6bebf,
0xbc2a8000,0xbdbfbdaa,0xbe36be2b,0xbe88be82,0xbcffbcaa,0xbdeabdd5,0xbe4cbe41,0xbe93be8d,0xbd54bd2a,0xbe0bbe00,0xbe62be57,0xbe9fbe99,0xbd95bd7f,0xbe20be15,0xbe79be6d,0xbeaabea4,
0xbc118000,0xbda3bd91,0xbe1bbe11,0xbe66be5c,0xbcd9bc91,0xbdc7bdb5,0xbe2dbe24,0xbe79be6f,0xbd35bd11,0xbdecbdda,0xbe40be37,0xbe86be81,0xbd7dbd59,0xbe08bdfe,0xbe53be49,0xbe90be8b,
0xbbef8000,0xbd86bd6f,0xbdffbdf0,0xbe3dbe35,0xbcb3bc6f,0xbda5bd95,0xbe0fbe07,0xbe4cbe44,0xbd15bcef,0xbdc3bdb4,0xbe1ebe16,0xbe5cbe54,0xbd51bd33,0xbde1bdd2,0xbe2dbe26,0xbe6bbe63,
0xbbbc8000,0xbd54bd3d,0xbdc9bdbd,0xbe14be0e,0xbc8dbc3d,0xbd82bd6c,0xbde1bdd5,0xbe20be1a,0xbcecbcbd,0xbd99bd8e,0xbdf9bded,0xbe2cbe26,0xbd25bd0d,0xbdb1bda5,0xbe08be02,0xbe39be32,
0xbb8a8000,0xbd1cbd0a,0xbd93bd8a,0xbdd9bdd0,0xbc4fbc0a,0xbd3ebd2d,0xbda5bd9c,0xbdeabde2,0xbcadbc8a,0xbd61bd50,0xbdb6bdad,0xbdfcbdf3,0xbcf2bccf,0xbd82bd72,0xbdc7bdbf,0xbe07be02,
0xbb308000,0xbcc6bcb0,0xbd3bbd30,0xbd8abd84,0xbc04bbb0,0xbcf2bcdc,0xbd51bd46,0xbd95bd8f,0xbc5cbc30,0xbd0fbd04,0xbd67bd5c,0xbda0bd9a,0xbc9abc84,0xbd25bd1a,0xbd7dbd72,0xbdabbda5,
0xba978000,0xbc2abc17,0xbca0bc97,0xbcecbce2,0xbb62bb17,0xbc4fbc3d,0xbcb3bcaa,0xbcffbcf5,0xbbbcbb97,0xbc75bc62,0xbcc6bcbd,0xbd09bd04,0xbc04bbe2,0xbc8dbc84,0xbcd9bccf,0xbd12bd0d,
0x39c90000,0x3b623b49,0x3bd63bc9,0x3c1d3c17,0x3a973a49,0x3b8a3b7b,0x3bef3be2,0x3c2a3c23,0x3afb3ac9,0x3ba33b97,0x3c043bfb,0x3c363c30,0x3b303b17,0x3bbc3bb0,0x3c113c0a,0x3c433c3d,
0x3afb0000,0x3c8d3c7b,0x3d063cfb,0x3d453d3d,0x3bbc3b7b,0x3cad3c9d,0x3d153d0d,0x3d543d4c,0x3c1d3bfb,0x3ccc3cbd,0x3d253d1d,0x3d643d5c,0x3c5c3c3d,0x3cec3cdc,0x3d353d2d,0x3d743d6c,
0x3b620000,0x3cff3ce2,0x3d713d62,0x3db13daa,0x3c2a3be2,0x3d1c3d0d,0x3d863d7f,0x3dbf3db8,0x3c8d3c62,0x3d383d2a,0x3d953d8e,0x3dce3dc7,0x3cc63caa,0x3d543d46,0x3da33d9c,0x3ddc3dd5,
0x3ba30000,0x3d383d23,0x3dae3da4,0x3e003df6,0x3c753c23,0x3d613d4c,0x3dc33db8,0x3e0b3e05,0x3ccc3ca3,0x3d853d75,0x3dd73dcd,0x3e153e10,0x3d0f3cf5,0x3d993d8f,0x3dec3de2,0x3e203e1a,
0x3bd60000,0x3d713d56,0x3de43dd6,0x3e283e22,0x3ca03c56,0x3d933d86,0x3dff3df1,0x3e363e2f,0x3d063cd6,0x3dae3da1,0x3e0d3e06,0x3e443e3d,0x3d3b3d20,0x3dc93dbb,0x3e1b3e14,0x3e523e4b,
0x3c040000,0x3d953d84,0x3e0d3e05,0x3e513e48,0x3cc63c84,0x3db63da5,0x3e1e3e15,0x3e623e5a,0x3d253d04,0x3dd73dc7,0x3e2f3e26,0x3e743e6b,0x3d673d46,0x3df93de8,0x3e403e37,0x3e833e7c,
0x3c1d0000,0x3db13d9d,0x3e283e1e,0x3e7a3e70,0x3cec3c9d,0x3dd93dc5,0x3e3d3e32,0x3e883e82,0x3d453d1d,0x3e003ded,0x3e513e47,0x3e923e8d,0x3d8a3d6c,0x3e143e0a,0x3e663e5b,0x3e9d3e97,
0x3c360000,0x3dce3db7,0x3e443e38,0x3e923e8c,0x3d093cb6,0x3dfc3de5,0x3e5c3e50,0x3e9f3e98,0x3d643d36,0x3e153e09,0x3e743e68,0x3eab3ea5,0x3da03d89,0x3e2c3e21,0x3e863e80,0x3eb83eb1,
0x3c4f0000,0x3dea3dd0,0x3e603e52,0x3ea83ea0,0x3d1c3ccf,0x3e0f3e02,0x3e7b3e6d,0x3eb63eaf,0x3d823d50,0x3e2a3e1d,0x3e8b3e84,0x3ec53ebd,0x3db63d9c,0x3e453e37,0x3e993e92,0x3ed43ecc,
0x3c680000,0x3e033de9,0x3e7c3e6d,0x3ebe3eb5,0x3d2e3ce9,0x3e213e12,0x3e8d3e86,0x3ece3ec6,0x3d923d69,0x3e3f3e30,0x3e9d3e95,0x3edf3ed7,0x3dcc3daf,0x3e5d3e4e,0x3ead3ea5,0x3ef13ee8,
0x3c810000,0x3e123e01,0x3e8c3e84,0x3ed43ecb,0x3d413d01,0x3e333e22,0x3e9e3e95,0x3ee73ede,0x3da13d81,0x3e543e44,0x3eaf3ea7,0x3efb3ef1,0x3de23dc2,0x3e763e65,0x3ec23eb9,0x3f083f03,
0x3c8d0000,0x3e203e0e,0x3e9b3e91,0x3eec3ee1,0x3d543d0d,0x3e453e32,0x3eae3ea4,0x3f013ef6,0x3db13d8e,0x3e6a3e57,0x3ec23eb8,0x3f0c3f06,0x3df93dd5,0x3e883e7c,0x3ed73ecc,0x3f183f12,
0x3c9a0000,0x3e2f3e1b,0x3ea93e9f,0x3f023ef8,0x3d673d1a,0x3e573e43,0x3ebf3eb4,0x3f0e3f08,0x3dc13d9a,0x3e7f3e6b,0x3ed53eca,0x3f1b3f15,0x3e073de8,0x3e943e8a,0x3eec3ee1,0x3f293f22,
0x3ca70000,0x3e3d3e28,0x3eb83ead,0x3f0f3f08,0x3d7a3d27,0x3e693e53,0x3ed03ec4,0x3f1d3f15,0x3dd13da7,0x3e8b3e7f,0x3ee93edc,0x3f2b3f24,0x3e133dfb,0x3ea13e96,0x3f013ef6,0x3f3b3f33,
0x3cb30000,0x3e4c3e35,0x3ec83ebb,0x3f1c3f14,0x3d863d33,0x3e7b3e63,0x3ee23ed5,0x3f2b3f23,0x3de13db4,0x3e963e89,0x3efd3eef,0x3f3c3f34,0x3e1e3e07,0x3eae3ea2,0x3f0d3f06,0x3f4e3f45,
0x3cc00000,0x3e5b3e42,0x3ed73ec9,0x3f293f21,0x3d903d40,0x3e873e74,0x3ef43ee5,0x3f3b3f32,0x3df13dc0,0x3ea13e94,0x3f093f01,0x3f4e3f45,0x3e293e11,0x3ebb3eae,0x3f193f11,0x3f633f58,
0x3f7f3f80,0x3f653f6b,0x3f2a3f33,0x3eaa3ec1,0x3f7c3f7e,0x3f593f60,0x3f163f20,0x3e753e92,0x3f773f7a,0x3f4b3f53,0x3f023f0c,0x3e143e45,0x3f6f3f73,0x3f3b3f44,0x3ed83eee,0x3d463dc6,
0x3f7c3f7e,0x3f5d3f63,0x3f213f2a,0x3e9f3eb5,0x3f773f7a,0x3f503f57,0x3f0e3f18,0x3e663e89,0x3f713f74,0x3f423f49,0x3ef43f04,0x3e0b3e38,0x3f683f6c,0x3f323f3a,0x3ecb3ee0,0x3d393db9,
0x3f773f7a,0x3f533f59,0x3f173f20,0x3e953eaa,0x3f713f74,0x3f463f4d,0x3f053f0f,0x3e563e80,0x3f693f6d,0x3f383f3f,0x3ee53ef8,0x3e013e2c,0x3f5f3f64,0x3f283f30,0x3ebe3ed2,0x3d2d3dad,
0x3f703f73,0x3f483f4f,0x3f0e3f16,0x3e8a3e9e,0x3f683f6c,0x3f3b3f42,0x3ef93f05,0x3e473e6e,0x3f5f3f64,0x3f2d3f34,0x3ed63ee8,0x3df03e20,0x3f543f5a,0x3f1e3f26,0x3eb13ec3,0x3d203da0,
0x3f663f6a,0x3f3d3f43,0x3f043f0c,0x3e803e92,0x3f5d3f62,0x3f303f36,0x3ee73ef8,0x3e383e5c,0x3f543f59,0x3f223f29,0x3ec63ed7,0x3ddd3e13,0x3f493f4e,0x3f133f1b,0x3ea33eb5,0x3d143d94,
0x3f5a3f5f,0x3f303f36,0x3ef33f01,0x3e6a3e86,0x3f513f56,0x3f233f2a,0x3ed53ee4,0x3e283e49,0x3f473f4c,0x3f163f1d,0x3eb63ec5,0x3dca3e07,0x3f3c3f42,0x3f083f0f,0x3e963ea6,0x3d073d87,
0x3f4d3f51,0x3f233f28,0x3ede3eec,0x3e553e73,0x3f433f48,0x3f163f1d,0x3ec23ed0,0x3e193e37,0x3f393f3e,0x3f0a3f10,0x3ea53eb4,0x3db83df4,0x3f2e3f34,0x3ef93f03,0x3e883e97,0x3cf53d75,
0x3f3d3f42,0x3f143f1a,0x3ec93ed5,0x3e3f3e5a,0x3f343f39,0x3f093f0f,0x3eaf3ebc,0x3e093e24,0x3f2a3f2f,0x3efa3f03,0x3e953ea2,0x3da53ddb,0x3f1f3f25,0x3ee23eee,0x3e753e88,0x3cdc3d5c,
0x3f2c3f31,0x3f053f0a,0x3eb33ebe,0x3e2a3e42,0x3f233f28,0x3ef53f00,0x3e9c3ea7,0x3df33e12,0x3f193f1e,0x3ee03eea,0x3e843e90,0x3d923dc2,0x3f0f3f14,0x3ec93ed4,0x3e593e71,0x3cc33d43,
0x3f193f1d,0x3eeb3ef4,0x3e9c3ea7,0x3e143e29,0x3f113f15,0x3ed83ee1,0x3e883e92,0x3dd43dfe,0x3f083f0c,0x3ec43ece,0x3e673e7c,0x3d7e3da9,0x3efd3f03,0x3eb13eba,0x3e3e3e53,0x3caa3d2a,
0x3f053f09,0x3eca3ed2,0x3e863e8f,0x3dfc3e10,0x3efb3f01,0x3eb93ec2,0x3e693e7a,0x3db43dd8,0x3eeb3ef3,0x3ea83eb1,0x3e453e57,0x3d593d90,0x3edb3ee3,0x3e973ea0,0x3e223e34,0x3c913d10,
0x3ee03ee6,0x3ea83eaf,0x3e5e3e6d,0x3dd13dee,0x3ed23ed9,0x3e9a3ea1,0x3e413e4f,0x3d953db3,0x3ec43ecb,0x3e8c3e93,0x3e233e32,0x3d333d6f,0x3eb63ebd,0x3e7b3e85,0x3e063e15,0x3c6f3cef,
0x3eb33eb8,0x3e863e8c,0x3e303e3b,0x3da53dbc,0x3ea83ead,0x3e753e80,0x3e193e24,0x3d6b3d8d,0x3e9c3ea2,0x3e5e3e6a,0x3e013e0d,0x3d0d3d3c,0x3e913e97,0x3e473e53,0x3dd43deb,0x3c3c3cbc,
0x3e843e89,0x3e453e4e,0x3e013e0a,0x3d723d8a,0x3e783e80,0x3e343e3d,0x3de03df1,0x3d2d3d4f,0x3e673e70,0x3e233e2c,0x3dbe3dcf,0x3ccf3d0a,0x3e563e5f,0x3e123e1b,0x3d9b3dad,0x3c0a3c8a,
0x3e2a3e2f,0x3dfc3e04,0x3da53db0,0x3d1a3d30,0x3e1f3e24,0x3de63df1,0x3d8f3d9a,0x3cdc3d04,0x3e143e19,0x3dd13ddb,0x3d723d84,0x3c843cb0,0x3e093e0e,0x3dbb3dc6,0x3d463d5c,0x3bb03c30,
0x3d923d97,0x3d593d62,0x3d0d3d17,0x3c843c97,0x3d893d8d,0x3d463d4f,0x3cf53d04,0x3c3c3c62,0x3d7e3d84,0x3d333d3c,0x3ccf3ce2,0x3be23c17,0x3d6b3d75,0x3d203d2a,0x3caa3cbc,0x3b173b97,
0xbcc3bcc9,0xbc91bc97,0xbc3cbc49,0xbbb0bbc9,0xbcb6bcbc,0xbc84bc8a,0xbc23bc30,0xbb7bbb97,0xbcaabcb0,0xbc6fbc7b,0xbc0abc17,0xbb17bb49,0xbc9dbca3,0xbc56bc62,0xbbe2bbfb,0xba49bac9,
0xbdf3bdfb,0xbdb4bdbc,0xbd6bbd7b,0xbcdcbcfb,0xbde3bdeb,0xbda5bdad,0xbd4cbd5c,0xbc9dbcbc,0xbdd4bddb,0xbd95bd9d,0xbd2dbd3c,0xbc3cbc7b,0xbdc4bdcc,0xbd85bd8d,0xbd0dbd1d,0xbb7bbbfb,
0xbe59be60,0xbe22be29,0xbdd4bde2,0xbd46bd62,0xbe4cbe53,0xbe14be1b,0xbdb8bdc6,0xbd0dbd2a,0xbe3ebe45,0xbe06be0d,0xbd9bbda9,0xbcaabce2,0xbe30be37,0xbdf0bdfe,0xbd7ebd8d,0xbbe2bc62,
0xbe9cbea1,0xbe69be73,0xbe19be23,0xbd8fbda3,0xbe92be97,0xbe55be5f,0xbe04be0e,0xbd4cbd75,0xbe88be8d,0xbe41be4b,0xbde0bdf4,0xbcf5bd23,0xbe7dbe83,0xbe2dbe37,0xbdb8bdcc,0xbc23bca3,
0xbec9becf,0xbe97be9e,0xbe47be54,0xbdbbbdd5,0xbebdbec3,0xbe8abe91,0xbe2dbe3a,0xbd85bda0,0xbeb1beb7,0xbe7bbe84,0xbe12be20,0xbd20bd56,0xbea4beaa,0xbe61be6e,0xbdf0be05,0xbc56bcd6,
0xbef5befc,0xbeb9bec1,0xbe75be82,0xbde6be04,0xbee7beee,0xbeaabeb2,0xbe55be65,0xbda5bdc6,0xbed8bedf,0xbe9abea2,0xbe34be45,0xbd46bd84,0xbec9bed0,0xbe8abe92,0xbe14be24,0xbc84bd04,
0xbf0fbf13,0xbedbbee3,0xbe91be9b,0xbe09be1c,0xbf07bf0b,0xbec9bed2,0xbe7dbe88,0xbdc4bdeb,0xbefdbf03,0xbeb6bec0,0xbe56be6a,0xbd6bbd9d,0xbeecbef5,0xbea4bead,0xbe30be43,0xbc9dbd1d,
0xbf23bf27,0xbefbbf02,0xbea8beb2,0xbe1fbe35,0xbf1abf1e,0xbee7bef1,0xbe92be9d,0xbde3be08,0xbf11bf15,0xbed2bedc,0xbe78be87,0xbd89bdb6,0xbf07bf0c,0xbebdbec8,0xbe4cbe62,0xbcb6bd36,
0xbf35bf39,0xbf0dbf12,0xbebebeca,0xbe34be4e,0xbf2bbf30,0xbf02bf07,0xbea5beb2,0xbe01be1b,0xbf22bf27,0xbeedbef8,0xbe8dbe99,0xbd9bbdcf,0xbf17bf1d,0xbed6bee1,0xbe67be80,0xbccfbd4f,
0xbf45bf4a,0xbf1bbf21,0xbed3bee1,0xbe4abe66,0xbf3cbf41,0xbf10bf16,0xbeb9bec6,0xbe11be2e,0xbf32bf37,0xbf03bf0a,0xbe9dbeab,0xbdaebde8,0xbf27bf2c,0xbeeebefa,0xbe81be8f,0xbce8bd68,
0xbf54bf58,0xbf29bf2f,0xbee9bef7,0xbe60be7f,0xbf4abf4f,0xbf1dbf23,0xbeccbeda,0xbe20be40,0xbf40bf45,0xbf10bf17,0xbeaebebd,0xbdc1be00,0xbf35bf3b,0xbf02bf09,0xbe8fbe9e,0xbd01bd81,
0xbf61bf65,0xbf37bf3d,0xbefdbf06,0xbe75be8c,0xbf58bf5c,0xbf2abf30,0xbedebeee,0xbe30be53,0xbf4ebf53,0xbf1cbf23,0xbebebece,0xbdd4be0d,0xbf42bf48,0xbf0ebf15,0xbe9cbead,0xbd0dbd8d,
0xbf6bbf6f,0xbf43bf49,0xbf09bf11,0xbe85be98,0xbf63bf67,0xbf36bf3c,0xbef0bf01,0xbe3fbe65,0xbf59bf5e,0xbf28bf2f,0xbecebedf,0xbde6be19,0xbf4fbf54,0xbf19bf20,0xbeaabebc,0xbd1abd9a,
0xbf74bf77,0xbf4ebf54,0xbf13bf1b,0xbe90bea4,0xbf6dbf70,0xbf41bf48,0xbf01bf0a,0xbe4fbe77,0xbf64bf68,0xbf33bf3a,0xbeddbef0,0xbdf9be26,0xbf5abf5f,0xbf23bf2b,0xbeb7beca,0xbd26bda6,
0xbf7abf7c,0xbf58bf5e,0xbf1cbf25,0xbe9abeaf,0xbf74bf77,0xbf4bbf52,0xbf0abf13,0xbe5ebe85,0xbf6dbf71,0xbf3dbf44,0xbeedbf00,0xbe06be32,0xbf63bf68,0xbf2dbf35,0xbec4bed9,0xbd33bdb3,
0xbf7ebf7f,0xbf61bf67,0xbf25bf2e,0xbea5bebb,0xbf7abf7c,0xbf55bf5b,0xbf12bf1c,0xbe6dbe8e,0xbf74bf77,0xbf47bf4e,0xbefcbf08,0xbe0fbe3f,0xbf6cbf70,0xbf37bf3f,0xbed1bee7,0xbd40bdbf,
0xbd468000,0xbed8bec1,0xbf3bbf33,0xbf6fbf6b,0xbe14bdc6,0xbf02beee,0xbf4bbf44,0xbf77bf73,0xbe75be45,0xbf16bf0c,0xbf59bf53,0xbf7cbf7a,0xbeaabe92,0xbf2abf20,0xbf65bf60,0xbf7fbf7e,
0xbd398000,0xbecbbeb5,0xbf32bf2a,0xbf68bf63,0xbe0bbdb9,0xbef4bee0,0xbf42bf3a,0xbf71bf6c,0xbe66be38,0xbf0ebf04,0xbf50bf49,0xbf77bf74,0xbe9fbe89,0xbf21bf18,0xbf5dbf57,0xbf7cbf7a,
0xbd2d8000,0xbebebeaa,0xbf28bf20,0xbf5fbf59,0xbe01bdad,0xbee5bed2,0xbf38bf30,0xbf69bf64,0xbe56be2c,0xbf05bef8,0xbf46bf3f,0xbf71bf6d,0xbe95be80,0xbf17bf0f,0xbf53bf4d,0xbf77bf74,
0xbd208000,0xbeb1be9e,0xbf1ebf16,0xbf54bf4f,0xbdf0bda0,0xbed6bec3,0xbf2dbf26,0xbf5fbf5a,0xbe47be20,0xbef9bee8,0xbf3bbf34,0xbf68bf64,0xbe8abe6e,0xbf0ebf05,0xbf48bf42,0xbf70bf6c,
0xbd148000,0xbea3be92,0xbf13bf0c,0xbf49bf43,0xbdddbd94,0xbec6beb5,0xbf22bf1b,0xbf54bf4e,0xbe38be13,0xbee7bed7,0xbf30bf29,0xbf5dbf59,0xbe80be5c,0xbf04bef8,0xbf3dbf36,0xbf66bf62,
0xbd078000,0xbe96be86,0xbf08bf01,0xbf3cbf36,0xbdcabd87,0xbeb6bea6,0xbf16bf0f,0xbf47bf42,0xbe28be07,0xbed5bec5,0xbf23bf1d,0xbf51bf4c,0xbe6abe49,0xbef3bee4,0xbf30bf2a,0xbf5abf56,
0xbcf58000,0xbe88be73,0xbef9beec,0xbf2ebf28,0xbdb8bd75,0xbea5be97,0xbf0abf03,0xbf39bf34,0xbe19bdf4,0xbec2beb4,0xbf16bf10,0xbf43bf3e,0xbe55be37,0xbedebed0,0xbf23bf1d,0xbf4dbf48,
0xbcdc8000,0xbe75be5a,0xbee2bed5,0xbf1fbf1a,0xbda5bd5c,0xbe95be88,0xbefabeee,0xbf2abf25,0xbe09bddb,0xbeafbea2,0xbf09bf03,0xbf34bf2f,0xbe3fbe24,0xbec9bebc,0xbf14bf0f,0xbf3dbf39,
0xbcc38000,0xbe59be42,0xbec9bebe,0xbf0fbf0a,0xbd92bd43,0xbe84be71,0xbee0bed4,0xbf19bf14,0xbdf3bdc2,0xbe9cbe90,0xbef5beea,0xbf23bf1e,0xbe2abe12,0xbeb3bea7,0xbf05bf00,0xbf2cbf28,
0xbcaa8000,0xbe3ebe29,0xbeb1bea7,0xbefdbef4,0xbd7ebd2a,0xbe67be53,0xbec4beba,0xbf08bf03,0xbdd4bda9,0xbe88be7c,0xbed8bece,0xbf11bf0c,0xbe14bdfe,0xbe9cbe92,0xbeebbee1,0xbf19bf15,
0xbc918000,0xbe22be10,0xbe97be8f,0xbedbbed2,0xbd59bd10,0xbe45be34,0xbea8bea0,0xbeebbee3,0xbdb4bd90,0xbe69be57,0xbeb9beb1,0xbefbbef3,0xbdfcbdd8,0xbe86be7a,0xbecabec2,0xbf05bf01,
0xbc6f8000,0xbe06bdee,0xbe7bbe6d,0xbeb6beaf,0xbd33bcef,0xbe23be15,0xbe8cbe85,0xbec4bebd,0xbd95bd6f,0xbe41be32,0xbe9abe93,0xbed2becb,0xbdd1bdb3,0xbe5ebe4f,0xbea8bea1,0xbee0bed9,
0xbc3c8000,0xbdd4bdbc,0xbe47be3b,0xbe91be8c,0xbd0dbcbc,0xbe01bdeb,0xbe5ebe53,0xbe9cbe97,0xbd6bbd3c,0xbe19be0d,0xbe75be6a,0xbea8bea2,0xbda5bd8d,0xbe30be24,0xbe86be80,0xbeb3bead,
0xbc0a8000,0xbd9bbd8a,0xbe12be0a,0xbe56be4e,0xbccfbc8a,0xbdbebdad,0xbe23be1b,0xbe67be5f,0xbd2dbd0a,0xbde0bdcf,0xbe34be2c,0xbe78be70,0xbd72bd4f,0xbe01bdf1,0xbe45be3d,0xbe84be80,
0xbbb08000,0xbd46bd30,0xbdbbbdb0,0xbe09be04,0xbc84bc30,0xbd72bd5c,0xbdd1bdc6,0xbe14be0e,0xbcdcbcb0,0xbd8fbd84,0xbde6bddb,0xbe1fbe19,0xbd1abd04,0xbda5bd9a,0xbdfcbdf1,0xbe2abe24,
0xbb178000,0xbcaabc97,0xbd20bd17,0xbd6bbd62,0xbbe2bb97,0xbccfbcbc,0xbd33bd2a,0xbd7ebd75,0xbc3cbc17,0xbcf5bce2,0xbd46bd3c,0xbd89bd84,0xbc84bc62,0xbd0dbd04,0xbd59bd4f,0xbd92bd8d,
0x3a490000,0x3be23bc9,0x3c563c49,0x3c9d3c97,0x3b173ac9,0x3c0a3bfb,0x3c6f3c62,0x3caa3ca3,0x3b7b3b49,0x3c233c17,0x3c843c7b,0x3cb63cb0,0x3bb03b97,0x3c3c3c30,0x3c913c8a,0x3cc33cbc,
0x3b7b0000,0x3d0d3cfb,0x3d853d7b,0x3dc43dbc,0x3c3c3bfb,0x3d2d3d1d,0x3d953d8d,0x3dd43dcc,0x3c9d3c7b,0x3d4c3d3c,0x3da53d9d,0x3de33ddb,0x3cdc3cbc,0x3d6b3d5c,0x3db43dad,0x3df33deb,
0x3be20000,0x3d7e3d62,0x3df03de2,0x3e303e29,0x3caa3c62,0x3d9b3d8d,0x3e063dfe,0x3e3e3e37,0x3d0d3ce2,0x3db83da9,0x3e143e0d,0x3e4c3e45,0x3d463d2a,0x3dd43dc6,0x3e223e1b,0x3e593e53,
0x3c230000,0x3db83da3,0x3e2d3e23,0x3e7d3e73,0x3cf53ca3,0x3de03dcc,0x3e413e37,0x3e883e83,0x3d4c3d23,0x3e043df4,0x3e553e4b,0x3e923e8d,0x3d8f3d75,0x3e193e0e,0x3e693e5f,0x3e9c3e97,
0x3c560000,0x3df03dd5,0x3e613e54,0x3ea43e9e,0x3d203cd6,0x3e123e05,0x3e7b3e6e,0x3eb13eaa,0x3d853d56,0x3e2d3e20,0x3e8a3e84,0x3ebd3eb7,0x3dbb3da0,0x3e473e3a,0x3e973e91,0x3ec93ec3,
0x3c840000,0x3e143e04,0x3e8a3e82,0x3ec93ec1,0x3d463d04,0x3e343e24,0x3e9a3e92,0x3ed83ed0,0x3da53d84,0x3e553e45,0x3eaa3ea2,0x3ee73edf,0x3de63dc6,0x3e753e65,0x3eb93eb2,0x3ef53eee,
0x3c9d0000,0x3e303e1c,0x3ea43e9b,0x3eec3ee3,0x3d6b3d1d,0x3e563e43,0x3eb63ead,0x3efd3ef5,0x3dc43d9d,0x3e7d3e6a,0x3ec93ec0,0x3f073f03,0x3e093deb,0x3e913e88,0x3edb3ed2,0x3f0f3f0b,
0x3cb60000,0x3e4c3e35,0x3ebd3eb2,0x3f073f02,0x3d893d36,0x3e783e62,0x3ed23ec8,0x3f113f0c,0x3de33db6,0x3e923e87,0x3ee73edc,0x3f1a3f15,0x3e1f3e08,0x3ea83e9d,0x3efb3ef1,0x3f233f1e,
0x3ccf0000,0x3e673e4e,0x3ed63eca,0x3f173f12,0x3d9b3d4f,0x3e8d3e80,0x3eed3ee1,0x3f223f1d,0x3e013dcf,0x3ea53e99,0x3f023ef8,0x3f2b3f27,0x3e343e1b,0x3ebe3eb2,0x3f0d3f07,0x3f353f30,
0x3ce80000,0x3e813e66,0x3eee3ee1,0x3f273f21,0x3dae3d68,0x3e9d3e8f,0x3f033efa,0x3f323f2c,0x3e113de8,0x3eb93eab,0x3f103f0a,0x3f3c3f37,0x3e4a3e2e,0x3ed33ec6,0x3f1b3f16,0x3f453f41,
0x3d010000,0x3e8f3e7f,0x3f023ef7,0x3f353f2f,0x3dc13d81,0x3eae3e9e,0x3f103f09,0x3f403f3b,0x3e203e00,0x3ecc3ebd,0x3f1d3f17,0x3f4a3f45,0x3e603e40,0x3ee93eda,0x3f293f23,0x3f543f4f,
0x3d0d0000,0x3e9c3e8c,0x3f0e3f06,0x3f423f3d,0x3dd43d8d,0x3ebe3ead,0x3f1c3f15,0x3f4e3f48,0x3e303e0d,0x3ede3ece,0x3f2a3f23,0x3f583f53,0x3e753e53,0x3efd3eee,0x3f373f30,0x3f613f5c,
0x3d1a0000,0x3eaa3e98,0x3f193f11,0x3f4f3f49,0x3de63d9a,0x3ece3ebc,0x3f283f20,0x3f593f54,0x3e3f3e19,0x3ef03edf,0x3f363f2f,0x3f633f5e,0x3e853e65,0x3f093f01,0x3f433f3c,0x3f6b3f67,
0x3d260000,0x3eb73ea4,0x3f233f1b,0x3f5a3f54,0x3df93da6,0x3edd3eca,0x3f333f2b,0x3f643f5f,0x3e4f3e26,0x3f013ef0,0x3f413f3a,0x3f6d3f68,0x3e903e77,0x3f133f0a,0x3f4e3f48,0x3f743f70,
0x3d330000,0x3ec43eaf,0x3f2d3f25,0x3f633f5e,0x3e063db3,0x3eed3ed9,0x3f3d3f35,0x3f6d3f68,0x3e5e3e32,0x3f0a3f00,0x3f4b3f44,0x3f743f71,0x3e9a3e85,0x3f1c3f13,0x3f583f52,0x3f7a3f77,
0x3d400000,0x3ed13ebb,0x3f373f2e,0x3f6c3f67,0x3e0f3dbf,0x3efc3ee7,0x3f473f3f,0x3f743f70,0x3e6d3e3f,0x3f123f08,0x3f553f4e,0x3f7a3f77,0x3ea53e8e,0x3f253f1c,0x3f613f5b,0x3f7e3f7c
};
#define DBG_END(z)
#define TS(i)
#define TZ(z, i)

struct Params {
  alignas(64) CUtensorMap x_g1, w1_a, w1_b2, w1_b1, k, v, w1_cs, kvz, h_st, h_st2, w2, h_ld, y_ld, x_ep, out_st, f_ld, y_st;
  const bf16 *x, *shift_k, *ssm_k, *ssm_D, *b1, *b2, *w2p, *w1p;
  bf16* kvZ;
  const uint32_t* tab;
  uint2 *stats, *cs;
  unsigned* flags;
  unsigned zero;
  unsigned char cnt[72];
  uchar4 map[NCTA];
};

constexpr int G1_W = 28672, G1_X = 16384, G1_NST = 4, OFF_X = G1_NST * G1_W;
constexpr int G2_STAGE = G1_W, G2_B = 16384, G2_NST = 6;
constexpr int CS_STAGE = 57344;
constexpr int RING = G1_NST * (G1_W + G1_X);
constexpr int OFF_C = RING;
constexpr int OFF_SR = OFF_C;
constexpr int OFF_DFT = OFF_C, OFF_G = OFF_C + 8192;
constexpr int KV_SLOT = 35 * 256, KV_V = 19 * 256;
constexpr int OFF_KVS = OFF_C + 20480, OFF_KV = OFF_KVS + 4096;
constexpr int OFF_KV4 = OFF_C + 20480 - KV_SLOT;
constexpr int OFF_T0 = K4E == 4 ? OFF_C + 28672 : K4E % 3 ? OFF_KV : OFF_C + 12288, OFF_T1 = OFF_C + (K4E == 4 ? 20480 : 34816), OFF_T2 = K4E == 4 ? OFF_C + 36864 : K4E == 2 ? OFF_C + 12288 : K4E == 1 ? OFF_T0 : OFF_C + 20480, OFF_T3 = OFF_X + 57344, OFF_T4 = K4E == 2 ? OFF_T0 : OFF_C + 12288;
constexpr int OFF_Y0 = K4E == 4 ? OFF_T0 : K4E % 3 ? OFF_KVS : OFF_C + 28672;
constexpr int OFF_XT = OFF_C + (PRE == 2 ? 28672 : 20480), XT_STEP = PRE == 2 ? 10240 : 13312, OFF_YT = OFF_C;
constexpr int OFF_EXT = 224256;
constexpr int OFF_ST1 = OFF_EXT + 3584;
constexpr int OFF_ST2 = OFF_ST1 + 2048;
constexpr int OFF_MISC = OFF_ST2 + 800;
constexpr int OFF_BAR = OFF_MISC + 32;
enum { B_FULL1 = 0  , B_KV = 4  , B_STAT = 6, B_FIRST = 7, B_EMPTY1 = 7  , B_FULL2 = 11  , B_EMPTY2 = 17  , B_G1FREE = 23, B_CX = 24  , B_RD = 29  ,
       B_EPOCH = 34, B_SKEW = 35, B_TAB = 36, B_EP = 37, B_EPY = 38, B_KVS = 39  , B_GO = 42, B_DONE = 43, B_STATFREE = 44, B_HS = 45  ,
       B_KVR = 53, B_LATE = 54, B_DFT = 55, B_HB = 56, B_H1 = 57, B_VD = 58, B_RT = 59, B_KV4 = 60, B_KVC = 61, B_DBG = 62, B_BAD = 63, B_XF = 64, B_T2 = 65, B_PF = 66  , B_COUNT = MC ? 72 : 66 };
constexpr int OFF_POLL = OFF_BAR + B_COUNT * 8;
constexpr int OFF_DBG = OFF_POLL + 192;
constexpr int SMEM_BYTES = OFF_DBG + (DBG_TIME ? 768 : 0);
static_assert(SMEM_BYTES <= 232448 && OFF_POLL % 16 == 0, "smem");
static_assert(OFF_XT + XT_STEP + 10240 <= (PRE == 2 ? OFF_ST2 : OFF_EXT) && (PRE != 2 || OFF_T2 + 8192 <= OFF_XT) && OFF_KV + 2 * KV_SLOT <= OFF_EXT && (K4E == 4 ? OFF_T2 + 8192 <= OFF_ST1 && OFF_T0 + 8192 <= OFF_KV + KV_SLOT + KV_V : OFF_T1 + 8192 <= OFF_EXT && OFF_T1 >= OFF_KV + KV_SLOT && OFF_T2 + 8192 <= OFF_KV + KV_SLOT) && OFF_KV4 % 128 == 0, "layout");
static_assert(OFF_EXT % 1024 == 0 && OFF_XT % 1024 == 0 && XT_STEP % 1024 == 0 && OFF_T1 % 1024 == 0 && 5 * G2_STAGE + 26624 <= OFF_T3 && 3 * CS_STAGE <= RING, "layout");

#define DEV __device__ __forceinline__
#define HD __host__ __device__ constexpr
DEV uint32_t smem_u32(const void* p) { return (uint32_t)__cvta_generic_to_shared(p); }
DEV uint64_t make_desc(uint32_t addr, uint32_t lbo, uint32_t sbo, uint32_t swz) {
  uint64_t d;
  asm volatile("mov.b64 %0, {%1, %2};" : "=l"(d) : "r"(((addr & 0x3FFFF) >> 4) | ((lbo >> 4) << 16)), "r"((sbo >> 4) | (swz << 30)));
  return d;
}
DEV void wg_fence() { asm volatile("wgmma.fence.sync.aligned;" ::: "memory"); }
DEV void wg_commit() { asm volatile("wgmma.commit_group.sync.aligned;" ::: "memory"); }
template <int n> DEV void wg_wait() { asm volatile("wgmma.wait_group.sync.aligned %0;" ::"n"(n) : "memory"); }
DEV uint32_t crank() { uint32_t r; asm("mov.u32 %0, %%cluster_ctarank;" : "=r"(r)); return r; }
#define MCA 4
DEV uint32_t own(uint32_t a) { return MC && !(MCA & 4) ? a + (crank() << 24) : a; }
DEV uint32_t owns(uint32_t a) { return MCA & 1 ? own(a) : a; }
DEV uint32_t ownb(uint32_t a) { return MCA & 2 ? own(a) : a; }
DEV void mbar_init(uint32_t bar, int cnt) { asm volatile("mbarrier.init.shared::cta.b64 [%0], %1;" ::"r"(ownb(bar)), "r"(cnt) : "memory"); }
DEV void mbar_expect(uint32_t bar, int bytes) { asm volatile("mbarrier.arrive.expect_tx.shared::cta.b64 _, [%0], %1;" ::"r"(ownb(bar)), "r"(bytes) : "memory"); }
DEV void mbar_arrive(uint32_t bar) { asm volatile("mbarrier.arrive.shared::cta.b64 _, [%0];" ::"r"(ownb(bar)) : "memory"); }
DEV void mbar_wait(uint32_t bar, uint32_t parity) {
  asm volatile("{\n.reg .pred p;\nW: mbarrier.try_wait.parity.shared::cta.b64 p, [%0], %1;\n@p bra X;\nbra W;\nX:\n}" ::"r"(ownb(bar)), "r"(parity) : "memory");
}
DEV bool mbar_test(uint32_t bar, uint32_t parity) {
  uint32_t r;
  asm volatile("{\n.reg .pred p;\nmbarrier.test_wait.parity.shared::cta.b64 p, [%1], %2;\nselp.u32 %0, 1, 0, p;\n}" : "=r"(r) : "r"(ownb(bar)), "r"(parity) : "memory");
  return __any_sync(0xffffffffu, r);
}
DEV void mbar_wait_b(uint32_t bar, uint32_t parity) {
  asm volatile("{\n.reg .pred p;\n.reg .u32 i;\nmov.u32 i, 0;\n"
               "W: mbarrier.try_wait.parity.shared::cta.b64 p, [%0], %1;\n@p bra X;\nadd.u32 i, i, 1;\nsetp.lt.u32 p, i, 262144;\n@p bra W;\ntrap;\nX:\n}"
               ::"r"(ownb(bar)), "r"(parity) : "memory");
}
template <int G> DEV void grid_wait() {
  if (G) asm volatile("{\n.reg .pred p;\n.reg .u32 a, b;\nmov.u32 a, %%clock;\nW: mov.u32 b, %%clock;\nxor.b32 b, b, a;\nsetp.lt.u32 p, b, %0;\n@p bra W;\n}" ::"n"(G) : "memory");
}
DEV void clk_wait(int n) {
  if (n) asm volatile("{\n.reg .pred p;\n.reg .u32 a, b;\nmov.u32 a, %%clock;\nW: mov.u32 b, %%clock;\nsub.u32 b, b, a;\nsetp.lt.u32 p, b, %0;\n@p bra W;\n}" ::"r"(n) : "memory");
}
DEV void trap_above(int n, int lim) { asm volatile("{\n.reg .pred p;\nsetp.gt.s32 p, %0, %1;\n@p trap;\n}" ::"r"(n), "r"(lim)); }
DEV unsigned flag_load(const unsigned* p) {
  unsigned v;
  asm volatile("ld.acquire.gpu.global.u32 %0, [%1];" : "=r"(v) : "l"(p) : "memory");
  return v;
}
template <bool BOUNDED> DEV void flag_wait(const unsigned* p, unsigned target) {
#pragma unroll 1
  for (int i = 0; !BOUNDED || i < (1 << 22); i++)
    if ((int)(flag_load(p) - target) >= 0) return;
  __trap();
}
template <bool BOUNDED> DEV void flag_poll(const unsigned* p, unsigned target, uint32_t buf) {
  asm volatile("{\n.reg .pred q;\n.reg .u32 a, t;\n"
               "cp.async.wait_group 0;\ncp.async.cg.shared.global [%5+0], [%0], 16;\ncp.async.commit_group;\nmov.u32 t, %%clock;\n"
               "W1: mov.u32 a, %%clock;\nsub.u32 a, a, t;\nsetp.lt.u32 q, a, %2;\n@q bra W1;\ncp.async.cg.shared.global [%5+16], [%0], 16;\ncp.async.commit_group;\n"
               "W2: mov.u32 a, %%clock;\nsub.u32 a, a, t;\nsetp.lt.u32 q, a, %3;\n@q bra W2;\ncp.async.cg.shared.global [%5+32], [%0], 16;\ncp.async.commit_group;\nmov.u32 t, 0;\n"
               "L: cp.async.wait_group 2;\nld.volatile.shared.u32 a, [%5+0];\nsub.u32 a, a, %1;\nsetp.ge.s32 q, a, 0;\n@q bra X;\ncp.async.cg.shared.global [%5+0], [%0], 16;\ncp.async.commit_group;\n"
               "cp.async.wait_group 2;\nld.volatile.shared.u32 a, [%5+16];\nsub.u32 a, a, %1;\nsetp.ge.s32 q, a, 0;\n@q bra X;\ncp.async.cg.shared.global [%5+16], [%0], 16;\ncp.async.commit_group;\n"
               "cp.async.wait_group 2;\nld.volatile.shared.u32 a, [%5+32];\nsub.u32 a, a, %1;\nsetp.ge.s32 q, a, 0;\n@q bra X;\ncp.async.cg.shared.global [%5+32], [%0], 16;\ncp.async.commit_group;\n"
               "add.u32 t, t, %4;\nsetp.lt.u32 q, t, 4194304;\n@q bra L;\ntrap;\nX:\n}"
               ::"l"(p), "r"(target), "n"(PD), "n"(2 * PD), "n"(BOUNDED ? 1 : 0), "r"(buf) : "memory");
}
DEV void tag_store(uint2* p, float a, float b, unsigned ep) {
  const unsigned long long v = (unsigned long long)__float_as_uint(a) | ((unsigned long long)((__float_as_uint(b) & ~255u) | (ep & 255u)) << 32);
  asm volatile("st.relaxed.gpu.global.u64 [%0], %1;" ::"l"(p), "l"(v) : "memory");
}
DEV uint2 tag_load(const uint2* p) { uint2 v; asm volatile("{\n.reg .b64 t;\nld.relaxed.gpu.global.b64 t, [%2];\nmov.b64 {%0,%1}, t;\n}" : "=r"(v.x), "=r"(v.y) : "l"(p) : "memory"); return v; }
template <int N> DEV void tag_wait(const uint2* const (&p)[N], uint2 (&v)[N], unsigned ep) {
#pragma unroll 1
  for (;;) {
    unsigned bad = 0;
#pragma unroll
    for (int j = 0; j < N; j++) bad |= v[j].y ^ ep;
    if (!__any_sync(0xffffffffu, (bad & 255u) != 0)) break;
#pragma unroll
    for (int j = 0; j < N; j++) v[j] = tag_load(p[j]);
  }
#pragma unroll
  for (int j = 0; j < N; j++) v[j].y &= ~255u;
}
template <int N> DEV void tag_wait2(const uint2* const (&p)[N], uint2 (&v)[N], unsigned ep) {
  uint2 w[N];
  clk_wait(TD);
#pragma unroll
  for (int j = 0; j < N; j++) w[j] = tag_load(p[j]);
#pragma unroll 1
  for (;;) {
    unsigned bad = 0;
#pragma unroll
    for (int j = 0; j < N; j++) bad |= v[j].y ^ ep;
    if (!__any_sync(0xffffffffu, (bad & 255u) != 0)) break;
#pragma unroll
    for (int j = 0; j < N; j++) v[j] = tag_load(p[j]);
    bad = 0;
#pragma unroll
    for (int j = 0; j < N; j++) bad |= w[j].y ^ ep;
    if (!__any_sync(0xffffffffu, (bad & 255u) != 0)) {
#pragma unroll
      for (int j = 0; j < N; j++) v[j] = w[j];
      break;
    }
#pragma unroll
    for (int j = 0; j < N; j++) w[j] = tag_load(p[j]);
  }
#pragma unroll
  for (int j = 0; j < N; j++) v[j].y &= ~255u;
}
#define REL 4
DEV void pub_fence(int bit) { if (REL & bit) asm volatile("fence.acq_rel.gpu;" ::: "memory"); }
DEV void flag_add_rlx(unsigned* p, unsigned n) { asm volatile("red.relaxed.gpu.global.add.u32 [%0], %1;" ::"l"(p), "r"(n) : "memory"); }
DEV void flag_add_all(unsigned* p, int n) {
#pragma unroll
  for (int r = 0; r < n; r++) flag_add_rlx(p + 32 * r, 1);
}
DEV void fence_async_smem() { asm volatile("fence.proxy.async.shared::cta;" ::: "memory"); }
#define RF 15
DEV void wfence(int bit) { if (!(RF & bit)) fence_async_smem(); }
DEV void rfence(int bit) { if ((RF & bit) && !(RF & 16)) fence_async_smem(); }
DEV void fence_async_global() { asm volatile("fence.proxy.async.global;" ::: "memory"); }
DEV void bar_sync(int id) { asm volatile("bar.sync %0, 128;" ::"r"(id) : "memory"); }
DEV bool elect() {
  uint32_t p;
  asm volatile("{\n.reg .pred p;\nelect.sync _|p, 0xffffffff;\nselp.u32 %0, 1, 0, p;\n}" : "=r"(p));
  return p;
}
DEV void warp_arrive(uint32_t bar) { __syncwarp(); if (elect()) mbar_arrive(bar); }
DEV void bulk_g2s(uint32_t dst, const void* src, int bytes, uint32_t bar) {
  asm volatile("cp.async.bulk.shared::cluster.global.mbarrier::complete_tx::bytes [%0], [%1], %2, [%3];" ::"r"(own(dst)), "l"(src), "r"(bytes), "r"(own(bar)) : "memory");
}
DEV void bulk_s2g(void* dst, uint32_t src, int bytes) { asm volatile("cp.async.bulk.global.shared::cta.bulk_group [%0], [%1], %2;" ::"l"(dst), "r"(owns(src)), "r"(bytes) : "memory"); }
DEV void bulk_prefetch(const void* src, int bytes) { asm volatile("cp.async.bulk.prefetch.L2.global [%0], %1;" ::"l"(src), "r"(bytes) : "memory"); }
DEV void tma2d(uint32_t dst, const CUtensorMap* m, int c0, int c1, uint32_t bar) {
  asm volatile("cp.async.bulk.tensor.2d.shared::cluster.global.mbarrier::complete_tx::bytes [%0], [%1, {%3, %4}], [%2];" ::"r"(own(dst)), "l"(m), "r"(own(bar)), "r"(c0), "r"(c1) : "memory");
}
DEV void tma3d(uint32_t dst, const CUtensorMap* m, int c0, int c1, int c2, uint32_t bar) {
  asm volatile("cp.async.bulk.tensor.3d.shared::cluster.global.mbarrier::complete_tx::bytes [%0], [%1, {%3, %4, %5}], [%2];" ::"r"(own(dst)), "l"(m), "r"(own(bar)), "r"(c0), "r"(c1), "r"(c2) : "memory");
}
DEV void tma3d_mc(uint32_t dst, const CUtensorMap* m, int c0, int c1, int c2, uint32_t bar) {
  asm volatile("cp.async.bulk.tensor.3d.shared::cluster.global.mbarrier::complete_tx::bytes.multicast::cluster [%0], [%1, {%3, %4, %5}], [%2], %6;" ::"r"(own(dst)), "l"(m), "r"(own(bar)), "r"(c0), "r"(c1), "r"(c2), "h"((uint16_t)3) : "memory");
}
DEV uint32_t lds_peer(uint32_t a) {
  uint32_t v;
  asm volatile("{\n.reg .b32 a;\nmapa.shared::cluster.u32 a, %1, %2;\nld.shared::cluster.u32 %0, [a];\n}" : "=r"(v) : "r"(own(a)), "r"(crank() ^ 1) : "memory");
  return v;
}
DEV void st_peer(uint32_t a, uint32_t v, uint32_t bar) {
  asm volatile("{\n.reg .b32 a, b;\nmapa.shared::cluster.u32 a, %0, %3;\nmapa.shared::cluster.u32 b, %2, %3;\nst.async.weak.shared::cluster.mbarrier::complete_tx::bytes.u32 [a], %1, [b];\n}"
               ::"r"(own(a)), "r"(v), "r"(own(bar)), "r"(crank() ^ 1) : "memory");
}
DEV void mbar_arrive_peer(uint32_t bar) {
  asm volatile("{\n.reg .b32 a;\nmapa.shared::cluster.u32 a, %0, %1;\nmbarrier.arrive.shared::cluster.b64 _, [a];\n}" ::"r"(own(bar)), "r"(crank() ^ 1) : "memory");
}
DEV void tma2d_st(const CUtensorMap* m, int c0, int c1, uint32_t src) {
  asm volatile("cp.async.bulk.tensor.2d.global.shared::cta.bulk_group [%0, {%2, %3}], [%1];" ::"l"(m), "r"(owns(src)), "r"(c0), "r"(c1) : "memory");
}
DEV void bulk_commit() { asm volatile("cp.async.bulk.commit_group;" ::: "memory"); }
DEV void bulk_wait_read() { asm volatile("cp.async.bulk.wait_group.read 0;" ::: "memory"); }
DEV void bulk_wait_all() { asm volatile("cp.async.bulk.wait_group 0;" ::: "memory"); }
DEV void prefetch_map(const CUtensorMap* m) { asm volatile("prefetch.tensormap [%0];" ::"l"(m) : "memory"); }
DEV uint32_t lds32(uint32_t a) { uint32_t v; asm volatile("ld.shared.b32 %0, [%1];" : "=r"(v) : "r"(a) : "memory"); return v; }
DEV uint2 lds64(uint32_t a) { uint2 v; asm volatile("ld.shared.v2.b32 {%0,%1}, [%2];" : "=r"(v.x), "=r"(v.y) : "r"(a) : "memory"); return v; }
DEV uint4 lds128(uint32_t a) { uint4 v; asm volatile("ld.shared.v4.b32 {%0,%1,%2,%3}, [%4];" : "=r"(v.x), "=r"(v.y), "=r"(v.z), "=r"(v.w) : "r"(a) : "memory"); return v; }
DEV void sts32(uint32_t a, uint32_t v) { asm volatile("st.shared.b32 [%0], %1;" ::"r"(a), "r"(v) : "memory"); }
DEV void sts128(uint32_t a, uint4 v) { asm volatile("st.shared.v4.b32 [%0], {%1,%2,%3,%4};" ::"r"(a), "r"(v.x), "r"(v.y), "r"(v.z), "r"(v.w) : "memory"); }
DEV void stsm4(uint32_t a, uint32_t r0, uint32_t r1, uint32_t r2, uint32_t r3) { asm volatile("stmatrix.sync.aligned.m8n8.x4.shared.b16 [%0], {%1,%2,%3,%4};" ::"r"(a), "r"(r0), "r"(r1), "r"(r2), "r"(r3) : "memory"); }
DEV void stsm4t(uint32_t a, uint32_t r0, uint32_t r1, uint32_t r2, uint32_t r3) { asm volatile("stmatrix.sync.aligned.m8n8.x4.trans.shared.b16 [%0], {%1,%2,%3,%4};" ::"r"(a), "r"(r0), "r"(r1), "r"(r2), "r"(r3) : "memory"); }
DEV void ldsm4(uint32_t a, uint32_t (&r)[4]) { asm volatile("ldmatrix.sync.aligned.m8n8.x4.shared.b16 {%0,%1,%2,%3}, [%4];" : "=r"(r[0]), "=r"(r[1]), "=r"(r[2]), "=r"(r[3]) : "r"(a) : "memory"); }
DEV void ldsm4t(uint32_t a, uint32_t (&r)[4]) { asm volatile("ldmatrix.sync.aligned.m8n8.x4.trans.shared.b16 {%0,%1,%2,%3}, [%4];" : "=r"(r[0]), "=r"(r[1]), "=r"(r[2]), "=r"(r[3]) : "r"(a) : "memory"); }
DEV uint32_t pack2(float lo, float hi) { uint32_t r; asm("cvt.rn.bf16x2.f32 %0, %1, %2;" : "=r"(r) : "f"(hi), "f"(lo)); return r; }
DEV uint32_t pack2v(float lo, float hi) { uint32_t r; asm volatile("cvt.rn.bf16x2.f32 %0, %1, %2;" : "=r"(r) : "f"(hi), "f"(lo)); return r; }
DEV float faddv(float a, float b) { float r; asm volatile("add.rn.f32 %0, %1, %2;" : "=f"(r) : "f"(a), "f"(b)); return r; }
DEV float blo(uint32_t u) { return __uint_as_float(u << 16); }
DEV float bhi(uint32_t u) { return __uint_as_float(u & 0xffff0000u); }
DEV float rcp_fast(float x) { float y; asm("rcp.approx.ftz.f32 %0, %1;" : "=f"(y) : "f"(x)); return y; }
DEV float tanh_fast(float x) { float y; asm("tanh.approx.f32 %0, %1;" : "=f"(y) : "f"(x)); return y; }
DEV uint32_t htanh2(uint32_t a) { uint32_t r; asm("tanh.approx.bf16x2 %0, %1;" : "=r"(r) : "r"(a)); return r; }
DEV uint32_t hadd2(uint32_t a, uint32_t b) { uint32_t r; asm("add.rn.bf16x2 %0, %1, %2;" : "=r"(r) : "r"(a), "r"(b)); return r; }
DEV uint32_t hadd2v(uint32_t a, uint32_t b) { uint32_t r; asm volatile("add.rn.bf16x2 %0, %1, %2;" : "=r"(r) : "r"(a), "r"(b)); return r; }
DEV uint32_t hmul2(uint32_t a, uint32_t b) { uint32_t r; asm("mul.rn.bf16x2 %0, %1, %2;" : "=r"(r) : "r"(a), "r"(b)); return r; }
DEV uint32_t hfma2(uint32_t a, uint32_t b, uint32_t c) { uint32_t r; asm("fma.rn.bf16x2 %0, %1, %2, %3;" : "=r"(r) : "r"(a), "r"(b), "r"(c)); return r; }
DEV uint32_t hfma2v(uint32_t a, uint32_t b, uint32_t c) { uint32_t r; asm volatile("fma.rn.bf16x2 %0, %1, %2, %3;" : "=r"(r) : "r"(a), "r"(b), "r"(c)); return r; }
DEV uint32_t hfms2(uint32_t a, uint32_t b, uint32_t c) { uint32_t r; asm("{\n.reg .b32 t;\nmul.bf16x2 t, %1, %2;\nsub.bf16x2 %0, %3, t;\n}" : "=r"(r) : "r"(a), "r"(b), "r"(c)); return r; }
DEV uint4 ldg128(const void* p) { uint4 v; asm volatile("ld.global.nc.v4.b32 {%0,%1,%2,%3}, [%4];" : "=r"(v.x), "=r"(v.y), "=r"(v.z), "=r"(v.w) : "l"(p)); return v; }
DEV uint32_t ldg32(const void* p) { uint32_t v; asm volatile("ld.global.nc.b32 %0, [%1];" : "=r"(v) : "l"(p)); return v; }
DEV float ldg_bf16(const bf16* p) { unsigned short v; asm volatile("ld.global.nc.u16 %0, [%1];" : "=h"(v) : "l"(p)); return __uint_as_float((uint32_t)v << 16); }
DEV float bf_round(float v) { return __bfloat162float(__float2bfloat16(v)); }
DEV uint32_t gelu2(float a, float b, float c1, float c2) {
  const uint32_t p = pack2(a, b);
  return hfma2(p, htanh2(hmul2(p, hfma2(hmul2(p, p), __float_as_uint(c2), __float_as_uint(c1)))), p);
}

DEV void wgmma_ssp_80_10(float* d, uint64_t da, uint64_t db, int keep) {
  asm volatile("{\n.reg .pred p;\nsetp.ne.b32 p, %42, 0;\nwgmma.mma_async.sync.aligned.m64n80k16.f32.bf16.bf16 {%0, %1, %2, %3, %4, %5, %6, %7, %8, %9, %10, %11, %12, %13, %14, %15, %16, %17, %18, %19, %20, %21, %22, %23, %24, %25, %26, %27, %28, %29, %30, %31, %32, %33, %34, %35, %36, %37, %38, %39}, %40, %41, p, 1, 1, 1, 0;\n}\n"
    : "+f"(d[0]), "+f"(d[1]), "+f"(d[2]), "+f"(d[3]), "+f"(d[4]), "+f"(d[5]), "+f"(d[6]), "+f"(d[7]), "+f"(d[8]), "+f"(d[9]), "+f"(d[10]), "+f"(d[11]), "+f"(d[12]), "+f"(d[13]), "+f"(d[14]), "+f"(d[15]), "+f"(d[16]), "+f"(d[17]), "+f"(d[18]), "+f"(d[19]), "+f"(d[20]), "+f"(d[21]), "+f"(d[22]), "+f"(d[23]), "+f"(d[24]), "+f"(d[25]), "+f"(d[26]), "+f"(d[27]), "+f"(d[28]), "+f"(d[29]), "+f"(d[30]), "+f"(d[31]), "+f"(d[32]), "+f"(d[33]), "+f"(d[34]), "+f"(d[35]), "+f"(d[36]), "+f"(d[37]), "+f"(d[38]), "+f"(d[39])
    : "l"(da), "l"(db), "r"(keep));
}
DEV void wgmma_ss_128_01(float* d, uint64_t da, uint64_t db) {
  asm volatile("{\n.reg .pred p;\nsetp.ne.b32 p, 1, 0;\nwgmma.mma_async.sync.aligned.m64n128k16.f32.bf16.bf16 {%0, %1, %2, %3, %4, %5, %6, %7, %8, %9, %10, %11, %12, %13, %14, %15, %16, %17, %18, %19, %20, %21, %22, %23, %24, %25, %26, %27, %28, %29, %30, %31, %32, %33, %34, %35, %36, %37, %38, %39, %40, %41, %42, %43, %44, %45, %46, %47, %48, %49, %50, %51, %52, %53, %54, %55, %56, %57, %58, %59, %60, %61, %62, %63}, %64, %65, p, 1, 1, 0, 1;\n}\n"
    : "+f"(d[0]), "+f"(d[1]), "+f"(d[2]), "+f"(d[3]), "+f"(d[4]), "+f"(d[5]), "+f"(d[6]), "+f"(d[7]), "+f"(d[8]), "+f"(d[9]), "+f"(d[10]), "+f"(d[11]), "+f"(d[12]), "+f"(d[13]), "+f"(d[14]), "+f"(d[15]), "+f"(d[16]), "+f"(d[17]), "+f"(d[18]), "+f"(d[19]), "+f"(d[20]), "+f"(d[21]), "+f"(d[22]), "+f"(d[23]), "+f"(d[24]), "+f"(d[25]), "+f"(d[26]), "+f"(d[27]), "+f"(d[28]), "+f"(d[29]), "+f"(d[30]), "+f"(d[31]), "+f"(d[32]), "+f"(d[33]), "+f"(d[34]), "+f"(d[35]), "+f"(d[36]), "+f"(d[37]), "+f"(d[38]), "+f"(d[39]), "+f"(d[40]), "+f"(d[41]), "+f"(d[42]), "+f"(d[43]), "+f"(d[44]), "+f"(d[45]), "+f"(d[46]), "+f"(d[47]), "+f"(d[48]), "+f"(d[49]), "+f"(d[50]), "+f"(d[51]), "+f"(d[52]), "+f"(d[53]), "+f"(d[54]), "+f"(d[55]), "+f"(d[56]), "+f"(d[57]), "+f"(d[58]), "+f"(d[59]), "+f"(d[60]), "+f"(d[61]), "+f"(d[62]), "+f"(d[63])
    : "l"(da), "l"(db));
}
DEV void wgmma_ss_96_01(float* d, uint64_t da, uint64_t db) {
  asm volatile("{\n.reg .pred p;\nsetp.ne.b32 p, 1, 0;\nwgmma.mma_async.sync.aligned.m64n96k16.f32.bf16.bf16 {%0, %1, %2, %3, %4, %5, %6, %7, %8, %9, %10, %11, %12, %13, %14, %15, %16, %17, %18, %19, %20, %21, %22, %23, %24, %25, %26, %27, %28, %29, %30, %31, %32, %33, %34, %35, %36, %37, %38, %39, %40, %41, %42, %43, %44, %45, %46, %47}, %48, %49, p, 1, 1, 0, 1;\n}\n"
    : "+f"(d[0]), "+f"(d[1]), "+f"(d[2]), "+f"(d[3]), "+f"(d[4]), "+f"(d[5]), "+f"(d[6]), "+f"(d[7]), "+f"(d[8]), "+f"(d[9]), "+f"(d[10]), "+f"(d[11]), "+f"(d[12]), "+f"(d[13]), "+f"(d[14]), "+f"(d[15]), "+f"(d[16]), "+f"(d[17]), "+f"(d[18]), "+f"(d[19]), "+f"(d[20]), "+f"(d[21]), "+f"(d[22]), "+f"(d[23]), "+f"(d[24]), "+f"(d[25]), "+f"(d[26]), "+f"(d[27]), "+f"(d[28]), "+f"(d[29]), "+f"(d[30]), "+f"(d[31]), "+f"(d[32]), "+f"(d[33]), "+f"(d[34]), "+f"(d[35]), "+f"(d[36]), "+f"(d[37]), "+f"(d[38]), "+f"(d[39]), "+f"(d[40]), "+f"(d[41]), "+f"(d[42]), "+f"(d[43]), "+f"(d[44]), "+f"(d[45]), "+f"(d[46]), "+f"(d[47])
    : "l"(da), "l"(db));
}
DEV void wgmma_ss_80_10(float* d, uint64_t da, uint64_t db) {
  asm volatile("{\n.reg .pred p;\nsetp.ne.b32 p, 1, 0;\nwgmma.mma_async.sync.aligned.m64n80k16.f32.bf16.bf16 {%0, %1, %2, %3, %4, %5, %6, %7, %8, %9, %10, %11, %12, %13, %14, %15, %16, %17, %18, %19, %20, %21, %22, %23, %24, %25, %26, %27, %28, %29, %30, %31, %32, %33, %34, %35, %36, %37, %38, %39}, %40, %41, p, 1, 1, 1, 0;\n}\n"
    : "+f"(d[0]), "+f"(d[1]), "+f"(d[2]), "+f"(d[3]), "+f"(d[4]), "+f"(d[5]), "+f"(d[6]), "+f"(d[7]), "+f"(d[8]), "+f"(d[9]), "+f"(d[10]), "+f"(d[11]), "+f"(d[12]), "+f"(d[13]), "+f"(d[14]), "+f"(d[15]), "+f"(d[16]), "+f"(d[17]), "+f"(d[18]), "+f"(d[19]), "+f"(d[20]), "+f"(d[21]), "+f"(d[22]), "+f"(d[23]), "+f"(d[24]), "+f"(d[25]), "+f"(d[26]), "+f"(d[27]), "+f"(d[28]), "+f"(d[29]), "+f"(d[30]), "+f"(d[31]), "+f"(d[32]), "+f"(d[33]), "+f"(d[34]), "+f"(d[35]), "+f"(d[36]), "+f"(d[37]), "+f"(d[38]), "+f"(d[39])
    : "l"(da), "l"(db));
}
DEV void wgmma_ss_8_10(float* d, uint64_t da, uint64_t db) {
  asm volatile("{\n.reg .pred p;\nsetp.ne.b32 p, 1, 0;\nwgmma.mma_async.sync.aligned.m64n8k16.f32.bf16.bf16 {%0, %1, %2, %3}, %4, %5, p, 1, 1, 1, 0;\n}\n"
    : "+f"(d[0]), "+f"(d[1]), "+f"(d[2]), "+f"(d[3])
    : "l"(da), "l"(db));
}
DEV void wgmma_ss_32_10(float* d, uint64_t da, uint64_t db) {
  asm volatile("{\n.reg .pred p;\nsetp.ne.b32 p, 1, 0;\nwgmma.mma_async.sync.aligned.m64n32k16.f32.bf16.bf16 {%0, %1, %2, %3, %4, %5, %6, %7, %8, %9, %10, %11, %12, %13, %14, %15}, %16, %17, p, 1, 1, 1, 0;\n}\n"
    : "+f"(d[0]), "+f"(d[1]), "+f"(d[2]), "+f"(d[3]), "+f"(d[4]), "+f"(d[5]), "+f"(d[6]), "+f"(d[7]), "+f"(d[8]), "+f"(d[9]), "+f"(d[10]), "+f"(d[11]), "+f"(d[12]), "+f"(d[13]), "+f"(d[14]), "+f"(d[15])
    : "l"(da), "l"(db));
}
DEV void wgmma_ssz_32_10(float* d, uint64_t da, uint64_t db) {
  asm volatile("{\n.reg .pred p;\nsetp.ne.b32 p, 0, 0;\nwgmma.mma_async.sync.aligned.m64n32k16.f32.bf16.bf16 {%0, %1, %2, %3, %4, %5, %6, %7, %8, %9, %10, %11, %12, %13, %14, %15}, %16, %17, p, 1, 1, 1, 0;\n}\n"
    : "=f"(d[0]), "=f"(d[1]), "=f"(d[2]), "=f"(d[3]), "=f"(d[4]), "=f"(d[5]), "=f"(d[6]), "=f"(d[7]), "=f"(d[8]), "=f"(d[9]), "=f"(d[10]), "=f"(d[11]), "=f"(d[12]), "=f"(d[13]), "=f"(d[14]), "=f"(d[15])
    : "l"(da), "l"(db));
}
DEV void wgmma_rs_64_0(float* d, const uint32_t* a, uint64_t db) {
  asm volatile("{\n.reg .pred p;\nsetp.ne.b32 p, 1, 0;\nwgmma.mma_async.sync.aligned.m64n64k16.f32.bf16.bf16 {%0, %1, %2, %3, %4, %5, %6, %7, %8, %9, %10, %11, %12, %13, %14, %15, %16, %17, %18, %19, %20, %21, %22, %23, %24, %25, %26, %27, %28, %29, %30, %31}, {%32, %33, %34, %35}, %36, p, 1, 1, 0;\n}\n"
    : "+f"(d[0]), "+f"(d[1]), "+f"(d[2]), "+f"(d[3]), "+f"(d[4]), "+f"(d[5]), "+f"(d[6]), "+f"(d[7]), "+f"(d[8]), "+f"(d[9]), "+f"(d[10]), "+f"(d[11]), "+f"(d[12]), "+f"(d[13]), "+f"(d[14]), "+f"(d[15]), "+f"(d[16]), "+f"(d[17]), "+f"(d[18]), "+f"(d[19]), "+f"(d[20]), "+f"(d[21]), "+f"(d[22]), "+f"(d[23]), "+f"(d[24]), "+f"(d[25]), "+f"(d[26]), "+f"(d[27]), "+f"(d[28]), "+f"(d[29]), "+f"(d[30]), "+f"(d[31])
    : "r"(a[0]), "r"(a[1]), "r"(a[2]), "r"(a[3]), "l"(db));
}
DEV void wgmma_rsz_64_0(float* d, const uint32_t* a, uint64_t db) {
  asm volatile("{\n.reg .pred p;\nsetp.ne.b32 p, 0, 0;\nwgmma.mma_async.sync.aligned.m64n64k16.f32.bf16.bf16 {%0, %1, %2, %3, %4, %5, %6, %7, %8, %9, %10, %11, %12, %13, %14, %15, %16, %17, %18, %19, %20, %21, %22, %23, %24, %25, %26, %27, %28, %29, %30, %31}, {%32, %33, %34, %35}, %36, p, 1, 1, 0;\n}\n"
    : "=f"(d[0]), "=f"(d[1]), "=f"(d[2]), "=f"(d[3]), "=f"(d[4]), "=f"(d[5]), "=f"(d[6]), "=f"(d[7]), "=f"(d[8]), "=f"(d[9]), "=f"(d[10]), "=f"(d[11]), "=f"(d[12]), "=f"(d[13]), "=f"(d[14]), "=f"(d[15]), "=f"(d[16]), "=f"(d[17]), "=f"(d[18]), "=f"(d[19]), "=f"(d[20]), "=f"(d[21]), "=f"(d[22]), "=f"(d[23]), "=f"(d[24]), "=f"(d[25]), "=f"(d[26]), "=f"(d[27]), "=f"(d[28]), "=f"(d[29]), "=f"(d[30]), "=f"(d[31])
    : "r"(a[0]), "r"(a[1]), "r"(a[2]), "r"(a[3]), "l"(db));
}
DEV void wgmma_rs_64_1(float* d, const uint32_t* a, uint64_t db) {
  asm volatile("{\n.reg .pred p;\nsetp.ne.b32 p, 1, 0;\nwgmma.mma_async.sync.aligned.m64n64k16.f32.bf16.bf16 {%0, %1, %2, %3, %4, %5, %6, %7, %8, %9, %10, %11, %12, %13, %14, %15, %16, %17, %18, %19, %20, %21, %22, %23, %24, %25, %26, %27, %28, %29, %30, %31}, {%32, %33, %34, %35}, %36, p, 1, 1, 1;\n}\n"
    : "+f"(d[0]), "+f"(d[1]), "+f"(d[2]), "+f"(d[3]), "+f"(d[4]), "+f"(d[5]), "+f"(d[6]), "+f"(d[7]), "+f"(d[8]), "+f"(d[9]), "+f"(d[10]), "+f"(d[11]), "+f"(d[12]), "+f"(d[13]), "+f"(d[14]), "+f"(d[15]), "+f"(d[16]), "+f"(d[17]), "+f"(d[18]), "+f"(d[19]), "+f"(d[20]), "+f"(d[21]), "+f"(d[22]), "+f"(d[23]), "+f"(d[24]), "+f"(d[25]), "+f"(d[26]), "+f"(d[27]), "+f"(d[28]), "+f"(d[29]), "+f"(d[30]), "+f"(d[31])
    : "r"(a[0]), "r"(a[1]), "r"(a[2]), "r"(a[3]), "l"(db));
}
DEV void wgmma_rsz_64_1(float* d, const uint32_t* a, uint64_t db) {
  asm volatile("{\n.reg .pred p;\nsetp.ne.b32 p, 0, 0;\nwgmma.mma_async.sync.aligned.m64n64k16.f32.bf16.bf16 {%0, %1, %2, %3, %4, %5, %6, %7, %8, %9, %10, %11, %12, %13, %14, %15, %16, %17, %18, %19, %20, %21, %22, %23, %24, %25, %26, %27, %28, %29, %30, %31}, {%32, %33, %34, %35}, %36, p, 1, 1, 1;\n}\n"
    : "=f"(d[0]), "=f"(d[1]), "=f"(d[2]), "=f"(d[3]), "=f"(d[4]), "=f"(d[5]), "=f"(d[6]), "=f"(d[7]), "=f"(d[8]), "=f"(d[9]), "=f"(d[10]), "=f"(d[11]), "=f"(d[12]), "=f"(d[13]), "=f"(d[14]), "=f"(d[15]), "=f"(d[16]), "=f"(d[17]), "=f"(d[18]), "=f"(d[19]), "=f"(d[20]), "=f"(d[21]), "=f"(d[22]), "=f"(d[23]), "=f"(d[24]), "=f"(d[25]), "=f"(d[26]), "=f"(d[27]), "=f"(d[28]), "=f"(d[29]), "=f"(d[30]), "=f"(d[31])
    : "r"(a[0]), "r"(a[1]), "r"(a[2]), "r"(a[3]), "l"(db));
}
DEV void wgmma_rs_128_1(float* d, const uint32_t* a, uint64_t db) {
  asm volatile("{\n.reg .pred p;\nsetp.ne.b32 p, 1, 0;\nwgmma.mma_async.sync.aligned.m64n128k16.f32.bf16.bf16 {%0, %1, %2, %3, %4, %5, %6, %7, %8, %9, %10, %11, %12, %13, %14, %15, %16, %17, %18, %19, %20, %21, %22, %23, %24, %25, %26, %27, %28, %29, %30, %31, %32, %33, %34, %35, %36, %37, %38, %39, %40, %41, %42, %43, %44, %45, %46, %47, %48, %49, %50, %51, %52, %53, %54, %55, %56, %57, %58, %59, %60, %61, %62, %63}, {%64, %65, %66, %67}, %68, p, 1, 1, 1;\n}\n"
    : "+f"(d[0]), "+f"(d[1]), "+f"(d[2]), "+f"(d[3]), "+f"(d[4]), "+f"(d[5]), "+f"(d[6]), "+f"(d[7]), "+f"(d[8]), "+f"(d[9]), "+f"(d[10]), "+f"(d[11]), "+f"(d[12]), "+f"(d[13]), "+f"(d[14]), "+f"(d[15]), "+f"(d[16]), "+f"(d[17]), "+f"(d[18]), "+f"(d[19]), "+f"(d[20]), "+f"(d[21]), "+f"(d[22]), "+f"(d[23]), "+f"(d[24]), "+f"(d[25]), "+f"(d[26]), "+f"(d[27]), "+f"(d[28]), "+f"(d[29]), "+f"(d[30]), "+f"(d[31]), "+f"(d[32]), "+f"(d[33]), "+f"(d[34]), "+f"(d[35]), "+f"(d[36]), "+f"(d[37]), "+f"(d[38]), "+f"(d[39]), "+f"(d[40]), "+f"(d[41]), "+f"(d[42]), "+f"(d[43]), "+f"(d[44]), "+f"(d[45]), "+f"(d[46]), "+f"(d[47]), "+f"(d[48]), "+f"(d[49]), "+f"(d[50]), "+f"(d[51]), "+f"(d[52]), "+f"(d[53]), "+f"(d[54]), "+f"(d[55]), "+f"(d[56]), "+f"(d[57]), "+f"(d[58]), "+f"(d[59]), "+f"(d[60]), "+f"(d[61]), "+f"(d[62]), "+f"(d[63])
    : "r"(a[0]), "r"(a[1]), "r"(a[2]), "r"(a[3]), "l"(db));
}
DEV void wgmma_rs_96_1(float* d, const uint32_t* a, uint64_t db) {
  asm volatile("{\n.reg .pred p;\nsetp.ne.b32 p, 1, 0;\nwgmma.mma_async.sync.aligned.m64n96k16.f32.bf16.bf16 {%0, %1, %2, %3, %4, %5, %6, %7, %8, %9, %10, %11, %12, %13, %14, %15, %16, %17, %18, %19, %20, %21, %22, %23, %24, %25, %26, %27, %28, %29, %30, %31, %32, %33, %34, %35, %36, %37, %38, %39, %40, %41, %42, %43, %44, %45, %46, %47}, {%48, %49, %50, %51}, %52, p, 1, 1, 1;\n}\n"
    : "+f"(d[0]), "+f"(d[1]), "+f"(d[2]), "+f"(d[3]), "+f"(d[4]), "+f"(d[5]), "+f"(d[6]), "+f"(d[7]), "+f"(d[8]), "+f"(d[9]), "+f"(d[10]), "+f"(d[11]), "+f"(d[12]), "+f"(d[13]), "+f"(d[14]), "+f"(d[15]), "+f"(d[16]), "+f"(d[17]), "+f"(d[18]), "+f"(d[19]), "+f"(d[20]), "+f"(d[21]), "+f"(d[22]), "+f"(d[23]), "+f"(d[24]), "+f"(d[25]), "+f"(d[26]), "+f"(d[27]), "+f"(d[28]), "+f"(d[29]), "+f"(d[30]), "+f"(d[31]), "+f"(d[32]), "+f"(d[33]), "+f"(d[34]), "+f"(d[35]), "+f"(d[36]), "+f"(d[37]), "+f"(d[38]), "+f"(d[39]), "+f"(d[40]), "+f"(d[41]), "+f"(d[42]), "+f"(d[43]), "+f"(d[44]), "+f"(d[45]), "+f"(d[46]), "+f"(d[47])
    : "r"(a[0]), "r"(a[1]), "r"(a[2]), "r"(a[3]), "l"(db));
}

struct Dft { uint32_t E[8], tt[8], ts[8]; };
DEV void dft_load(Dft& k, const uint32_t* tab, int tid) {
#pragma unroll
  for (int q = 0; q < 6; q++) {
    const uint4 v = ldg128(tab + 3072 + 512 * q + 4 * tid);
    uint32_t* d = (q < 2 ? k.E : q < 4 ? k.tt : k.ts) + 4 * (q & 1);
    d[0] = v.x; d[1] = v.y; d[2] = v.z; d[3] = v.w;
  }
}
template <int SG> DEV void rotate(const float* d, const Dft& k, uint32_t* o) {
#pragma unroll
  for (int j = 0; j < 8; j++) {
    const uint32_t re = pack2(d[4 * j], d[4 * j + 1]), im = pack2(d[4 * j + 2], d[4 * j + 3]);
    uint32_t a, b;
    if (SG > 0) { a = hfms2(k.tt[j], im, re); b = hfma2(k.ts[j], a, im); a = hfms2(k.tt[j], b, a); }
    else { a = hfma2(k.tt[j], im, re); b = hfms2(k.ts[j], a, im); a = hfma2(k.tt[j], b, a); }
    o[2 * j] = a; o[2 * j + 1] = b;
  }
}
DEV void dft64(float* d, const uint32_t* a, uint64_t db) {
  wgmma_rsz_64_1(d, a, db);
#pragma unroll
  for (int kk = 1; kk < 4; kk++) wgmma_rs_64_1(d, a + 4 * kk, db + kk * (2048 >> 4));
}
DEV bool conv(const Dft& k, uint32_t sb, uint32_t t, uint32_t ty, float dv, int bar, int w, int lane, unsigned* go, uint32_t ep, uint32_t zero) {
  const uint32_t tag = KVCHK ? lds32(t + 1024 * w + 32 * lane + 4 * (lane & 4)) : ep;
  dv = __uint_as_float(__float_as_uint(dv) | (tag & zero));
  float dh[32], dx[32];
  uint32_t ah[16], ax[16];
  const uint64_t cs = make_desc(sb + OFF_DFT, 16, 1024, 1), bh = make_desc(t + 4096, 16, 1024, 1), bx = make_desc(t, 1024, 256, 3);
  wg_fence();
  wgmma_rsz_64_1(dh, k.E, bh); wgmma_rs_64_1(dh, k.E + 4, bh + (2048 >> 4)); wg_commit();
  wgmma_rsz_64_1(dx, k.E, bx); wgmma_rs_64_1(dx, k.E + 4, bx + (512 >> 4)); wg_commit();
  wg_wait<1>();
  dh[0] = fmaf(dv, blo(k.E[0]), dh[0]); dh[2] = fmaf(dv, blo(k.E[1]), dh[2]);
  rotate<1>(dh, k, ah);
  wg_fence(); dft64(dh, ah, cs); wg_commit();
  if (GO_AT == 1 && go) flag_add_rlx(go, 1);
  wg_wait<1>();
  rotate<1>(dx, k, ax);
  wg_fence(); dft64(dx, ax, cs); wg_commit();
  wg_wait<1>();
#pragma unroll
  for (int j = 0; j < 8; j++) { ah[2 * j] = pack2(dh[4 * j], dh[4 * j + 1]); ah[2 * j + 1] = pack2(dh[4 * j + 2], dh[4 * j + 3]); }
  wg_wait<0>();
#pragma unroll
  for (int j = 0; j < 4; j++) {
    const uint32_t pr = pack2(dx[4 * j], dx[4 * j + 1]), pi = pack2(dx[4 * j + 2], dx[4 * j + 3]);
    const uint32_t qr = pack2(dx[16 + 4 * j], dx[17 + 4 * j]), qi = pack2(dx[18 + 4 * j], dx[19 + 4 * j]);
    const uint32_t rr = ah[2 * j], ri = ah[2 * j + 1], sr = ah[8 + 2 * j], si = ah[9 + 2 * j];
    ax[2 * j] = hfma2(qi, si, hfms2(qr, sr, hfms2(pi, ri, hmul2(pr, rr))));
    ax[2 * j + 1] = hfms2(qi, sr, hfms2(qr, si, hfma2(pi, rr, hmul2(pr, ri))));
    ax[8 + 2 * j] = hfms2(qi, ri, hfma2(qr, rr, hfms2(pi, si, hmul2(pr, sr))));
    ax[9 + 2 * j] = hfma2(qi, rr, hfma2(qr, ri, hfma2(pi, sr, hmul2(pr, si))));
  }
  wg_fence();
  wgmma_rsz_64_0(dx, ax, cs);
#pragma unroll
  for (int kk = 1; kk < 4; kk++) wgmma_rs_64_0(dx, ax + 4 * kk, cs + 2 * kk);
  wg_commit();
  if (GO_AT == 2 && go) flag_add_rlx(go, 1);
  wg_wait<0>();
  rotate<-1>(dx, k, ah);
  const int m = lane >> 3, i = lane & 7;
  const uint32_t za = t + (16 * w + 8 * (m & 1) + i) * 128;
#pragma unroll
  for (int q = 0; q < 4; q++) stsm4(za + (((2 * q + (m >> 1)) ^ i) << 4), ah[4 * q], ah[4 * q + 1], ah[4 * q + 2], ah[4 * q + 3]);
  fence_async_smem();
  uint32_t ok;
  asm volatile("{\n.reg .pred p, q;\nsetp.eq.u32 p, %1, 0;\nbarrier.red.and.aligned.pred q, %2, 128, p;\nselp.u32 %0, 1, 0, q;\n}" : "=r"(ok) : "r"((tag ^ ep) & 1), "r"(bar) : "memory");
  const uint64_t da = make_desc(t, 16, 1024, 1), db = make_desc(sb + OFF_G, 16, 1024, 1);
  if (K4E) mbar_wait(sb + OFF_BAR + 8 * B_KVC, 0);
  wg_fence();
  wgmma_ssz_32_10(dh, da, db);
#pragma unroll
  for (int kk = 1; kk < 4; kk++) wgmma_ss_32_10(dh, da + kk * (2048 >> 4), db + 2 * kk);
  wg_commit();
  if (GO_AT == 3 && go) flag_add_rlx(go, 1);
  wg_wait<0>();
  if (!K4E) mbar_wait(sb + OFF_BAR + 8 * B_KVC, 0);
  const uint32_t ya = ty + (8 * (m >> 1) + i) * 128 + (((2 * w + (m & 1)) ^ i) << 4);
#pragma unroll
  for (int q = 0; q < 2; q++)
    stsm4t(ya + q * 2048, pack2(dh[8 * q], dh[8 * q + 1]), pack2(dh[8 * q + 2], dh[8 * q + 3]), pack2(dh[8 * q + 4], dh[8 * q + 5]), pack2(dh[8 * q + 6], dh[8 * q + 7]));
  wfence(4);
  return !KVCHK || __all_sync(0xffffffffu, ok);
}

DEV void g1_issue(const Params& P, uint32_t sb, int s, uint32_t fb, int kb, int rb, int fs) {
  const uint32_t st = sb + s * G1_W;
  mbar_expect(fb, G1_W + G1_X);
  tma2d(sb + OFF_X + s * G1_X, &P.x_g1, 64 * kb, 128 * rb, fb);
  tma3d(st, &P.w1_a, 0, 64 * kb, 3 * fs, fb);
  tma3d(st + 16384, &P.w1_b2, 0, 64 * kb, 6 * fs + 4, fb);
  tma3d(st + 24576, &P.w1_b1, 0, 64 * kb, 48 + fs, fb);
}
DEV void g1_issue_mc(const Params& P, uint32_t sb, int s, uint32_t fb, int kb, int rb, int fs, bool first) {
  const uint32_t st = sb + s * G1_W, pf = sb + OFF_BAR + 8 * (B_PF + s);
  mbar_expect(fb, G1_W + G1_X);
  if (!first && MC == 2) mbar_arrive_peer(pf);
  if (!first || !MCX) tma2d(sb + OFF_X + s * G1_X, &P.x_g1, 64 * kb, 128 * rb, fb);
  if (!first) { if (MC == 2) mbar_wait(pf, ((kb - MC0) >> 2) & 1); else mbar_wait(sb + OFF_BAR + 8 * (B_PF + kb - 4), 0); }
  if (crank()) {
    tma3d_mc(st + 16384, &P.w1_b2, 0, 64 * kb, 6 * fs + 4, fb);
    tma3d_mc(st + 24576, &P.w1_b1, 0, 64 * kb, 48 + fs, fb);
  } else tma3d_mc(st, &P.w1_a, 0, 64 * kb, 3 * fs, fb);
  if (first && MCX) tma2d(sb + OFF_X + s * G1_X, &P.x_g1, 64 * kb, 128 * rb, fb);
}
DEV void kv_issue(const Params& P, uint32_t dst, uint32_t bar, int r, int g1) {
  mbar_expect(bar, KV_SLOT);
  tma2d(dst, &P.k, 128 * r, 16 * g1 - 3, bar);
  tma2d(dst + 19 * 256, &P.v, 128 * r, 16 * g1, bar);
}
DEV void h_flag(const Params& P, int rb, int o) {
  const int j0 = (128 * rb) / 80;
  flag_add_rlx(P.flags + FL_H + 32 * (o + j0), 1); flag_add_rlx(P.flags + FL_H + 32 * (o + j0 + 1), 1);
  if (80 * (j0 + 2) < 128 * rb + 128) flag_add_rlx(P.flags + FL_H + 32 * (o + j0 + 2), 1);
}
DEV void h_wait(const Params& P, int tj, int o, unsigned ep, uint32_t buf) {
  const unsigned n = ep * (((80 * tj) >> 7) == (min(80 * tj + 79, S_ - 1) >> 7) ? 8 : 16);
  if (POLL & 4) flag_poll<false>(P.flags + FL_H + 32 * (o + tj), n, buf); else flag_wait<false>(P.flags + FL_H + 32 * (o + tj), n);
  if (FNC & 2) fence_async_global();
}
DEV uint32_t h_tag(uint32_t sb, int tj, int q, int lane) {
  const int r = min(q < 2 ? 32 * q + lane : 64 + (lane & 15), S_ - 1 - 80 * tj);
  return sb + G2_B + r * 128 + ((r & 7) << 4) + 4 * ((2 * tj + (r >> 3)) & 3);
}
DEV uint32_t conv_tile(uint32_t sb, int c) { return sb + (c == 1 ? OFF_T1 : c == 2 ? OFF_T2 : c == 3 ? OFF_T3 : c == 4 ? OFF_T4 : OFF_T0); }
DEV void conv_issue_f(const Params& P, uint32_t t, int ch, uint32_t bar) { mbar_expect(bar, 4096); tma2d(t + 4096, &P.f_ld, 0, 32 * ch, bar); }
DEV void conv_issue_x(const Params& P, uint32_t t, int ch, uint32_t bar) {
  mbar_expect(bar, 4096);
  tma3d(t, &P.kvz, 16 * ((ch & ~63) | ((ch & 3) << 4) | ((ch & 63) >> 2)), 0, 0, bar);
}
HD int h_slot(int j) { return SPLIT9 && j ? 3 - j : j; }
DEV int g2_slot(int s) { return !RM || s < 3 ? s : s == 5 ? 3 : s + 1; }
HD int out_piece(int j) { return j > 4 ? 9 : ((OUTP ? OUTP : 0x21100) >> (4 * j)) & 15; }
DEV int g2_block(int i) { return i < 24 ? 3 * (i & 7) + (i >> 3) : i; }
DEV int ext_col(int n, int fs) { return min(n < 192 ? 192 * fs + n : 1344 + 32 * fs + n, F_ - 2); }
DEV uint32_t ext_off(int n, int k) {
  const int m = n - 128;
  return n < 128 ? (n >> 6) * 1024 + k * 128 + ((((n & 63) >> 3) ^ k) << 4) + (n & 7) * 2
                 : 2048 + (m >> 5) * 512 + k * 64 + ((((m & 31) >> 3) ^ (k >> 1)) << 4) + (m & 7) * 2;
}
DEV uint32_t kv_elem(uint32_t k0, uint32_t k1, uint32_t k2, uint32_t k3, const uint32_t (&w)[4], uint32_t v) {
  if (MIM & 2) return hmul2(hadd2(hadd2(hadd2(hmul2(k0, w[3]), hmul2(k1, w[2])), hmul2(k2, w[1])), hmul2(k3, w[0])), v);
  return hmul2(hfma2(k3, w[0], hfma2(k2, w[1], hfma2(k1, w[2], hmul2(k0, w[3])))), v);
}
DEV void kv_store(uint32_t z, const uint32_t (&p)[8]) {
  sts128(z, make_uint4(__byte_perm(p[0], p[1], 0x5410), __byte_perm(p[2], p[3], 0x5410), __byte_perm(p[4], p[5], 0x5410), __byte_perm(p[6], p[7], 0x5410)));
  sts128(z + 512, make_uint4(__byte_perm(p[0], p[1], 0x7632), __byte_perm(p[2], p[3], 0x7632), __byte_perm(p[4], p[5], 0x7632), __byte_perm(p[6], p[7], 0x7632)));
}
DEV void kv_out(const Params& P, uint32_t src, int r, int g1) { bulk_s2g(reinterpret_cast<uint8_t*>(P.kvZ) + g1 * 20480 + r * 4096, src, 4096); }
DEV void tap_split(uint4 q, uint32_t (&w)[4]) {
  w[0] = __byte_perm(q.x, q.z, 0x5410); w[1] = __byte_perm(q.x, q.z, 0x7632); w[2] = __byte_perm(q.y, q.w, 0x5410); w[3] = __byte_perm(q.y, q.w, 0x7632);
}

}

__global__ void
__cluster_dims__(2, 1, 1)
__launch_bounds__(512, 1) h3_fused_kernel(const __grid_constant__ Params P) {
  extern __shared__ __align__(1024) uint8_t smem_raw[];
  const uint32_t sb = smem_u32(smem_raw);

#define BAR(i) (sb + OFF_BAR + 8 * (i))
  const int warp = __shfl_sync(0xffffffffu, threadIdx.x >> 5, 0);
  const int wg = warp >> 2;
  const int tid = threadIdx.x & 127, lane = threadIdx.x & 31;
  uint32_t smid, nsmid;
  asm volatile("mov.u32 %0, %%smid;" : "=r"(smid));
  asm volatile("mov.u32 %0, %%nsmid;" : "=r"(nsmid));
  const uint32_t cta = nsmid == NCTA ? smid : blockIdx.x;
  const uchar4 mp = P.map[cta];
  const int g1 = mp.x, g2 = mp.y;
  const bool has1 = g1 < 128, has2 = g2 != 255;
  const int fs = g1 & 7, rb = g1 >> 3;
  const int tj = g2 >> 3, dt = g2 & 7;

  auto paired = [&]() {
    if (MCV != 1) return true;
    asm volatile("barrier.cluster.wait.acquire.aligned;" ::: "memory");
    const uint32_t pg = lds_peer(sb + OFF_POLL);
    return (bool)__all_sync(0xffffffffu, pg < 128 && (pg & 7) == fs);
  };
  if (warp != 12) {
    if (elect()) {
      if (smem_u32(smem_raw) != own(sb) || (sb & 1023)) __trap();
#pragma unroll 1
      for (int b = B_FIRST + warp - (warp > 12); b < B_COUNT; b += 15) mbar_init(BAR(b), P.cnt[b]);
      fence_async_smem();
      if (MC >= 2) asm volatile("fence.mbarrier_init.release.cluster;" ::: "memory");
    }
    __syncwarp();
    if (MC >= 2 && (MCV != 1 || warp)) asm volatile("barrier.cluster.arrive.relaxed.aligned;" ::: "memory");
    asm volatile("bar.arrive 7, 512;" ::: "memory");
    asm volatile("bar.sync 0, 512;" ::: "memory");
    if (MCV == 1 && !warp) {
      sts32(sb + OFF_POLL, g1);
      asm volatile("barrier.cluster.arrive.release.aligned;" ::: "memory");
    }
    if (MC == 3 && !MCV) asm volatile("barrier.cluster.wait.aligned;" ::: "memory");
  }

  if (EXPECT(wg < 3)) {
    const int w4 = warp & 3, g = lane >> 2, c = lane & 3;
    asm volatile("setmaxnreg.inc.sync.aligned.u32 %0;" ::"n"(R_G));
    Dft dft;
    uint32_t ep, dq[3];
    auto misc_load = [&]() {
      const int l = wg == 0 ? CH_W0 : wg == 1 ? CH_W1 : CH_W2;
      ep = lds32(sb + OFF_MISC);
#pragma unroll
      for (int j = 0; j < 3; j++) dq[j] = lds32(sb + OFF_MISC + 4 + 4 * ((l >> (4 * j)) & 7));
    };
    if (wg < 2) {
      if (has1) {
        float acc[112];
        const uint64_t da0 = make_desc(sb + OFF_X + wg * 8192, 16, 1024, 1), db0 = make_desc(sb, 8192, 1024, 1), dc0 = make_desc(sb + 16384, 4096, 512, 2);
        const bool lead = tid == 0;
        const bool mc = MC == 3 && w4 == 0 && paired();
#pragma unroll
        for (int i = 0; i < 112; i++) acc[i] = 0.f;
        auto block = [&](int kb) {
          const int s = kb & 3;
          const uint64_t o = s * (G1_W >> 4), da = da0 + s * (G1_X >> 4), db = db0 + o, dc = dc0 + o;
          mbar_wait(BAR(B_FULL1 + s), (kb >> 2) & 1);
          TZ(tid, 64 + 10 * wg + kb);
          wg_fence();
#pragma unroll
          for (int kk = 0; kk < 4; kk++) {
            wgmma_ss_128_01(acc, da + 2 * kk, db + kk * (2048 >> 4));
            wgmma_ss_96_01(acc + 64, da + 2 * kk, dc + kk * (1024 >> 4));
            if (kk == EREL - 1) {
              wg_commit(); wg_wait<1>();
              if (lead && kb && kb < 7) mbar_arrive(BAR(B_EMPTY1 + ((kb - 1) & 3)));
            }
          }
          wg_commit();
        };
#pragma unroll 1
        for (int kb = 0; kb < 10 - SPLIT9; kb++) {
          block(kb);
          if (!EREL && kb < NOW) {
            wg_wait<1>();
            if (lead && kb && kb < 7) {
              if (mc) mbar_arrive_peer(BAR(B_PF + kb - 1));
              mbar_arrive(BAR(B_EMPTY1 + ((kb - 1) & 3)));
            }
          }
        }
        TZ(tid | (wg ^ 1), 123);
        mbar_wait(BAR(B_TAB), 0);
        TZ(tid, 8 + wg);
        const uint32_t sa = sb + OFF_ST1 + 16 * (64 * wg + 16 * w4 + g);
        const float r0 = __uint_as_float(lds32(sa + 12)), r1 = __uint_as_float(lds32(sa + 128 + 12));
        {
          uint32_t ax[4];
          ax[0] = lds32(sa + 4 * c); ax[1] = lds32(sa + 128 + 4 * c);
          if (c == 3) { ax[0] = 0; ax[1] = 0; }
          asm volatile("mov.b32 %0, 0;" : "=r"(ax[2])); asm volatile("mov.b32 %0, 0;" : "=r"(ax[3]));
          if (SPLIT9) {
            const uint64_t da = da0 + (G1_X >> 4), db = db0 + (G1_W >> 4), dc = dc0 + (G1_W >> 4);
            wg_fence();
            wgmma_rs_128_1(acc, ax, make_desc(sb + OFF_EXT, 1024, 0, 1));
            wgmma_rs_96_1(acc + 64, ax, make_desc(sb + OFF_EXT + 2048, 512, 0, 2));
            mbar_wait(BAR(B_FULL1 + 1), 0);
            TZ(tid, 64 + 10 * wg + 9);
#pragma unroll
            for (int kk = 0; kk < 4; kk++) wgmma_ss_128_01(acc, da + 2 * kk, db + kk * (2048 >> 4));
            wg_commit();
#pragma unroll
            for (int kk = 0; kk < 4; kk++) wgmma_ss_96_01(acc + 64, da + 2 * kk, dc + kk * (1024 >> 4));
            wg_commit();
          } else {
          wg_fence();
          wgmma_rs_128_1(acc, ax, make_desc(sb + OFF_EXT, 1024, 0, 1));
          wgmma_rs_96_1(acc + 64, ax, make_desc(sb + OFF_EXT + 2048, 512, 0, 2));
          wg_commit();
          }
        }
        constexpr float K1 = 0.7978845608028654f, K2 = 0.7978845608028654f * 0.044715f;
        float c10 = K1 * r0, c11 = K1 * r1, c20 = K2 * r0 * r0 * r0, c21 = K2 * r1 * r1 * r1;
        c10 = __uint_as_float(pack2(c10, c10)); c11 = __uint_as_float(pack2(c11, c11)); c20 = __uint_as_float(pack2(c20, c20)); c21 = __uint_as_float(pack2(c21, c21));
        const int hr = 16 * w4 + ((lane >> 3) & 1) * 8 + (lane & 7);
        const uint32_t hs = sb + OFF_X + wg * 8192 + hr * 128, hx = (lane >> 4) ^ (lane & 7);
        const uint32_t hs2 = sb + OFF_X + 3 * G1_X + wg * 4096 + hr * 64, hx2 = (lane >> 4) ^ ((lane >> 1) & 3);
        if (SPLIT9) wg_wait<1>(); else wg_wait<0>();
        TZ(tid, 2 + wg);
        if (!SPLIT9 && tid < 5) mbar_arrive(BAR(tid < 4 ? B_EMPTY2 + (RM && tid == 3 ? 5 : tid) : B_G1FREE));
        uint32_t zn = 0;
        misc_load();
        const uint32_t par = ep & 1;
#pragma unroll
        for (int i = 0; i < 28; i += 2) {
          if (i == 24) { if (fs >= 6) break; if (wg) mbar_wait(BAR(B_G1FREE), 0); }
          if (i && i % GELU_BF16 == 0) {
            const uint32_t z = LOOKAHEAD ? zn : lds32(sb + OFF_MISC + 24);
            c20 = __uint_as_float(__float_as_uint(c20) + z); c21 = __uint_as_float(__float_as_uint(c21) + z);
          }
          if (LOOKAHEAD && (i + LOOKAHEAD) % GELU_BF16 == 0) zn = lds32(sb + OFF_MISC + 24);
          if (SPLIT9 && i == 16) { wg_wait<0>(); if (tid < 5) mbar_arrive(BAR(tid < 4 ? B_EMPTY2 + tid : B_G1FREE)); }
          if (i == DFT_AT) dft_load(dft, P.tab, tid);
          const float* a = &acc[4 * i];
          uint32_t p0 = gelu2(a[0], a[1], c10, c20), p1 = gelu2(a[2], a[3], c11, c21);
          if (!(i & 7)) { if (c == ((2 * w4) & 3)) p0 = (p0 & ~1u) | par; if (c == ((2 * w4 + 1) & 3)) p1 = (p1 & ~1u) | par; }
          const uint32_t p2 = gelu2(a[4], a[5], c10, c20), p3 = gelu2(a[6], a[7], c11, c21);
          if (i > HS_LAG && !((i - HS_LAG) & 7)) { wfence(2); warp_arrive(BAR(B_HS + 4 * wg + (i >> 3) - 1)); }
          if (i < 24) stsm4(hs + h_slot(i >> 3) * G1_X + ((hx ^ (i & 7)) << 4), p0, p1, p2, p3);
          else stsm4(hs2 + ((hx2 ^ (i & 3)) << 4), p0, p1, p2, p3);
          if ((i == 22 && fs >= 6) || i == 26) { wfence(2); warp_arrive(BAR(B_HS + 4 * wg + (i >> 3))); }
        }
        TZ(tid, 4 + wg);
      } else if (wg == 1) {
        float cs[7][4];
#pragma unroll
        for (int j = 0; j < 7; j++) cs[j][0] = cs[j][1] = cs[j][2] = cs[j][3] = 0.f;
        if (tid < 64) sts32(sb + OFF_EXT + 4 * tid, 0x3f803f80u);
        fence_async_smem();
        bar_sync(4);
        const uint64_t da0 = make_desc(sb, 16, 1024, 1), db = make_desc(sb + OFF_EXT, 128, 128, 0);
        int s = 0, ph = 0;
#pragma unroll 1
        for (int kb = SP_FAKE ? 10 : CS_KB; kb < 10; kb++) {
          mbar_wait(BAR(B_FULL1 + s), ph);
          wg_fence();
#pragma unroll 1
          for (int kk = 0; kk < 4; kk++) {
#pragma unroll
            for (int j = 0; j < 7; j++) wgmma_ss_8_10(cs[j], da0 + (s * (CS_STAGE >> 4) + kk * (2048 >> 4)) + j * (8192 >> 4), db);
            wg_commit();
          }
          wg_wait<0>();
          if (tid < 4) mbar_arrive(BAR(B_EMPTY1 + s));
          if (++s == 3) { s = 0; ph ^= 1; }
        }
        mbar_wait(BAR(B_EPOCH), 0);
        ep = lds32(sb + OFF_MISC);
#pragma unroll
        for (int j = 0; j < 7; j++) {
          const float a = (c & 1) ? cs[j][2] : cs[j][0], b = __shfl_down_sync(0xffffffffu, a, 4);
          if (c < 2 && !(g & 1)) tag_store(P.cs + CSP + 32 * (7 * (g1 - 128) + j) + 8 * w4 + 4 * c + (g >> 1), a, b, ep);
        }
        TZ(tid, 24);
        if (tid < 2 * G2_NST + 2 * RM) mbar_arrive(BAR(tid >= 2 * G2_NST ? B_G1FREE : B_EMPTY2 + (tid >> 1)));
      }
    } else {
      if (has1) {
        const bf16* skp = P.shift_k + (128 * (w4 >> 1) + 64 * (w4 & 1) + 4 * (lane & 15)) * 4;
        uint4 tap0 = ldg128(skp), tap1 = ldg128(skp + 8);
        auto stats = [&]() {
        mbar_wait(BAR(B_STAT), 0);
        TZ(tid, 19);
        float sum = 0.f, sq = 0.f;
        const uint32_t sa = sb + OFF_SR + (tid >> 3) * 1280 + 16 * (lane & 7);
        uint4 nq[2] = {lds128(sa), lds128(sa + 128)};
#pragma unroll 1
        for (int z = 0; z < 5; z++) {
          const uint4 xq[2] = {nq[0], nq[1]};
          if (z < 4) { nq[0] = lds128(sa + 256 * z + 256); nq[1] = lds128(sa + 256 * z + 384); }
          else warp_arrive(BAR(B_STATFREE) + ((xq[0].x | xq[1].x) & P.zero));
#pragma unroll
          for (int i = 0; i < 2; i++) {
            const uint32_t u[4] = {xq[i].x, xq[i].y, xq[i].z, xq[i].w};
#pragma unroll
            for (int e = 0; e < 4; e++) { const float a = blo(u[e]), b = bhi(u[e]); sum += a + b; sq = fmaf(a, a, fmaf(b, b, sq)); }
          }
        }
#pragma unroll
        for (int o = 1; o < 8; o *= 2) { sum += __shfl_xor_sync(0xffffffffu, sum, o); sq += __shfl_xor_sync(0xffffffffu, sq, o); }
        const float mean = sum * (1.f / D_), var = fmaxf(fmaf(-mean, mean, sq * (1.f / D_)), 0.f);
        const float ve = bf_round(bf_round(var) + 1e-5f);
        if ((lane & 7) == 0) tag_store(P.stats + 16 * g1 + (tid >> 3), MIM & 1 ? bf_round(mean) : mean, MIM & 1 ? rcp_fast(bf_round(ve * rsqrtf(ve))) : rsqrtf(var + 1e-5f), ep);
        TZ(tid, 22);
        };
        const uint32_t slot = sb + OFF_KV + (w4 >> 1) * KV_SLOT;
        const uint32_t ka = slot + 8 * (lane >> 4) * 256 + 128 * (w4 & 1) + 8 * (lane & 15);
        const uint32_t zo = (64 * (w4 & 1) + (lane & 15)) * 32 + (lane >> 4) * 16;
        if (DFT_EARLY == 2) dft_load(dft, P.tab, tid);
        mbar_wait(BAR(B_EPOCH), 0);
        misc_load();
        const uint32_t hf4 = (lane >> 4) ^ (w4 >> 1);
        const uint32_t tagm = lane < 16 ? 0x00010001u : 0u, tagv = (ep & 1) ? tagm : 0u;
        auto round4 = [&](uint4 tap) {
          uint32_t wa[4], p[8], kk[11];
          tap_split(tap, wa);
          const uint32_t k4 = sb + OFF_KV4 + 8 * (lane >> 4) * 256 + 128 * (w4 & 1) + 8 * (lane & 15) + 4 * hf4;
          mbar_wait(BAR(B_KV4), 0);
          TZ(tid, 62);
#pragma unroll
          for (int j = 0; j < 11; j++) kk[j] = lds32(k4 + j * 256);
#pragma unroll
          for (int j = 0; j < 8; j++) p[j] = lds32(k4 + (19 + j) * 256);
          if (DFT_EARLY == 4) dft_load(dft, P.tab, tid);
#pragma unroll
          for (int j = 0; j < 8; j++) p[j] = kv_elem(kk[j], kk[j + 1], kk[j + 2], kk[j + 3], wa, p[j]);
          bar_sync(3 + ((p[0] | p[1] | p[2] | p[3] | p[4] | p[5] | p[6] | p[7]) & P.zero));
          p[0] = (p[0] & ~tagm) | tagv;
          kv_store(sb + OFF_KV4 + KV_V + zo + 1024 * hf4, p);
          wfence(1);
          warp_arrive(BAR(B_KVS + 2));
        };
        uint4 tap4;
        if (K4E == 3) { tap4 = ldg128(P.shift_k + (512 + 64 * (w4 & 1) + 4 * (lane & 15) + 2 * hf4) * 4); stats(); }
#pragma unroll 1
        for (int r = w4 >> 1; r < (K4E ? 4 : 5); r += 2) {
          uint32_t wa[4], wb[4], p[8], q[8];
          uint2 kk[11];
          tap_split(tap0, wa); tap_split(tap1, wb);
          if (K4E) {
            if (r < 2) { skp += 1024; tap0 = ldg128(skp); tap1 = ldg128(skp + 8); }
            else { if (K4E != 3) tap0 = ldg128(P.shift_k + (512 + 64 * (w4 & 1) + 4 * (lane & 15) + 2 * hf4) * 4); if (DFT_EARLY == 3) dft_load(dft, P.tab, tid); }
          } else {
          if (r < 3) { skp += 1024; tap0 = ldg128(skp); tap1 = ldg128(skp + 8); }
          else if (DFT_EARLY == 3) dft_load(dft, P.tab, tid);
          }
          mbar_wait(BAR(B_KV + (r & 1)), (r >> 1) & 1);
          TZ(tid & 63, 58 + r);
#pragma unroll
          for (int j = 0; j < 11; j++) kk[j] = lds64(ka + j * 256);
#pragma unroll
          for (int j = 0; j < 8; j++) { const uint2 vv = lds64(ka + (19 + j) * 256); p[j] = vv.x; q[j] = vv.y; }
#pragma unroll
          for (int j = 0; j < 8; j++) {
            p[j] = kv_elem(kk[j].x, kk[j + 1].x, kk[j + 2].x, kk[j + 3].x, wa, p[j]);
            q[j] = kv_elem(kk[j].y, kk[j + 1].y, kk[j + 2].y, kk[j + 3].y, wb, q[j]);
          }
          asm volatile("bar.sync %0, 64;" ::"r"(5 + (r & 1) + ((p[0] | p[1] | p[2] | p[3] | p[4] | p[5] | p[6] | p[7]) & P.zero)) : "memory");
          TZ(tid | (r ^ 2) | (DBG_TIME == 2), 10);
          if (r < (K4E ? 2 : 4) && w4 == 0 && elect()) kv_issue(P, slot, BAR(B_KV), r + 2, g1);
          if (r == 2) mbar_wait(BAR(B_KVR), 0);
          TZ(tid | (r ^ 2) | (DBG_TIME == 2), 45);
          const uint32_t z = zo + (r < 4 && w4 < 2 ? sb + OFF_KVS : slot + KV_V);
          p[0] = (p[0] & ~tagm) | tagv; q[0] = (q[0] & ~tagm) | tagv;
          kv_store(z, p); kv_store(z + 1024, q);
          wfence(1);
          warp_arrive(BAR(B_KVS + (r >> 1)));
          TZ(tid | (r ^ 2) | (DBG_TIME == 2), 49);
          if (r < 2) { if (K4E == 3) round4(tap4); else stats(); }
        }
        if (K4E % 3) round4(tap0);
        TZ(tid, 21);
        if (!DFT_EARLY) dft_load(dft, P.tab, tid);
      }
    }

    if (has1) {
      mbar_wait(BAR(B_DFT), 0);
      if (((HOLD >> wg) & 1) && wg < 2) mbar_wait(BAR(B_RD + 1), 0);
      int tries = 0;
#pragma unroll 1
      for (int l = wg == 0 ? CH_W0 : wg == 1 ? CH_W1 : CH_W2; (l & 15) != 15;) {
        const int i = l & 15;
        const float dv = c == 0 ? __uint_as_float(dq[0]) : 0.f;
        TZ(tid, 31 + 4 * i);
        mbar_wait(BAR(B_CX + i), tries & 1);
        TZ(tid, 30 + 4 * i);
        if (conv(dft, sb, conv_tile(sb, i), i ? conv_tile(sb, i) : sb + OFF_Y0, dv, 1 + wg, w4, lane, tid == 0 && ((GO_WG >> wg) & 1) && (l >> 4) == 15 && !tries ? P.flags + FL_G2 + 32 * mp.z : nullptr, ep, P.zero)) {
          warp_arrive(BAR(B_RD + i));
          l >>= 4; tries = 0; dq[0] = dq[1]; dq[1] = dq[2];
        } else {
          fence_async_smem();
          bar_sync(1 + wg);
          trap_above(++tries, 100000);
          if (tid == 0) { conv_issue_f(P, conv_tile(sb, i), g1 + 128 * i, BAR(B_CX + i)); conv_issue_x(P, conv_tile(sb, i), g1 + 128 * i, BAR(B_CX + i)); }
        }
        TZ(tid, 32 + 4 * i);
      }
    }
    if (!PRE && wg == 2 && has2) {
      const uint2* const ps[1] = {P.stats + min(80 * tj + tid, S_ - 1)};
      uint2 sv[1] = {tag_load(ps[0])};
      mbar_wait(BAR(B_EPOCH), 0);
      tag_wait<1>(ps, sv, lds32(sb + OFF_MISC));
      const float r = __uint_as_float(sv[0].y), mr = -__uint_as_float(sv[0].x) * (MIM & 1 ? 1.f : r);
      const float r2 = __shfl_down_sync(0xffffffffu, r, 1), mr2 = __shfl_down_sync(0xffffffffu, mr, 1);
      if (tid < 80 && !(tid & 1)) {
        const uint32_t hi = pack2(r, r2);
        sts128(sb + OFF_ST2 + 8 * tid, make_uint4(hi, pack2(mr, mr2), __float_as_uint(0.25f * r), __float_as_uint(0.25f * r2)));
        sts32(sb + OFF_ST2 + 640 + 2 * tid, pack2(r - blo(hi), r2 - bhi(hi)));
      }
      warp_arrive(BAR(B_EP));
    }
    if ((!has2 || wg == 2) && tid == 0) mbar_arrive(BAR(B_DONE));
    if (has2 && wg < 2) {
      float acc[40];
      const uint64_t da0 = make_desc(sb + wg * 8192, 16, 1024, 1), db0 = make_desc(sb + G2_B, 16, 1024, 1);
      const float b20 = 0.5f * ldg_bf16(P.b2 + 128 * dt + 64 * wg + 16 * w4 + g), b21 = 0.5f * ldg_bf16(P.b2 + 128 * dt + 64 * wg + 16 * w4 + g + 8);
      if (threadIdx.x == 0) mbar_arrive(BAR(B_GO));
      if (!PRE) mbar_wait(BAR(B_GO), 0);
      const bool lead = tid == 0;
      const int mi = lane >> 3, rr = lane & 7;
      const uint32_t xa = sb + OFF_XT + wg * XT_STEP + ((mi >> 1) * 8 + rr) * 128 + (((2 * w4 + (mi & 1)) ^ rr) << 4);
      const uint32_t ya = sb + OFF_YT + (64 * wg + 16 * w4 + (mi & 1) * 8 + rr) * 160 + (mi >> 1) * 16;
      uint32_t xr[5][4], xn[5][4];
      uint2 rq[10];
      uint32_t va = sb + OFF_MISC + 28, ta = sb + OFF_ST2 + 16 * c, tb = sb + OFF_ST2 + 640 + 4 * c;
      asm volatile("" : "+r"(ta), "+r"(tb));
      uint4 st[10];
      uint32_t lo[10];
      auto norm = [&](int i) {
        const uint32_t d0 = hadd2v(xr[i >> 1][2 * (i & 1)], st[i].y), d1 = hadd2v(xr[i >> 1][2 * (i & 1) + 1], st[i].y);
        st[i].y = hfma2v(d1, st[i].x, hmul2(d1, lo[i])); st[i].x = hfma2v(d0, st[i].x, hmul2(d0, lo[i]));
      };
      auto piece = [&](int j) {
        if (j == 3) {
#pragma unroll
          for (int i = 0; i < 10; i += 2) ldsm4t(xa + i * 1024, xr[i >> 1]);
        } else if (j == 4) {
#pragma unroll
          for (int i = 0; i < 10; i++) norm(i);
        } else {
#pragma unroll
          for (int i = j ? 3 * j + 1 : 0; i < 3 * j + 4; i++) { st[i] = lds128(ta + 64 * i); lo[i] = lds32(tb + 16 * i); }
        }
      };
      int np = 0;
      TZ(tid | wg, 157);
      mbar_wait(BAR(B_XF), 0);
#pragma unroll
      for (int j = 0; j < 3; j++)
        if (j < NCH && np == j && !mbar_test(BAR(B_GO), 0)) { piece(j); np = j + 1; }
      if (NCH > 3 && np == 3) {
#pragma unroll 1
        while (!mbar_test(BAR(B_GO), 0))
          if (mbar_test(BAR(B_EP), 0)) { piece(3); np = 4; break; }
      }
      if (NCH > 4 && np == 4 && !mbar_test(BAR(B_GO), 0)) { piece(4); np = 5; }
      TZ(tid | wg, 158);
      mbar_wait(BAR(B_GO), 0);
      TZ(tid | wg, 159);
#pragma unroll
      for (int i = 0; i < 40; i++) acc[i] = 0.f;
#pragma unroll 1
      for (int k0 = 0; k0 < 9; k0++) {
        const int s0 = 3 * (k0 & 1);
        const uint32_t fb = BAR(B_FULL2 + s0);
#pragma unroll
        for (int u = 0; u < 3; u++) {
          const int so = (u < 2 ? (RM ? 4 : 3) * (k0 & 1) + u : 2 + (RM ? 1 : 3) * (k0 & 1)) * (G2_STAGE >> 4);
          const uint64_t da = da0 + so, db = db0 + so;
          if (u == SK2 && k0 == 8 && wg == 1) mbar_wait(BAR(B_SKEW), 0);
          mbar_wait(fb + 8 * u, (k0 >> 1) & 1);
          TZ(threadIdx.x, 64 + 32 + 3 * k0 + u);
          wg_fence();
#pragma unroll
          for (int kk = 0; kk < 4; kk++) wgmma_ss_80_10(acc, da + kk * (2048 >> 4), db + 2 * kk);
          wg_commit();
          if (SK2 > 2 || k0 < 8) wg_wait<1>();
          if (u) { if (lead) mbar_arrive(fb + 8 * (G2_NST + u - 1)); }
          else if (lead && k0) mbar_arrive(BAR(B_EMPTY2 + 5) - 8 * s0);
        }
      }
      if (SK2 <= 2 && threadIdx.x == 0) mbar_arrive(BAR(B_SKEW));
#pragma unroll
      for (int j = 0; j < 5; j++)
        if (np <= j) { if (j == 3) mbar_wait(BAR(B_EP), 0); piece(j); }
      if (RM && TAB_AT == 2) {
#pragma unroll
        for (int i = 0; i < 10; i++) { st[i] = lds128(ta + 64 * i); lo[i] = lds32(tb + 16 * i); }
      }
      if (RM && NORM_AT == 1) {
#pragma unroll
        for (int i = 0; i < 10; i++) norm(i);
      }
#pragma unroll
      for (int i = 0; i < 10; i++) { rq[i] = make_uint2(st[i].z, st[i].w); xn[i >> 1][2 * (i & 1)] = st[i].x; xn[i >> 1][2 * (i & 1) + 1] = st[i].y; }
      TZ(threadIdx.x, 155);
      uint32_t yr[5][4];
      if (YPRE == 1) {
        mbar_wait(BAR(B_EPY), 0);
#pragma unroll
        for (int i = 0; i < 5; i++) ldsm4(ya + i * 32, yr[i]);
      }
      auto repeat = [&]() {
        wg_wait<0>();
#pragma unroll 1
        for (int i = 0, n = 0; i < 4 * 27 && n < 100000;) {
          if (!(i & 3)) {
            asm volatile("bar.sync 9, 256;" ::: "memory");
            if (threadIdx.x == 0) {
              mbar_expect(BAR(B_RT), 26624);
              tma3d(sb, &P.w2, 0, 64 * g2_block(i >> 2), 2 * dt, BAR(B_RT));
              tma2d(sb + G2_B, &P.h_ld, 64 * g2_block(i >> 2), 80 * tj, BAR(B_RT));
            }
            mbar_wait(BAR(B_RT), n++ & 1);
            uint32_t bad = 0;
            ep = lds32(sb + OFF_MISC);
#pragma unroll 1
            for (int q = 0; q < 6; q++) bad |= lds32(h_tag(sb, tj, q >> 1, lane) ^ (i >= 96 && (q & 1) ? 64 : 0)) ^ ep;
            if (__any_sync(0xffffffffu, bad & 1)) continue;
          }
          wg_fence();
          wgmma_ssp_80_10(acc, da0 + (i & 3) * (2048 >> 4), db0 + 2 * (i & 3), i);
          wg_commit();
          wg_wait<0>();
          i++;
        }
      };
      uint32_t vp = 0;
      if (!SPEC) {
        mbar_wait(BAR(B_VD), 0);
        TZ(threadIdx.x, 187);
        if (FB && mbar_test(BAR(B_BAD), 0)) repeat();
      }
    again:
      wg_wait<0>();
      TZ(tid, 50 + wg);
      mbar_wait(BAR(B_EPY), 0);
      if (!(PRE && SPEC) && tid == 0) mbar_arrive(BAR(B_DONE));
      TZ(tid, 52 + wg);
      if (YPRE == 2) {
#pragma unroll
        for (int i = 0; i < 5; i++) ldsm4(ya + i * 32, yr[i]);
      }
#pragma unroll
      for (int i = 0; i < 10; i += 2) {
        uint32_t ov[4];
        if (!YPRE) ldsm4(ya + i * 16, yr[i >> 1]);
        const uint32_t* const yq = yr[i >> 1];
#pragma unroll
        for (int j = 0; j < 2; j++) {
#pragma unroll
          for (int hf = 0; hf < 2; hf++) {
            const float bb2 = hf ? b21 : b20;
            const float z0 = fmaf(acc[4 * (i + j) + 2 * hf], __uint_as_float(rq[i + j].x), bb2), z1 = fmaf(acc[4 * (i + j) + 2 * hf + 1], __uint_as_float(rq[i + j].y), bb2);
            const uint32_t gt = pack2(fmaf(z0, tanh_fast(z0), z0), fmaf(z1, tanh_fast(z1), z1));
            ov[2 * j + hf] = hfma2(hmul2(xn[i >> 1][2 * j + hf], yq[2 * j + hf]), gt, xr[i >> 1][2 * j + hf]);
          }
        }
        if (SPEC && i == 4) {
          mbar_wait(BAR(B_VD), 0);
          TZ(threadIdx.x, 187);
          if (mbar_test(BAR(B_BAD), vp)) { repeat(); vp = 1; goto again; }
          if (tid == 0) mbar_arrive(BAR(B_DONE));
        }
        if (!OUTP && (i == 4 || i == 8)) { wfence(8); warp_arrive(BAR(B_HS + 4 * wg + (i == 8))); }
        stsm4t(xa + i * 1024, ov[0], ov[1], ov[2], ov[3]);
        if (OUTP && out_piece(i >> 1) != out_piece((i >> 1) + 1)) { wfence(8); warp_arrive(BAR(B_HS + 4 * wg + out_piece(i >> 1))); }
      }
      if (!OUTP) { wfence(8); warp_arrive(BAR(B_HS + 4 * wg + 2)); }
      TZ(tid, 6 + wg);
      DBG_END(tid);
    }
  } else {
    asm volatile("setmaxnreg.dec.sync.aligned.u32 %0;" ::"n"(R_P));
#define W(b) mbar_wait_b(BAR(b), 0);
#define KV(r) kv_issue(P, sb + OFF_KV + (r) * KV_SLOT, BAR(B_KV + (r)), r, g1);
#define PUBA rfence(1); kv_out(P, sb + OFF_KVS, 0, g1); kv_out(P, sb + OFF_KV + KV_SLOT + KV_V, 1, g1); bulk_commit(); bulk_wait_read(); \
  kv_issue(P, sb + OFF_KV + KV_SLOT, BAR(B_KV + 1), 3, g1); mbar_arrive(BAR(B_KVR)); bulk_wait_all(); pub_fence(1); flag_add_all(P.flags + FL_KV, NREP); TS(56);
#define PUBB mbar_wait_b(BAR(B_KVS + 1), 0); rfence(1); kv_out(P, sb + OFF_KVS, 2, g1); kv_out(P, sb + OFF_KV + KV_SLOT + KV_V, 3, g1); bulk_commit(); bulk_wait_read();
#define FLB bulk_wait_all(); pub_fence(1); flag_add_all(P.flags + FL_KV + 256, NREP); TS(57);
#define PUBC mbar_wait_b(BAR(B_KVS + 2), 0); rfence(1); kv_out(P, sb + (K4E ? OFF_KV4 : OFF_KV) + KV_V, 4, g1); bulk_commit(); bulk_wait_read();
#define PUBC0 mbar_wait_b(BAR(B_KVS + 2), 0); rfence(1); kv_out(P, sb + OFF_KV4 + KV_V, 4, g1); bulk_commit();
#define K4 kv_issue(P, sb + OFF_KV4, BAR(B_KV4), 4, g1);
#define KG mbar_expect(BAR(B_KVC), 4096); bulk_g2s(sb + OFF_G, P.tab + 2048, 4096, BAR(B_KVC));
#define FLC bulk_wait_all(); pub_fence(1); flag_add_all(P.flags + FL_KV + 512, NREP); TS(63);
#define KC mbar_expect(BAR(B_DFT), K4E ? 8192 : 12288); bulk_g2s(sb + OFF_DFT, P.tab, K4E ? 8192 : 12288, BAR(B_DFT));
#define F(c) conv_issue_f(P, conv_tile(sb, c), g1 + 128 * (c), BAR(B_CX + (c)));
#define G(i) if ((POLL & 2) && ((i) || (POLL & 16))) flag_poll<true>(P.flags + FL_KV + 256 * (i) + 32 * (mp.z & (NREP - 1)), ep * 128, sb + OFF_POLL + 48 * (warp - 12)); else flag_wait<true>(P.flags + FL_KV + 256 * (i) + 32 * (mp.z & (NREP - 1)), ep * 128); if (FNC & 1) fence_async_global(); TS((i) == 2 ? 28 : 23 + 6 * (i));
#define X(c) conv_issue_x(P, conv_tile(sb, c), g1 + 128 * (c), BAR(B_CX + (c)));
#define Y(c) mbar_wait_b(BAR(B_RD + (c)), 0); rfence(4); tma2d_st(&P.y_st, 0, 32 * (g1 + 128 * (c)), (c) ? conv_tile(sb, c) : sb + OFF_Y0); bulk_commit();
#define XE if (!RM) { mbar_expect(BAR(B_EP), 20480); tma2d(sb + OFF_XT, &P.x_ep, 128 * dt, 80 * tj, BAR(B_EP)); tma2d(sb + OFF_XT + XT_STEP, &P.x_ep, 128 * dt + 64, 80 * tj, BAR(B_EP)); }
#define R if (!RM) bulk_wait_read();
#define A(b) mbar_arrive(BAR(b));
#define PF(c) bulk_prefetch(P.ssm_k + (g1 + 128 * (c)) * S_, 4096);
#define PW bulk_prefetch(P.w2p + g1 * (F_ * D_ / 128), F_ * D_ / 64);
    if (warp >= 14) {
      if (has1) {
        auto b1_rows = [&]() {
          const int n0 = B1E ? 2 * lane + 64 * (warp & 1) : 0;
          if (B1E) {
            const int n1 = min(128 + n0, 222);
            const uint32_t b0 = ldg32(P.b1 + ext_col(n0, fs)), b1 = ldg32(P.b1 + ext_col(n1, fs));
            const uint32_t e0 = sb + OFF_EXT + ext_off(n0, 0), e1 = sb + OFF_EXT + ext_off(n1, 0);
#pragma unroll
            for (int k = 3; k < 8; k++) { sts32((e0 + 128 * k) ^ (k << 4), k < 5 ? b0 : 0u); sts32((e1 + 64 * k) ^ ((k >> 1) << 4), k < 5 ? b1 : 0u); }
          } else
        if (warp == 15) {
#pragma unroll 1
          for (int j = 0; j < 2; j++) {
            const int n0 = 2 * lane + 64 * j, n1 = min(128 + n0, 222);
            const uint32_t b0 = ldg32(P.b1 + ext_col(n0, fs)), b1 = ldg32(P.b1 + ext_col(n1, fs));
            const uint32_t e0 = sb + OFF_EXT + ext_off(n0, 0), e1 = sb + OFF_EXT + ext_off(n1, 0);
#pragma unroll
            for (int k = 3; k < 8; k++) { sts32((e0 + 128 * k) ^ (k << 4), k < 5 ? b0 : 0u); sts32((e1 + 64 * k) ^ ((k >> 1) << 4), k < 5 ? b1 : 0u); }
          }
        }
              };
        if (B1E) b1_rows();
        {
          float cs[8];
          const bool mc = MC == 3 && paired();
#pragma unroll
          for (int e = 0; e < 8; e++) cs[e] = 0.f;
          const int q = min(2 * rb, 26) + (lane & 1), kr = lane >> 1;
          const uint32_t stp = rb < 8 ? 2048 : 1024;
          const uint32_t a0 = sb + (warp & 1) * 2 * stp + (rb < 8 ? (q >> 3) * 8192 + kr * 128 + (((q & 7) ^ (kr & 7)) << 4)
                                                  : 16384 + ((q - 16) >> 2) * 4096 + kr * 64 + (((q & 3) ^ ((kr >> 1) & 3)) << 4));
#pragma unroll 1
          for (int kb = 0; kb < CS_KB; kb++) {
            const uint32_t a = a0 + (kb & 3) * G1_W;
            mbar_wait(BAR(B_FULL1 + (kb & 3)), kb >> 2);
            const uint4 u = lds128(a), w = lds128(a + stp);
            if (mc) { __syncwarp(); if (elect()) mbar_arrive_peer(BAR(B_PF + kb) + ((u.x | w.x) & P.zero)); }
            warp_arrive(BAR(B_EMPTY1 + (kb & 3)) + ((u.x | w.x) & P.zero));
            cs[0] += blo(u.x) + blo(w.x); cs[1] += bhi(u.x) + bhi(w.x); cs[2] += blo(u.y) + blo(w.y); cs[3] += bhi(u.y) + bhi(w.y);
            cs[4] += blo(u.z) + blo(w.z); cs[5] += bhi(u.z) + bhi(w.z); cs[6] += blo(u.w) + blo(w.w); cs[7] += bhi(u.w) + bhi(w.w);
          }
#pragma unroll
          for (int kb = CS_KB; kb < 6; kb++) { mbar_wait(BAR(B_EMPTY1 + (kb & 3)), 0); if (elect()) mbar_arrive(BAR(B_EMPTY1 + (kb & 3))); }
#pragma unroll
          for (int e = 0; e < 4; e++) {
            const bool up = lane & 4;
            const float o = __shfl_xor_sync(0xffffffffu, up ? cs[e] : cs[e + 4], 4);
            cs[e] = (up ? cs[e + 4] : cs[e]) + o;
          }
#pragma unroll
          for (int e = 0; e < 2; e++) {
            const bool up = lane & 2;
            const float o = __shfl_xor_sync(0xffffffffu, up ? cs[e] : cs[e + 2], 2);
            cs[e] = (up ? cs[e + 2] : cs[e]) + o;
            cs[e] += __shfl_xor_sync(0xffffffffu, cs[e], 8);
            cs[e] += __shfl_xor_sync(0xffffffffu, cs[e], 16);
          }
          const uint32_t xa = sb + OFF_ST2 + 8 * (lane & 7);
          if (warp == 15 && lane < 8) { sts32(xa, __float_as_uint(cs[0])); sts32(xa + 4, __float_as_uint(cs[1])); }
          asm volatile("bar.sync 8, 64;" ::: "memory");
          if (warp == 14) {
            const uint2 o = lds64(xa);
            mbar_wait(BAR(B_EPOCH), 0);
            if (lane < 8 && rb < 14 && (rb < 12 || fs < 6))
              tag_store(P.cs + (ext_col(16 * rb, fs) >> 1) + 4 * (lane & 1) + (lane >> 1), cs[0] + __uint_as_float(o.x), cs[1] + __uint_as_float(o.y), lds32(sb + OFF_MISC));
            TZ(lane, 18);
          }
        }
        if (!B1E) b1_rows();
      }
      mbar_wait(BAR(B_EPOCH), 0);
      const unsigned ep = lds32(sb + OFF_MISC);
      if (has1) {
        const int l2 = tid - 64, n0 = 2 * l2, n1 = min(128 + 2 * l2, 222), f0 = ext_col(n0, fs), f1 = ext_col(n1, fs);
        const uint32_t e0 = sb + OFF_EXT + ext_off(n0, 0), e1 = sb + OFF_EXT + ext_off(n1, 0);
        const uint2* const pc[4] = {P.cs + (f0 >> 1), P.cs + (f1 >> 1), P.cs + CSP + (f0 >> 1), P.cs + CSP + (f1 >> 1)};
        if (warp == 14) TZ(lane, 126);
        uint2 v[4] = {tag_load(pc[0]), tag_load(pc[1]), tag_load(pc[2]), tag_load(pc[3])};
        tag_wait<4>(pc, v, ep);
#pragma unroll
        for (int i = 0; i < 2; i++) {
          const float x = __uint_as_float(v[i].x) + __uint_as_float(v[i + 2].x), y = __uint_as_float(v[i].y) + __uint_as_float(v[i + 2].y);
          const uint32_t hi = pack2(x, y), lo = pack2(x - blo(hi), y - bhi(hi));
#pragma unroll
          for (int k = 0; k < 3; k++) sts32(i ? (e1 + 64 * k) ^ ((k >> 1) << 4) : (e0 + 128 * k) ^ (k << 4), k < 2 ? hi : lo);
        }
        TZ(lane, 25);
        fence_async_smem();
        warp_arrive(BAR(B_TAB));
      }
      if (PRE && has2 && warp == 14) {
        const int q1 = 32 + (lane & 7);
        const uint2 *const p0 = P.stats + min(80 * tj + 2 * lane, S_ - 2), *const p1 = P.stats + min(80 * tj + 2 * q1, S_ - 2);
        const uint2* const ps[4] = {p0, p0 + 1, p1, p1 + 1};
        uint2 sv[4] = {tag_load(ps[0]), tag_load(ps[1]), tag_load(ps[2]), tag_load(ps[3])};
        tag_wait<4>(ps, sv, ep);
#pragma unroll
        for (int j = 0; j < 2; j++) {
          const float r = __uint_as_float(sv[2 * j].y), r2 = __uint_as_float(sv[2 * j + 1].y);
          const uint32_t hi = pack2(r, r2), q = j ? q1 : lane;
          sts128(sb + OFF_ST2 + 16 * q, make_uint4(hi, pack2(-__uint_as_float(sv[2 * j].x), -__uint_as_float(sv[2 * j + 1].x)), __float_as_uint(0.25f * r), __float_as_uint(0.25f * r2)));
          sts32(sb + OFF_ST2 + 640 + 4 * q, pack2(r - blo(hi), r2 - bhi(hi)));
        }
        warp_arrive(BAR(PRE == 2 ? B_XF : B_EP));
      }
      __syncwarp();
      if (elect()) {
        if (warp == 15) {
          if (CHK == 3) for (int s = 0; s < G2_NST; s++) mbar_arrive(BAR(B_EMPTY2 + s));
          if (has1) {
            prefetch_map(&P.h_st); prefetch_map(&P.h_st2);
#pragma unroll
            for (int j = 0; j < 4; j++) {
              mbar_wait(BAR(B_HS + 4 * (j & 1) + (j & 2)), 0); rfence(2);
              if (j & 1) TS(33 + 4 * (j & 2));
              tma2d_st(&P.h_st, 192 * fs + 64 * (j & 2), 128 * rb + 64 * (j & 1), sb + OFF_X + (j & 2) * G1_X + (j & 1) * 8192);
              if (j == 1) {
                bulk_commit();
                bulk_wait_all();
                h_flag(P, rb, 0);
                mbar_arrive(BAR(B_EMPTY2 + 4 - RM));
                TS(26);
              }
            }
            if (fs < 6) {
#pragma unroll
              for (int w = 0; w < 2; w++) {
                mbar_wait(BAR(B_HS + 4 * w + 3), 0); rfence(2);
                tma2d_st(&P.h_st2, 1536 + 32 * fs, 128 * rb + 64 * w, sb + OFF_X + 3 * G1_X + w * 4096);
              }
            }
            bulk_commit();
            bulk_wait_all();
            mbar_arrive(BAR(B_EMPTY2 + 5 - RM));
            pub_fence(2);
            h_flag(P, rb, 64);
            TS(14);
          }
          if (has2) {
            h_wait(P, tj, 64, ep, sb + OFF_POLL + 144);
            mbar_arrive(BAR(B_HB));
            TS(17);
          }
        }
      }
      __syncwarp();
      if (warp == 15 && has2) {
        uint32_t ta[3], bad = 0;
#pragma unroll
        for (int q = 0; q < 3; q++) ta[q] = h_tag(sb, tj, q, lane);
        int s = 0, ph = 0;
#pragma unroll 1
        for (int kb = 0; kb < 27; kb++) {
          mbar_wait(BAR(B_FULL2 + s), ph);
          uint32_t t = 0;
#pragma unroll
          for (int q = 0; q < 3; q++) t |= lds32(ta[q] + g2_slot(s) * G2_STAGE) ^ ep;
          if (kb >= 24) {
#pragma unroll
            for (int q = 0; q < 3; q++) t |= lds32((ta[q] ^ 64) + g2_slot(s) * G2_STAGE) ^ ep;
          }
          bad |= t;
          if (CHK == 3 && lane == 0) mbar_arrive(BAR(B_EMPTY2 + s) + (t & P.zero));
          if (++s == G2_NST) { s = 0; ph ^= 1; }
        }
        bad = __any_sync(0xffffffffu, bad & 1);
        if (lane == 0) { if (!PRE) sts32(sb + OFF_MISC + 28, bad); else if (bad) mbar_arrive(BAR(B_BAD)); mbar_arrive(BAR(B_VD)); }
      }
      if (elect()) {
        if (W14ON && warp == 14 && has1) { prefetch_map(&P.kvz); prefetch_map(&P.f_ld); W14 }
        if (warp == 14 && has2) {
          prefetch_map(&P.h_ld);
          auto x_issue = [&]() {
            mbar_expect(BAR(B_EP), 20480);
            tma2d(sb + g2_slot(5) * G2_STAGE, &P.x_ep, 128 * dt, 80 * tj, BAR(B_EP));
            tma2d(sb + g2_slot(5) * G2_STAGE + 10240, &P.x_ep, 128 * dt + 64, 80 * tj, BAR(B_EP));
          };
          if (RM) { prefetch_map(&P.x_ep); mbar_wait(BAR(B_G1FREE), 0); }
          if (RM && XE_AT == 0) x_issue();
          if (RM && XE_AT == 3) { if (has1) mbar_wait(BAR(B_HS + 1), 0); x_issue(); }
          h_wait(P, tj, 0, ep, sb + OFF_POLL + 96);
          if (RM && XE_AT == 1) x_issue();
          TS(16);
#pragma unroll 1
          for (int k0 = 0; k0 < 9; k0++) {
#pragma unroll
            for (int u = 0; u < 3; u++) {
              const int kb = 3 * k0 + u, s = 3 * (k0 & 1) + u;
              if (RM && !GO5 && u == 2 && k0 == 1) mbar_wait(BAR(B_XF), 0);
              if (RM && GO5 ? u == 2 && k0 == 1 : u == 0 && k0 == 2) {
                if (POLL & 1) flag_poll<false>(P.flags + FL_G2 + 32 * mp.z, ep * mp.w * GO_N, sb + OFF_POLL + 96); else flag_wait<false>(P.flags + FL_G2 + 32 * mp.z, ep * mp.w * GO_N);
                mbar_arrive(BAR(B_GO));
                TS(20);
              }
              if (RM && XE_AT == 2 && u == 0 && k0 == 1) x_issue();
              if (RM && GO5 && u == 2 && k0 == 1) mbar_wait(BAR(B_XF), 0);
              if (u == 2 && k0 == 2) mbar_wait(BAR(B_H1), 0);
              if (u == 1 && k0 == 5) mbar_wait(BAR(B_HB), 0);
              mbar_wait(BAR(B_EMPTY2 + s), (k0 >> 1) & 1);
              TS(64 + 96 + kb);
              mbar_expect(BAR(B_FULL2 + s), 10240);
              tma2d(sb + (u < 2 ? (RM ? 4 : 3) * (k0 & 1) + u : 2 + (RM ? 1 : 3) * (k0 & 1)) * G2_STAGE + G2_B, &P.h_ld, 64 * g2_block(kb), 80 * tj, BAR(B_FULL2 + s));
              if (u == YK % 3 && k0 == YK / 3) mbar_arrive(BAR(B_LATE));
            }
          }
        }
        if (has2) {
          const int w = 15 - warp;
          prefetch_map(&P.out_st);
#pragma unroll
          for (int j = 0; j < 5; j++) {
            if (!j || out_piece(j) != out_piece(j - 1)) { mbar_wait(BAR(B_HS + 4 * w + out_piece(j)), has1 && (out_piece(j) < 3 || fs < 6)); rfence(8); }
            tma2d_st(&P.out_st, 128 * dt + 64 * w, 80 * tj + 16 * j, sb + OFF_XT + w * XT_STEP + j * 2048);
          }
          bulk_commit();
        }
        mbar_arrive(BAR(B_DONE));
        bulk_wait_read();
        TS(54 + 15 - warp);
        DBG_END(0);
      }
    } else if (warp == 13) {
      unsigned ep;
      asm volatile("ld.relaxed.gpu.global.u32 %0, [%1];" : "=r"(ep) : "l"(P.flags + FL_EPOCH) : "memory");
      if (has1 && lane < 5) sts32(sb + OFF_MISC + 4 + 4 * lane, __float_as_uint(ldg_bf16(P.ssm_D + g1 + 128 * lane)));
      ep += 1;
      __syncwarp();
      if (elect()) {
        sts32(sb + OFF_MISC, ep); sts32(sb + OFF_MISC + 24, 0);
        mbar_arrive(BAR(B_EPOCH));
        if (PFW && has1) bulk_prefetch(P.w1p + 256 * F_ + g1 * (PFW * F_ / 2), PFW * F_);
        flag_add_rlx(P.flags + FL_START, 1);
        if (!has1 && has2) flag_add_rlx(P.flags + FL_G2 + 32 * mp.z, GO_N);
        if (has1) {
          prefetch_map(&P.kvz); prefetch_map(&P.f_ld); prefetch_map(&P.y_st);
          AUX_SEQ
          bulk_wait_all(); pub_fence(4);
          flag_add_all(P.flags + FL_Y, NREPY);
          TS(12);
          if (g1 == 0) { flag_wait<true>(P.flags + FL_START, ep * NCTA); P.flags[FL_EPOCH] = ep; }
        }
        if (has2) {
          mbar_expect(BAR(B_EPY), 20480);
          prefetch_map(&P.y_ld);
          if (!RM && !has1) {
            if (PRE) mbar_wait_b(BAR(B_EMPTY2), 0);
            mbar_expect(BAR(B_EP), 20480);
            tma2d(sb + OFF_XT, &P.x_ep, 128 * dt, 80 * tj, BAR(B_EP));
            tma2d(sb + OFF_XT + XT_STEP, &P.x_ep, 128 * dt + 64, 80 * tj, BAR(B_EP));
          }
          flag_wait<true>(P.flags + FL_Y + 32 * (mp.z & (NREPY - 1)), ep * 128);
          fence_async_global();
          mbar_wait_b(BAR(B_LATE), 0);
          TS(13);
          tma2d(sb + OFF_YT, &P.y_ld, 80 * tj, 128 * dt, BAR(B_EPY));
        }
        mbar_wait_b(BAR(B_DONE), 0);
      }
    } else {
      const bool lead = elect();
      if (lead) {
        mbar_init(BAR(B_FULL1), 1);
        fence_async_smem();
        grid_wait<GRIDS>();
        if (has1) g1_issue(P, sb, 0, BAR(B_FULL1), 0, rb, fs);
        else if (!SP_D0 && !SP_FAKE) { mbar_expect(BAR(B_FULL1), CS_STAGE); tma3d(sb, &P.w1_cs, 0, 64 * CS_KB, 7 * (g1 - 128), BAR(B_FULL1)); }
#pragma unroll
        for (int b = 1; b < B_FIRST; b++) mbar_init(BAR(b), 1);
        fence_async_smem();
        if (MC == 2) asm volatile("fence.mbarrier_init.release.cluster;" ::: "memory");
      }
      __syncwarp();
      if (MC >= 2) asm volatile("barrier.cluster.arrive.relaxed.aligned;" ::: "memory");
      asm volatile("bar.arrive 0, 512;" ::: "memory");
      if (MC == 2 && (MC1 < 4 || MCW == 1)) asm volatile("barrier.cluster.wait.aligned;" ::: "memory");
      if (lead) {
        if (has1) {
#define S(kb) if (MC >= 2 && kb >= MC1) g1_issue_mc(P, sb, kb, BAR(B_FULL1 + (kb)), kb, rb, fs, true); else g1_issue(P, sb, kb, BAR(B_FULL1 + (kb)), kb, rb, fs);
#define K(r) kv_issue(P, sb + OFF_KV + (r) * KV_SLOT, BAR(B_KV + (r)), r, g1);
#define T mbar_expect(BAR(B_STAT), 20480); bulk_g2s(sb + OFF_SR, P.x + g1 * 16 * D_, 20480, BAR(B_STAT));
          grid_wait<GRID0>();
          INIT_SEQ
          TS(64 + 20 + 3);
        } else {
#pragma unroll
          for (int kb = SP_FAKE ? 3 : SP_D0 ? 0 : 1; kb < 3; kb++) { clk_wait(kb ? SP_D1 : SP_D0); mbar_expect(BAR(B_FULL1 + kb), CS_STAGE); tma3d(sb + kb * CS_STAGE, &P.w1_cs, 0, 64 * (CS_KB + kb), 7 * (g1 - 128), BAR(B_FULL1 + kb)); }
        }
      }
      __syncwarp();
      if (MC == 2 && MC1 == 4 && MCW == 2) asm volatile("barrier.cluster.wait.aligned;" ::: "memory");
      asm volatile("bar.sync 7, 512;" ::: "memory");
      if (MC == 2 && MC1 == 4 && MCW == 0) asm volatile("barrier.cluster.wait.aligned;" ::: "memory");
      bool mc = MC >= 2 && has1 && paired();
      if (MCV == 2) {
        if (lead) { mbar_expect(BAR(B_PF + 4), 4); st_peer(sb + OFF_POLL, g1, BAR(B_PF + 4)); }
        __syncwarp();
        mbar_wait(BAR(B_PF + 4), 0);
        const uint32_t pg = lds32(sb + OFF_POLL);
        mc = __all_sync(0xffffffffu, has1 && pg < 128 && (pg & 7) == fs);
      }
      if (lead) {
        if (has1) {
#pragma unroll 1
          for (int kb = G1_NST; kb < STE; kb++) {
            const int s = kb & 3;
            mbar_wait(BAR(B_EMPTY1 + s), ((kb >> 2) - 1) & 1);
            grid_wait<GRID1>();
            TS(64 + 20 + kb);
            if (mc && kb >= MC0) g1_issue_mc(P, sb, s, BAR(B_FULL1 + s), kb, rb, fs, false);
            else g1_issue(P, sb, s, BAR(B_FULL1 + s), kb, rb, fs);
          }
        }
      }
      __syncwarp();
      if (has1) {
        const uint2* const p0 = P.stats + 128 * rb + lane;
        const uint2* const ps[4] = {p0, p0 + 32, p0 + 64, p0 + 96};
        TZ(lane, 124);
        uint2 sv[4] = {tag_load(ps[0]), tag_load(ps[1]), tag_load(ps[2]), tag_load(ps[3])};
        if (lead) {
#pragma unroll
          for (int kb = STE; kb < 10; kb++) {
            const int s = kb & 3;
            mbar_wait(BAR(B_EMPTY1 + s), ((kb >> 2) - 1) & 1);
            TS(64 + 20 + kb);
            if (mc) g1_issue_mc(P, sb, s, BAR(B_FULL1 + s), kb, rb, fs, false);
            else g1_issue(P, sb, s, BAR(B_FULL1 + s), kb, rb, fs);
          }
        }
        __syncwarp();
        mbar_wait(BAR(B_EPOCH), 0);
        if (POLL & 8) tag_wait2<4>(ps, sv, lds32(sb + OFF_MISC)); else tag_wait<4>(ps, sv, lds32(sb + OFF_MISC));
#pragma unroll
        for (int j = 0; j < 4; j++) {
          const float mn = -__uint_as_float(sv[j].x), mh = bf_round(mn), sd = rcp_fast(__uint_as_float(sv[j].y)), sh = bf_round(sd);
          sts128(sb + OFF_ST1 + 16 * (lane + 32 * j), make_uint4(pack2(mh, mn - mh), pack2(mh, sh), pack2(sd - sh, 0.f), sv[j].y));
        }
        warp_arrive(BAR(B_TAB));
        TZ(lane, 11);
      }
      if (lead) {
        if (!has1) {
#pragma unroll
          for (int kb = SP_FAKE ? 10 : CS_KB + 3; kb < 10; kb++) {
            const int s = kb - CS_KB - 3;
            mbar_wait(BAR(B_EMPTY1 + s), 0);
            clk_wait(SP_D1);
            mbar_expect(BAR(B_FULL1 + s), CS_STAGE);
            tma3d(sb + s * CS_STAGE, &P.w1_cs, 0, 64 * kb, 7 * (g1 - 128), BAR(B_FULL1 + s));
          }
        }
        auto h_second = [&]() {
#pragma unroll
          for (int w = 0; w < 2; w++) {
            mbar_wait(BAR(B_HS + 4 * w + 1), 0); rfence(2);
            tma2d_st(&P.h_st, 192 * fs + 64, 128 * rb + 64 * w, sb + OFF_X + G1_X + w * 8192);
          }
          TS(37);
          bulk_commit();
          bulk_wait_all();
          mbar_arrive(BAR(B_EMPTY2 + 4 - RM)); mbar_arrive(BAR(B_EMPTY2 + 5 - RM));
          pub_fence(2);
          h_flag(P, rb, 32);
          TS(27);
        };
        if (has2) {
          prefetch_map(&P.w2);
#pragma unroll 1
          for (int k0 = 0; k0 < 9; k0++) {
#pragma unroll
            for (int u = 0; u < 3; u++) {
              const int kb = 3 * k0 + u, s = 3 * (k0 & 1) + u;
              if (u == 1 - RM && k0 == 1 && has1) h_second();
              if (RM && u == 2 && k0 == 1) mbar_wait(BAR(B_XF), 0);
              if (u == 0 && k0 == 2) { mbar_wait(BAR(B_EPOCH), 0); h_wait(P, tj, 32, lds32(sb + OFF_MISC), sb + OFF_POLL); mbar_arrive(BAR(B_H1)); TS(15); }
              mbar_wait(BAR(B_EMPTY2 + s), (k0 >> 1) & 1);
              mbar_expect(BAR(B_FULL2 + s), 16384);
              tma3d(sb + (u < 2 ? (RM ? 4 : 3) * (k0 & 1) + u : 2 + (RM ? 1 : 3) * (k0 & 1)) * G2_STAGE, &P.w2, 0, 64 * g2_block(kb), 2 * dt, BAR(B_FULL2 + s));
            }
          }
        }
        mbar_arrive(BAR(B_DONE));
      }
    }
  }

#undef BAR
}

typedef CUresult (*EncodeFn)(CUtensorMap*, CUtensorMapDataType, cuuint32_t, void*, const cuuint64_t*, const cuuint64_t*, const cuuint32_t*,
                             const cuuint32_t*, CUtensorMapInterleave, CUtensorMapSwizzle, CUtensorMapL2promotion, CUtensorMapFloatOOBfill);

static void enc(EncodeFn f, CUtensorMap* m, const void* base, int rank, const cuuint64_t* dims, const cuuint64_t* strides, const cuuint32_t* box, CUtensorMapSwizzle sw) {
  const cuuint32_t es[5] = {1, 1, 1, 1, 1};
  f(m, CU_TENSOR_MAP_DATA_TYPE_BFLOAT16, rank, const_cast<void*>(base), dims, strides, box, es, CU_TENSOR_MAP_INTERLEAVE_NONE, sw,
    CU_TENSOR_MAP_L2_PROMOTION_L2_128B, CU_TENSOR_MAP_FLOAT_OOB_FILL_NONE);
}
static void enc2(EncodeFn f, CUtensorMap* m, const void* base, uint64_t d0, uint64_t d1, uint32_t b0, uint32_t b1, CUtensorMapSwizzle sw) {
  const cuuint64_t dims[2] = {d0, d1}, strides[1] = {d0 * 2};
  const cuuint32_t box[2] = {b0, b1};
  enc(f, m, base, 2, dims, strides, box, sw);
}

extern "C" void kernel_launch(void* const* d_in, const int* in_sizes, int n_in, void* d_out, int out_size) {
  (void)in_sizes; (void)n_in; (void)out_size;
  static EncodeFn fn = nullptr;
  static void *p_h, *p_kvZ, *p_yT, *p_stats, *p_cs, *p_flags, *p_tab;
  if (!fn) {
    cudaDriverEntryPointQueryResult qr;
    void* f = nullptr;
    cudaGetDriverEntryPoint("cuTensorMapEncodeTiled", &f, cudaEnableDefault, &qr);
    fn = (EncodeFn)f;
    cudaFuncSetAttribute(h3_fused_kernel, cudaFuncAttributeMaxDynamicSharedMemorySize, SMEM_BYTES);
    cudaGetSymbolAddress(&p_h, g_h); cudaGetSymbolAddress(&p_kvZ, g_kvZ); cudaGetSymbolAddress(&p_yT, g_yT);
    cudaGetSymbolAddress(&p_stats, g_stats); cudaGetSymbolAddress(&p_cs, g_cs); cudaGetSymbolAddress(&p_flags, g_flags); cudaGetSymbolAddress(&p_tab, g_tab);
  }
  Params P;
  const bf16 *x = (const bf16*)d_in[0], *k = (const bf16*)d_in[1], *v = (const bf16*)d_in[2];
  const bf16 *w1 = (const bf16*)d_in[7], *w2 = (const bf16*)d_in[9];
  P.x = x; P.shift_k = (const bf16*)d_in[3]; P.ssm_k = (const bf16*)d_in[4]; P.ssm_D = (const bf16*)d_in[5];
  P.b1 = (const bf16*)d_in[8]; P.b2 = (const bf16*)d_in[10]; P.w2p = w2; P.w1p = w1;
  P.zero = 0; P.kvZ = (bf16*)p_kvZ; P.tab = (const uint32_t*)p_tab; P.stats = (uint2*)p_stats; P.cs = (uint2*)p_cs; P.flags = (unsigned*)p_flags;
  enc2(fn, &P.x_g1, x, D_, S_, 64, 128, CU_TENSOR_MAP_SWIZZLE_128B);
  {
    const cuuint64_t dims[3] = {64, D_, 27}, strides[2] = {F_ * 2, 128};
    const cuuint32_t box[3] = {64, 64, 2};
    enc(fn, &P.w1_a, w1, 3, dims, strides, box, CU_TENSOR_MAP_SWIZZLE_128B);
    const cuuint32_t box7[3] = {64, 64, 7};
    enc(fn, &P.w1_cs, w1, 3, dims, strides, box7, CU_TENSOR_MAP_SWIZZLE_128B);
    const cuuint64_t dims2[3] = {32, D_, 54}, strides2[2] = {F_ * 2, 64};
    const cuuint32_t box2[3] = {32, 64, 2}, box1[3] = {32, 64, 1};
    enc(fn, &P.w1_b2, w1, 3, dims2, strides2, box2, CU_TENSOR_MAP_SWIZZLE_64B);
    enc(fn, &P.w1_b1, w1, 3, dims2, strides2, box1, CU_TENSOR_MAP_SWIZZLE_64B);
  }
  enc2(fn, &P.h_ld, p_h, F_, S_, 64, 80, CU_TENSOR_MAP_SWIZZLE_128B);
  {
    const cuuint64_t dims[3] = {64, F_, 10}, strides[2] = {D_ * 2, 128};
    const cuuint32_t box[3] = {64, 64, 2};
    enc(fn, &P.w2, w2, 3, dims, strides, box, CU_TENSOR_MAP_SWIZZLE_128B);
  }
  enc2(fn, &P.h_st, p_h, F_, S_, 64, 64, CU_TENSOR_MAP_SWIZZLE_128B);
  enc2(fn, &P.h_st2, p_h, F_, S_, 32, 64, CU_TENSOR_MAP_SWIZZLE_64B);
  enc2(fn, &P.k, k, D_, S_, 128, 19, CU_TENSOR_MAP_SWIZZLE_NONE);
  enc2(fn, &P.v, v, D_, S_, 128, 16, CU_TENSOR_MAP_SWIZZLE_NONE);
  {
    const cuuint64_t dims[3] = {D_ * 16, 32, 4}, strides[2] = {D_ * 128, D_ * 32};
    const cuuint32_t box[3] = {16, 32, 4};
    enc(fn, &P.kvz, p_kvZ, 3, dims, strides, box, CU_TENSOR_MAP_SWIZZLE_32B);
  }
  enc2(fn, &P.f_ld, P.ssm_k, 64, D_ * 32, 64, 32, CU_TENSOR_MAP_SWIZZLE_128B);
  enc2(fn, &P.y_st, p_yT, 64, D_ * 32, 64, 32, CU_TENSOR_MAP_SWIZZLE_128B);
  enc2(fn, &P.y_ld, p_yT, S_, D_, 80, 128, CU_TENSOR_MAP_SWIZZLE_NONE);
  enc2(fn, &P.x_ep, x, D_, S_, 64, 80, CU_TENSOR_MAP_SWIZZLE_128B);
  enc2(fn, &P.out_st, d_out, D_, S_, 64, 16, CU_TENSOR_MAP_SWIZZLE_128B);
  for (int b = 0; b < 72; b++) P.cnt[b] = 1;
  P.cnt[B_XF] = PRE == 2 ? 1 : 8;
  for (int b = 0; b < 5; b++) { P.cnt[B_CX + b] = 2; P.cnt[B_RD + b] = 4; }
  for (int b = 0; b < 4; b++) P.cnt[B_EMPTY1 + b] = 4;
  if (MC == 3) for (int b = 0; b < 6; b++) P.cnt[B_PF + b] = b < CS_KB ? 4 : 2;
  for (int b = 0; b < 2 * G2_NST; b++) P.cnt[B_FULL2 + b] = CHK == 3 && b >= G2_NST ? 3 : 2;
  P.cnt[B_DBG] = 4;
  P.cnt[B_G1FREE] = P.cnt[B_GO] = 2; P.cnt[B_TAB] = 3; P.cnt[B_EP] = PRE == 2 ? 1 : PRE ? 2 : 5; P.cnt[B_DONE] = 6;
  for (int b = 0; b < 8; b++) P.cnt[B_HS + b] = 4;
  P.cnt[B_KVS] = P.cnt[B_KVS + 1] = P.cnt[B_STATFREE] = 4; P.cnt[B_KVS + 2] = K4E ? 4 : 2;
  {
    const char *g1s = G1MAP, *g2s = G2MAP, *gos = GOMAP;
    int mem[10][18], cnt[10] = {0}, used[10] = {0}, gn[9] = {0};
    for (int b = 0; b < NCTA; b++) {
      const int tpc = b >> 1;
      const int gp = tpc < 32 ? tpc % 8 : tpc < 60 ? 1 + (tpc - 32) % 7 : tpc < 62 ? tpc - 54 : tpc == 63 ? 8 : tpc == 64 ? 9 : 0;
      mem[gp][cnt[gp]++] = b;
      P.map[b] = make_uchar4(255, 255, gos[gp] - '0', 0);
    }
    auto tile = [&](int gp, int i) { const int q = g1s[gp] - '0'; return (4 * (q >> 1) + (i & 3)) * 8 + 4 * (q & 1) + (i >> 2); };
    for (int gp = 0; gp < 8; gp++)
      for (int i = 0; i < (gp ? 16 : 8); i++) P.map[mem[gp][i]].x = tile(gp, i);
    for (int i = 0; i < 4; i++) {
      P.map[mem[8 + (i >> 1)][i & 1]].x = tile(0, 8 + i);
      P.map[mem[0][8 + i]].x = tile(0, 12 + i);
      P.map[mem[6 + (i >> 1)][16 + (i & 1)]].x = 128 + i;
    }
    for (int n = 0; *g2s; g2s++) {
      if (*g2s == ' ') continue;
      const int gp = *g2s < 'a' ? *g2s - 'A' : *g2s - 's' + 8;
      P.map[mem[gp][used[gp]++]].y = n / 5 * 8 + n % 5;
      gn[gos[gp] - '0']++;
      n++;
    }
    for (int b = 0; b < NCTA; b++) P.map[b].w = gn[P.map[b].z];
  }
  h3_fused_kernel<<<NCTA, 512, SMEM_BYTES, cudaStreamPerThread>>>(P);
}
```
